```python
import torch

def _softmax(x, axis=-1):
    return torch.softmax(x, dim=axis)

def _gelu(x):
    return torch.nn.functional.gelu(x, approximate='tanh')

def _silu(x):
    return torch.nn.functional.silu(x)

def _sigmoid(x):
    return torch.sigmoid(x)

def _layernorm(x, axis=-1, eps=1e-05):
    m = x.mean(dim=axis, keepdim=True)
    v = x.var(dim=axis, keepdim=True, unbiased=False)
    return (x - m) / torch.sqrt(v + eps)

def _scatter_add(tgt, idx, src, axis=0):
    return tgt.clone().index_add_(axis, idx, src)

def _segment_sum(src, seg, n):
    out = torch.zeros((n,) + src.shape[1:], dtype=src.dtype)
    return out.index_add_(0, seg, src)

def _pad(x, pw):
    flat = tuple((v for pair in reversed(pw) for v in pair))
    return torch.nn.functional.pad(x, flat)
kernel_name = 'standalone__swin_window_attn__vision'

def setup_inputs():

    _w = lambda a: (lambda t: t.to(torch.bfloat16) if t.is_floating_point() else t)(torch.as_tensor(a))
    H = W = 512 // 8 * 8
    C, win = (192, 8)
    return {'x': _w((lambda *s: torch.randn(*s, dtype=torch.bfloat16) * 0.2)(1, H, W, C)), 'wqkv': _w((lambda *s: torch.randn(*s, dtype=torch.bfloat16) * 0.2)(C, 3 * C)), 'wo': _w((lambda *s: torch.randn(*s, dtype=torch.bfloat16) * 0.05)(C, C))}

def reference(x, wqkv, wo):
    B, H, W, C = x.shape
    win = 8
    nh, nw = (H // win, W // win)
    xw = (lambda x, *d: x.permute(*d))(x.reshape(B, nh, win, nw, win, C), 0, 1, 3, 2, 4, 5)
    xw = xw.reshape(B * nh * nw, win * win, C)
    qkv = xw @ wqkv
    q, k, v = (qkv[..., :C].clone(), qkv[..., C:2 * C].clone(), qkv[..., 2 * C:].clone())
    scale = C ** (-0.5)
    p = _softmax(torch.einsum('bqc,bkc->bqk', q, k) * scale, axis=-1)
    o = torch.einsum('bqk,bkc->bqc', p, v) @ wo
    o = (lambda x, *d: x.permute(*d))(o.reshape(B, nh, nw, win, win, C), 0, 1, 3, 2, 4, 5)
    return o.reshape(B, H, W, C)
```

```cpp
#include <cuda_runtime.h>
#include <cuda_bf16.h>
#include <cuda.h>
#include <stdint.h>

namespace {

constexpr int kC      = 192;
constexpr int kHW     = 512;
#define MAXWIN 4096
constexpr int kNWin   = MAXWIN;
constexpr int kXBytes = 64 * kC * 2;
constexpr int kWBytes = kC * kC * 2;
constexpr int kNWG    = 3;
constexpr int kThreads = kNWG * 128;
constexpr int kTiles  = 144;
#define TRK_STEP 850
#define TRK_START 1200
#define TRK_FIRST 2
#define EF_LOAD 0
#define EF_STORE 0
#define PF_INIT 1
#define PF_LEAD 400
#define PF_UP 128
#define PF_DOWN 36
#define PF_MIN 150

constexpr int kOffWm  = 0;
constexpr int kOffWv  = kWBytes;
constexpr int kOffX   = 2 * kWBytes;
constexpr int kOffBar = kOffX + kNWG * kXBytes;
constexpr int kOffStash = kOffBar + 128;
constexpr int kOffProf = kOffStash + kThreads * 16;
constexpr int kSmemBytes = kOffProf;
constexpr uint32_t kSmemBase = 1024;

__device__ uint4 g_wfold[2 * kWBytes / 16];
__device__ __align__(128) uint32_t g_ticket[32];
__device__ __align__(128) uint32_t g_cnt[2 * 32];

#define PROF(slot)
#define PROFG(slot)
#define PROFT(t, slot)
#define PROF_FLUSH()
#define TRACE(n)
__device__ __forceinline__ uint32_t smem_u32(const void* p) { return (uint32_t)__cvta_generic_to_shared(p); }

__device__ __forceinline__ void mbar_init(uint32_t bar, uint32_t count) {
    asm volatile("mbarrier.init.shared::cta.b64 [%0], %1;" ::"r"(bar), "r"(count) : "memory");
}
__device__ __forceinline__ void mbar_expect_tx(uint32_t bar, uint32_t bytes) {
    asm volatile("mbarrier.arrive.expect_tx.shared::cta.b64 _, [%0], %1;" ::"r"(bar), "r"(bytes) : "memory");
}
__device__ __forceinline__ void mbar_wait(uint32_t bar, uint32_t parity) {
    uint32_t ok;
    uint32_t spins = 0;
    do {
        asm volatile("{\n.reg .pred p;\n"
                     "mbarrier.try_wait.parity.shared::cta.b64 p, [%1], %2;\n"
                     "selp.b32 %0, 1, 0, p;\n}\n"
                     : "=r"(ok) : "r"(bar), "r"(parity) : "memory");
        if (++spins > (1u << 26)) __trap();
    } while (!ok);
}
__device__ __forceinline__ uint32_t tid_now() {
    uint32_t t;
    asm volatile("mov.u32 %0, %%tid.x;" : "=r"(t));
    return t;
}
__device__ __forceinline__ bool elect_one() {
    uint32_t pred;
    asm volatile("{\n.reg .pred p;\nelect.sync _|p, 0xffffffff;\nselp.b32 %0, 1, 0, p;\n}\n" : "=r"(pred));
    return pred != 0;
}
#define RING 1
#define PASS1 11
#define PASS2 5
#define PASS3 3
#define WMASK 4095
__device__ __forceinline__ void ring_wait() {
    asm volatile("bar.sync %0, 256;" ::"r"((tid_now() >> 7) + 8) : "memory");
}
__device__ __forceinline__ void ring_pass() {
    const uint32_t w = tid_now() >> 7;
    asm volatile("bar.arrive %0, 256;" ::"r"(w == kNWG - 1 ? 8u : w + 9u) : "memory");
}
__device__ __forceinline__ uint32_t wg_uniform() { return __reduce_or_sync(0xffffffffu, tid_now() >> 7); }
__device__ __forceinline__ uint64_t policy_evict_first() {
    uint64_t p;
    asm("createpolicy.fractional.L2::evict_first.b64 %0, 1.0;" : "=l"(p));
    return p;
}
__device__ __forceinline__ uint64_t policy_unchanged() {
    uint64_t p;
    asm("createpolicy.fractional.L2::evict_unchanged.b64 %0, 1.0;" : "=l"(p));
    return p;
}
__device__ __forceinline__ uint64_t policy_normal() {
    uint64_t p;
    asm("createpolicy.fractional.L2::evict_normal.b64 %0, 1.0;" : "=l"(p));
    return p;
}
#define EF_LO 0
#define EF_HI 4096
__device__ __forceinline__ void tma_load_x(uint32_t dst, const CUtensorMap* tm, uint32_t bar, int win) {
    const int wh = win >> 6, ww = win & 63;
    asm volatile("cp.async.bulk.tensor.4d.shared::cluster.global.mbarrier::complete_tx::bytes"
                 " [%0], [%1, {%3, %4, %5, %6}], [%2];"
                 ::"r"(dst), "l"(tm), "r"(bar), "r"(0), "r"(ww * 8), "r"(wh * 8), "r"(0) : "memory");
}
__device__ __forceinline__ void tma_load_x_chunk(uint32_t dst, const CUtensorMap* tm, uint32_t bar, int win, int chunk) {
    const int wh = win >> 6, ww = win & 63;
    asm volatile("cp.async.bulk.tensor.4d.shared::cluster.global.mbarrier::complete_tx::bytes"
                 " [%0], [%1, {%3, %4, %5, %6}], [%2];"
                 ::"r"(dst), "l"(tm), "r"(bar), "r"(0), "r"(ww * 8), "r"(wh * 8), "r"(chunk) : "memory");
}
__device__ __forceinline__ void bulk_load(uint32_t dst, const void* src, uint32_t bytes, uint32_t bar) {
    asm volatile("cp.async.bulk.shared::cluster.global.mbarrier::complete_tx::bytes [%0], [%1], %2, [%3];"
                 ::"r"(dst), "l"(src), "r"(bytes), "r"(bar) : "memory");
}

__device__ __forceinline__ void stg128(void* p, uint4 v) {
    asm volatile("st.global.v4.b32 [%0], {%1, %2, %3, %4};" ::"l"(p), "r"(v.x), "r"(v.y), "r"(v.z), "r"(v.w) : "memory");
}
__device__ __forceinline__ void wg_fence()  { asm volatile("wgmma.fence.sync.aligned;" ::: "memory"); }
__device__ __forceinline__ void wg_commit() { asm volatile("wgmma.commit_group.sync.aligned;" ::: "memory"); }
__device__ __forceinline__ void wg_wait0()  { asm volatile("wgmma.wait_group.sync.aligned 0;" ::: "memory"); }
__device__ __forceinline__ void wg_wait1()  { asm volatile("wgmma.wait_group.sync.aligned 1;" ::: "memory"); }

template <int N> __device__ __forceinline__ void fence_regs(float (&d)[N]) {
#pragma unroll
    for (int i = 0; i < N; i++) asm volatile("" : "+f"(d[i])::"memory");
}
template <int N> __device__ __forceinline__ void fence_regs(uint32_t (&d)[N]) {
#pragma unroll
    for (int i = 0; i < N; i++) asm volatile("" : "+r"(d[i])::"memory");
}

#define ACC8(c, d, i) c(d[i]), c(d[i + 1]), c(d[i + 2]), c(d[i + 3]), c(d[i + 4]), c(d[i + 5]), c(d[i + 6]), c(d[i + 7])
#define ACC32(c, d) ACC8(c, d, 0), ACC8(c, d, 8), ACC8(c, d, 16), ACC8(c, d, 24)
#define ACC96(c, d) ACC32(c, d), ACC8(c, d, 32), ACC8(c, d, 40), ACC8(c, d, 48), ACC8(c, d, 56), \
                    ACC8(c, d, 64), ACC8(c, d, 72), ACC8(c, d, 80), ACC8(c, d, 88)
#define C_IO(x) "+f"(x)
#define C_O(x) "=f"(x)
#define REGS32 "{%0, %1, %2, %3, %4, %5, %6, %7, %8, %9, %10, %11, %12, %13, %14, %15, " \
               "%16, %17, %18, %19, %20, %21, %22, %23, %24, %25, %26, %27, %28, %29, %30, %31}"
#define REGS96 "{%0, %1, %2, %3, %4, %5, %6, %7, %8, %9, %10, %11, %12, %13, %14, %15, " \
               "%16, %17, %18, %19, %20, %21, %22, %23, %24, %25, %26, %27, %28, %29, %30, %31, " \
               "%32, %33, %34, %35, %36, %37, %38, %39, %40, %41, %42, %43, %44, %45, %46, %47, " \
               "%48, %49, %50, %51, %52, %53, %54, %55, %56, %57, %58, %59, %60, %61, %62, %63, " \
               "%64, %65, %66, %67, %68, %69, %70, %71, %72, %73, %74, %75, %76, %77, %78, %79, " \
               "%80, %81, %82, %83, %84, %85, %86, %87, %88, %89, %90, %91, %92, %93, %94, %95}"

#define DESC_HI "0x40000040"
#define MK_DESC(name, lo, off) "add.u32 t, " lo ", " off ";\nmov.b64 " name ", {t, " DESC_HI "};\n"

template <bool First, int OA, int OB> __device__ __forceinline__ void wg192_ss(float (&d)[96], uint32_t la, uint32_t lb) {
    if constexpr (First)
        asm volatile("{\n.reg .pred p;\n.reg .b32 t;\n.reg .b64 da, db;\nsetp.ne.b32 p, 0, 0;\n"
                     MK_DESC("da", "%96", "%98") MK_DESC("db", "%97", "%99")
                     "wgmma.mma_async.sync.aligned.m64n192k16.f32.bf16.bf16 " REGS96 ", da, db, p, 1, 1, 0, 0;\n}\n"
                     : ACC96(C_O, d) : "r"(la), "r"(lb), "n"(OA), "n"(OB));
    else
        asm volatile("{\n.reg .pred p;\n.reg .b32 t;\n.reg .b64 da, db;\nsetp.ne.b32 p, 1, 0;\n"
                     MK_DESC("da", "%96", "%98") MK_DESC("db", "%97", "%99")
                     "wgmma.mma_async.sync.aligned.m64n192k16.f32.bf16.bf16 " REGS96 ", da, db, p, 1, 1, 0, 0;\n}\n"
                     : ACC96(C_IO, d) : "r"(la), "r"(lb), "n"(OA), "n"(OB));
}
template <bool First, int TB, int OB> __device__ __forceinline__ void wg192_rs(float (&d)[96], const uint32_t* a, uint32_t lb) {
    if constexpr (First)
        asm volatile("{\n.reg .pred p;\n.reg .b32 t;\n.reg .b64 db;\nsetp.ne.b32 p, 0, 0;\n"
                     MK_DESC("db", "%100", "%102")
                     "wgmma.mma_async.sync.aligned.m64n192k16.f32.bf16.bf16 " REGS96 ", {%96, %97, %98, %99}, db, p, 1, 1, %101;\n}\n"
                     : ACC96(C_O, d) : "r"(a[0]), "r"(a[1]), "r"(a[2]), "r"(a[3]), "r"(lb), "n"(TB), "n"(OB));
    else
        asm volatile("{\n.reg .pred p;\n.reg .b32 t;\n.reg .b64 db;\nsetp.ne.b32 p, 1, 0;\n"
                     MK_DESC("db", "%100", "%102")
                     "wgmma.mma_async.sync.aligned.m64n192k16.f32.bf16.bf16 " REGS96 ", {%96, %97, %98, %99}, db, p, 1, 1, %101;\n}\n"
                     : ACC96(C_IO, d) : "r"(a[0]), "r"(a[1]), "r"(a[2]), "r"(a[3]), "r"(lb), "n"(TB), "n"(OB));
}
template <bool First, int OB> __device__ __forceinline__ void wg64_rs(float (&d)[32], const uint32_t* a, uint32_t lb) {
    if constexpr (First)
        asm volatile("{\n.reg .pred p;\n.reg .b32 t;\n.reg .b64 db;\nsetp.ne.b32 p, 0, 0;\n"
                     MK_DESC("db", "%36", "%37")
                     "wgmma.mma_async.sync.aligned.m64n64k16.f32.bf16.bf16 " REGS32 ", {%32, %33, %34, %35}, db, p, 1, 1, 0;\n}\n"
                     : ACC32(C_O, d) : "r"(a[0]), "r"(a[1]), "r"(a[2]), "r"(a[3]), "r"(lb), "n"(OB));
    else
        asm volatile("{\n.reg .pred p;\n.reg .b32 t;\n.reg .b64 db;\nsetp.ne.b32 p, 1, 0;\n"
                     MK_DESC("db", "%36", "%37")
                     "wgmma.mma_async.sync.aligned.m64n64k16.f32.bf16.bf16 " REGS32 ", {%32, %33, %34, %35}, db, p, 1, 1, 0;\n}\n"
                     : ACC32(C_IO, d) : "r"(a[0]), "r"(a[1]), "r"(a[2]), "r"(a[3]), "r"(lb), "n"(OB));
}
__host__ __device__ constexpr int koff(int kk, int chunk) { return ((kk >> 2) * chunk + (kk & 3) * 32) >> 4; }

#define ST_SLOTS 0x2000000000001ull
__host__ __device__ constexpr int slot_begin(int i) {
    int b = 0;
    for (int k = -1; k < i; k++) b += (int)((ST_SLOTS >> (4 * (11 - k))) & 15);
    return b;
}
#define PACE_DT 160
#define PACE_MODE 0
template <int J, int E> __device__ __forceinline__ void store_range(const uint4 (&h)[12], uint8_t* hptr) {
    if constexpr (J < E) {
        constexpr int r = J / 6, a = J % 6;
        stg128(hptr + r * (kHW * kC * 2) + a * 64, h[2 * a + r]);
        store_range<J + 1, E>(h, hptr);
    }
}
template <int I> __device__ __forceinline__ void store_slot(const uint4 (&h)[12], uint8_t* hptr) {
    store_range<slot_begin(I), slot_begin(I + 1)>(h, hptr);
}
__device__ __forceinline__ uint32_t clock_now() {
    uint32_t t;
    asm volatile("mov.u32 %0, %%clock;" : "=r"(t));
    return t;
}
template <int J> __device__ __forceinline__ void store_paced(const uint4 (&h)[12], uint8_t* hptr, uint32_t t0) {
    if constexpr (J < 12) {
        while (clock_now() - t0 < (uint32_t)((J - slot_begin(12) + 1) * PACE_DT)) {}
        store_range<J, J + 1>(h, hptr);
        store_paced<J + 1>(h, hptr, t0);
    }
}
template <int K> struct Gemm1St {
    static __device__ __forceinline__ void run(float (&d)[96], uint32_t lx, uint32_t lw, const uint4 (&h)[12], uint8_t* hptr) {
        if constexpr (K > 0) Gemm1St<K - 1>::run(d, lx, lw, h, hptr);
        wg192_ss<K == 0, koff(K, 8192), koff(K, 24576)>(d, lx, lw);
        if constexpr (K == 11) wg_commit();
        if constexpr (K == PASS1) ring_pass();
        if constexpr (slot_begin(K + 1) > slot_begin(K)) {
            __syncwarp();
            store_slot<K>(h, hptr);
            __syncwarp();
        }
    }
};
template <int K0, int K> struct Gemm1 {
    static __device__ __forceinline__ void run(float (&d)[96], uint32_t lx, uint32_t lw) {
        if constexpr (K > K0) Gemm1<K0, K - 1>::run(d, lx, lw);
        wg192_ss<K == 0, koff(K, 8192), koff(K, 24576)>(d, lx, lw);
    }
};
__device__ __forceinline__ uint32_t draw_ticket() {
    uint32_t ticket = 0;
    asm volatile("{\n.reg .pred p;\nsetp.eq.u32 p, %2, 0;\n@p atom.relaxed.gpu.global.inc.u32 %0, [%1], %3;\n}\n"
                 : "+r"(ticket) : "l"(g_ticket), "r"(tid_now() & 127), "n"(kNWin - 1) : "memory");
    return ticket;
}
#define DRAW_AT 1
template <int KK> struct Gemm2 { static __device__ __forceinline__ void run(float (&d)[32], const uint32_t* a, uint32_t lx) {
    Gemm2<KK - 1>::run(d, a, lx); wg64_rs<KK == 0, koff(KK, 8192)>(d, a + 4 * KK, lx);
    if constexpr (KK == PASS2 && KK < 11) ring_pass(); } };
template <> struct Gemm2<-1> { static __device__ __forceinline__ void run(float (&)[32], const uint32_t*, uint32_t) {} };
template <int KK> struct Gemm3 { static __device__ __forceinline__ void run(float (&d)[96], const uint32_t* a, uint32_t lxt) {
    Gemm3<KK - 1>::run(d, a, lxt); wg192_rs<KK == 0, 1, KK * (2048 >> 4)>(d, a + 4 * KK, lxt);
    if constexpr (KK == PASS3 && KK < 3) ring_pass(); } };
template <> struct Gemm3<-1> { static __device__ __forceinline__ void run(float (&)[96], const uint32_t*, uint32_t) {} };
template <int K0, int KK> struct Gemm4 { static __device__ __forceinline__ void run(float (&d)[96], const uint32_t* a, uint32_t lw) {
    if constexpr (KK > K0) Gemm4<K0, KK - 1>::run(d, a, lw);
    wg192_rs<KK == 0, 0, koff(KK, 24576)>(d, a + 4 * KK, lw); } };

__device__ __forceinline__ uint32_t pack_bf16(float lo, float hi) {
    uint32_t r;
    asm("cvt.rn.bf16x2.f32 %0, %1, %2;" : "=r"(r) : "f"(hi), "f"(lo));
    return r;
}
__device__ __forceinline__ float ex2(float x) {
    float r;
    asm("ex2.approx.ftz.f32 %0, %1;" : "=f"(r) : "f"(x));
    return r;
}
__device__ __forceinline__ float rcp(float x) {
    float r;
    asm("rcp.approx.ftz.f32 %0, %1;" : "=f"(r) : "f"(x));
    return r;
}
__device__ __forceinline__ void mma16816(float (&c)[4], uint32_t a0, uint32_t a1, uint32_t a2, uint32_t a3,
                                         uint32_t b0, uint32_t b1) {
    asm volatile("mma.sync.aligned.m16n8k16.row.col.f32.bf16.bf16.f32 {%0,%1,%2,%3}, {%4,%5,%6,%7}, {%8,%9}, {%0,%1,%2,%3};"
                 : "+f"(c[0]), "+f"(c[1]), "+f"(c[2]), "+f"(c[3])
                 : "r"(a0), "r"(a1), "r"(a2), "r"(a3), "r"(b0), "r"(b1));
}

struct FoldRegs { uint4 B0[6], B1[6]; uint32_t A[48]; };

__device__ __forceinline__ void fold_store(char* img, int n_lo, int n_hi, int k0, int q, const float (&c0)[4], const float (&c1)[4]) {
    const int u = ((k0 & 63) >> 3) + (q >> 1);
    const int base = (k0 >> 6) * 24576 + (q & 1) * 8;
    *reinterpret_cast<uint2*>(img + base + n_lo * 128 + ((u ^ (n_lo & 7)) << 4)) = make_uint2(pack_bf16(c0[0], c0[1]), pack_bf16(c1[0], c1[1]));
    *reinterpret_cast<uint2*>(img + base + n_hi * 128 + ((u ^ (n_hi & 7)) << 4)) = make_uint2(pack_bf16(c0[2], c0[3]), pack_bf16(c1[2], c1[3]));
}
__device__ __forceinline__ void fold_load_qk(FoldRegs& r, const __nv_bfloat16* __restrict__ wqkv, int tile, int lane) {
    const int g = lane >> 2, q = lane & 3;
    const int n0 = (tile / 12) * 16, k0 = (tile % 12) * 16;
    const int kb = k0 + 4 * (g >> 1) + (g & 1);
    const uint4* pa0 = reinterpret_cast<const uint4*>(wqkv + (size_t)(n0 + g) * 576 + 192 + 8 * q);
    const uint4* pa1 = reinterpret_cast<const uint4*>(wqkv + (size_t)(n0 + g + 8) * 576 + 192 + 8 * q);
    const uint4* pb0 = reinterpret_cast<const uint4*>(wqkv + (size_t)kb * 576 + 8 * q);
    const uint4* pb1 = reinterpret_cast<const uint4*>(wqkv + (size_t)(kb + 2) * 576 + 8 * q);
#pragma unroll
    for (int j = 0; j < 6; j++) {
        const uint4 lo = __ldg(pa0 + 4 * j), hi = __ldg(pa1 + 4 * j);
        r.A[8 * j + 0] = lo.x; r.A[8 * j + 1] = hi.x; r.A[8 * j + 2] = lo.y; r.A[8 * j + 3] = hi.y;
        r.A[8 * j + 4] = lo.z; r.A[8 * j + 5] = hi.z; r.A[8 * j + 6] = lo.w; r.A[8 * j + 7] = hi.w;
        r.B0[j] = __ldg(pb0 + 4 * j);
        r.B1[j] = __ldg(pb1 + 4 * j);
    }
}
__device__ __forceinline__ void fold_load_vo(FoldRegs& r, const __nv_bfloat16* __restrict__ wqkv, const __nv_bfloat16* __restrict__ wo,
                                             int tile, int lane) {
    const int g = lane >> 2, q = lane & 3;
    const int ch0 = (tile / 12) * 16 + 2 * g;
    const int k0 = (tile % 12) * 16;
    const int kb = k0 + 4 * (g >> 1) + (g & 1);
    const uint4* pb0 = reinterpret_cast<const uint4*>(wqkv + (size_t)kb * 576 + 384 + 8 * q);
    const uint4* pb1 = reinterpret_cast<const uint4*>(wqkv + (size_t)(kb + 2) * 576 + 384 + 8 * q);
    const uint32_t* pw = reinterpret_cast<const uint32_t*>(wo + (size_t)(8 * q) * kC + ch0);
#pragma unroll
    for (int j = 0; j < 6; j++) {
        r.B0[j] = __ldg(pb0 + 4 * j);
        r.B1[j] = __ldg(pb1 + 4 * j);
#pragma unroll
        for (int i = 0; i < 8; i++) r.A[8 * j + i] = __ldg(pw + (32 * j + i) * (kC / 2));
    }
}
template <bool kVO>
__device__ __forceinline__ void fold_compute_store(FoldRegs& r, int tile, int lane) {
    const int g = lane >> 2, q = lane & 3;
    float c0[4] = {0.f, 0.f, 0.f, 0.f}, c1[4] = {0.f, 0.f, 0.f, 0.f}, c2[4] = {0.f, 0.f, 0.f, 0.f}, c3[4] = {0.f, 0.f, 0.f, 0.f};
#pragma unroll
    for (int j = 0; j < 6; j++) {
        uint32_t a[8];
        if constexpr (kVO) {
#pragma unroll
            for (int i = 0; i < 4; i++) {
                a[2 * i]     = __byte_perm(r.A[8 * j + 2 * i], r.A[8 * j + 2 * i + 1], 0x5410);
                a[2 * i + 1] = __byte_perm(r.A[8 * j + 2 * i], r.A[8 * j + 2 * i + 1], 0x7632);
            }
        } else {
#pragma unroll
            for (int i = 0; i < 8; i++) a[i] = r.A[8 * j + i];
        }
        mma16816(c0, a[0], a[1], a[2], a[3], r.B0[j].x, r.B0[j].y);
        mma16816(c1, a[0], a[1], a[2], a[3], r.B1[j].x, r.B1[j].y);
        mma16816(c2, a[4], a[5], a[6], a[7], r.B0[j].z, r.B0[j].w);
        mma16816(c3, a[4], a[5], a[6], a[7], r.B1[j].z, r.B1[j].w);
    }
#pragma unroll
    for (int i = 0; i < 4; i++) { c0[i] += c2[i]; c1[i] += c3[i]; }
    const int k0 = (tile % 12) * 16;
    if constexpr (kVO) {
        const int ch0 = (tile / 12) * 16 + 2 * g;
        const int n = 32 * (ch0 >> 5) + 8 * ((ch0 >> 1) & 3) + 2 * ((ch0 >> 3) & 3);
        fold_store(reinterpret_cast<char*>(g_wfold) + kWBytes, n, n + 1, k0, q, c0, c1);
    } else {
        const int n0 = (tile / 12) * 16;
        fold_store(reinterpret_cast<char*>(g_wfold), n0 + g, n0 + g + 8, k0, q, c0, c1);
    }
}

__device__ __forceinline__ uint32_t ld_acquire(const uint32_t* p) {
    uint32_t v;
    asm volatile("ld.acquire.gpu.global.u32 %0, [%1];" : "=r"(v) : "l"(p) : "memory");
    return v;
}
__device__ __forceinline__ void prefetch_x(const CUtensorMap* tm, int win) {
    const int wh = win >> 6, ww = win & 63;
    asm volatile("cp.async.bulk.prefetch.tensor.3d.L2.global.tile [%0, {%1, %2, %3}];"
                 ::"l"(tm), "r"(0), "r"(ww * 8), "r"(wh * 8) : "memory");
}

#define PF_EARLY 1
__device__ __forceinline__ void prefetch_for_ticket(const CUtensorMap* tmp, int t) {
    const int base = kNWG * (int)gridDim.x;
    auto lead = [&](int tt) {
        int down = max(((kNWin - base - tt) * PF_DOWN) >> 8, PF_MIN);
        return min(min(PF_INIT * (int)gridDim.x + ((tt * PF_UP) >> 8), PF_LEAD), down);
    };
    const int hi = base + t + lead(t);
    int lo = max(max(base + t - 1 + lead(t - 1), base + t) + 1, base + PF_INIT * (int)gridDim.x);
#pragma unroll 1
    for (; lo <= hi && lo < kNWin; lo++) prefetch_x(tmp, lo);
}

__global__ void __launch_bounds__(kThreads, 1)
swin_attn_kernel(const __nv_bfloat16* __restrict__ wqkv, const __nv_bfloat16* __restrict__ wo, __nv_bfloat16* __restrict__ out,
                 const __grid_constant__ CUtensorMap tmx, const __grid_constant__ CUtensorMap tmp, const __grid_constant__ CUtensorMap tmc) {
    extern __shared__ uint8_t smem_raw[];
    constexpr uint32_t sbase = kSmemBase;
    if (smem_u32(smem_raw) != kSmemBase) __trap();
    const int tid = threadIdx.x, lane = tid & 31;
    const uint32_t warpu = __reduce_or_sync(0xffffffffu, (uint32_t)tid >> 5), wgu = warpu >> 2;
    const int warp = (int)warpu, wg = (int)wgu;
    const int G = gridDim.x;
    const uint32_t bar_full = sbase + kOffBar + 8 * wg;
    const uint32_t bar_w0 = sbase + kOffBar + 32, bar_w1 = bar_w0 + 8;
    int win = wg * G + blockIdx.x;

    PROF(0); PROFG(1);
    const int ftile = blockIdx.x + (warp & 1) * G;
    const bool fold_qk = warp < 2 && ftile < kTiles, fold_vo = (warp >> 1) == 1 && ftile < kTiles;
    FoldRegs fr;
    if (fold_qk) fold_load_qk(fr, wqkv, ftile, lane);
    else if (fold_vo) fold_load_vo(fr, wqkv, wo, ftile, lane);
    const bool poller = (tid == kThreads - 32);
    PROFT(0, 32);
    const bool xloader = (tid == kThreads - 64);
    if (xloader) {
#pragma unroll
        for (int w = 0; w < kNWG; w++) mbar_init(sbase + kOffBar + 8 * w, 1);
        asm volatile("fence.mbarrier_init.release.cluster;" ::: "memory");
#pragma unroll
        for (int w = 0; w < kNWG; w++) mbar_expect_tx(sbase + kOffBar + 8 * w, kXBytes);
#pragma unroll
        for (int c = 0; c < TRK_FIRST; c++) tma_load_x_chunk(sbase + kOffX + c * 8192, &tmc, sbase + kOffBar, blockIdx.x, c);
    }
    if (poller) {
        mbar_init(bar_w0, 1);
        mbar_init(bar_w1, 1);
        mbar_init(sbase + kOffBar + 48, 1);
        mbar_init(sbase + kOffBar + 56, 1);
        asm volatile("st.shared.v2.u32 [%0], {%1, %1};" ::"r"(sbase + kOffBar + 80), "r"(0) : "memory");
        asm volatile("fence.mbarrier_init.release.cluster;" ::: "memory");
    }
    PROFT(0, 33);
    __syncthreads();
    PROFT(0, 34);
    if (xloader) {
        const uint32_t t0 = (uint32_t)clock64();
        for (int i = TRK_FIRST; i < 3 * kNWG; i++) {
            while ((uint32_t)clock64() - t0 < (uint32_t)(TRK_START + (i - TRK_FIRST) * TRK_STEP)) {}
            const int w = i / 3, c = i % 3;
            tma_load_x_chunk(sbase + kOffX + w * kXBytes + c * 8192, &tmc, sbase + kOffBar + 8 * w, w * G + blockIdx.x, c);
        }
    }
    if (fold_qk || fold_vo) {
        if (fold_qk) fold_compute_store<false>(fr, ftile, lane);
        else         fold_compute_store<true>(fr, ftile, lane);
        PROFT(0, 35); PROFT(64, 40);
        __syncwarp();
        if (lane == 0)
            asm volatile("red.release.gpu.global.add.u32 [%0], %1;" ::"l"(&g_cnt[fold_qk ? 0 : 32]), "r"(1u) : "memory");
        PROFT(0, 36); PROFT(64, 41);
    }
    for (int t = ftile + 2 * G; (warp < 4) && t < kTiles; t += 2 * G) {
        if (warp < 2) { fold_load_qk(fr, wqkv, t, lane); fold_compute_store<false>(fr, t, lane); }
        else          { fold_load_vo(fr, wqkv, wo, t, lane); fold_compute_store<true>(fr, t, lane); }
        __syncwarp();
        if (lane == 0)
            asm volatile("red.release.gpu.global.add.u32 [%0], %1;" ::"l"(&g_cnt[warp < 2 ? 0 : 32]), "r"(1u) : "memory");
    }
    PROF(6);
    if (poller) {
        uint32_t spins = 0;
        while (ld_acquire(&g_cnt[0]) < kTiles) { if (++spins > (1u << 24)) __trap(); }
        PROFT(kThreads - 32, 37);
        asm volatile("fence.proxy.async.global;" ::: "memory");
        auto load_m = [&](int c) {
            const uint32_t bar = c == 0 ? bar_w0 : sbase + kOffBar + 40 + 8 * c;
            mbar_expect_tx(bar, 24576);
            bulk_load(sbase + kOffWm + c * 24576, reinterpret_cast<const char*>(g_wfold) + c * 24576, 24576, bar);
        };
        load_m(0); load_m(1); load_m(2);
        spins = 0;
        PROFT(kThreads - 32, 38);
        while (ld_acquire(&g_cnt[32]) < kTiles) { if (++spins > (1u << 24)) __trap(); }
        PROFT(kThreads - 32, 39);
        asm volatile("fence.proxy.async.global;" ::: "memory");
        mbar_expect_tx(bar_w1, kWBytes);
#pragma unroll
        for (int c = 0; c < 3; c++)
            bulk_load(sbase + kOffWv + c * 24576, reinterpret_cast<const char*>(g_wfold) + kWBytes + c * 24576, 24576, bar_w1);
        for (int i = 0; i < PF_INIT; i++)
            if ((kNWG + i) * G + (int)blockIdx.x < kNWin) prefetch_x(&tmp, (kNWG + i) * G + blockIdx.x);
    }
    __syncwarp();
    if (wg == kNWG - 1) asm volatile("bar.sync 7, 128;" ::: "memory");
    if (wg == 1) asm volatile("bar.arrive 8, 256;" ::: "memory");
    for (int i = 0; i < wg; i++) { ring_wait(); ring_pass(); }

    constexpr uint32_t dWm = ((sbase + kOffWm) >> 4) | (1u << 16);
    constexpr uint32_t dWv = ((sbase + kOffWv) >> 4) | (1u << 16);
    const float cs = 0.07216878364870322f * 1.4426950408889634f;
    PROF(2);
    mbar_wait(bar_w0, 0);
    PROF(3);
    mbar_wait(bar_full, 0);

    uint4 hv[12];
    uint8_t* hptr;
    uint32_t phase = 0;
    float acc[96];
    uint32_t ticket = 0;
    {
        const uint32_t dX = ((sbase + kOffX + wg_uniform() * kXBytes) >> 4) | (1u << 16);
        ring_wait();
        wg_fence();
        Gemm1<0, 3>::run(acc, dX, dWm);
        mbar_wait(sbase + kOffBar + 48, 0);
        wg_fence();
        Gemm1<4, 7>::run(acc, dX, dWm);
        mbar_wait(sbase + kOffBar + 56, 0);
        wg_fence();
        Gemm1<8, 11>::run(acc, dX, dWm);
        wg_commit();
        ring_pass();
        if constexpr (DRAW_AT == 1) ticket = draw_ticket();
        wg_wait0();
    }

    while (true) {
        TRACE(0);
        uint32_t fa[48];
        const uint32_t dX = ((sbase + kOffX + wg_uniform() * kXBytes) >> 4) | (1u << 16);
        fence_regs(acc);
#pragma unroll
        for (int i = 0; i < 48; i++) fa[i] = pack_bf16(acc[2 * i], acc[2 * i + 1]);

        float s[32];
        fence_regs(fa);
        TRACE(4);
        ring_wait();
        TRACE(5);
        wg_fence();
        Gemm2<11>::run(s, fa, dX);
        wg_commit();
        if constexpr (PASS2 == 11) ring_pass();
        if constexpr (DRAW_AT == 2) ticket = draw_ticket();
        TRACE(6);
        wg_wait0();
        TRACE(7);
        fence_regs(s);
        fence_regs(fa);

        uint32_t pa[16];
        {
            float a0[8], a1[8];
#pragma unroll
            for (int j = 0; j < 8; j++) { a0[j] = fmaxf(s[4 * j], s[4 * j + 1]); a1[j] = fmaxf(s[4 * j + 2], s[4 * j + 3]); }
#pragma unroll
            for (int d = 4; d > 0; d >>= 1)
#pragma unroll
                for (int j = 0; j < d; j++) { a0[j] = fmaxf(a0[j], a0[j + d]); a1[j] = fmaxf(a1[j], a1[j + d]); }
            float m0 = a0[0], m1 = a1[0];
            m0 = fmaxf(m0, __shfl_xor_sync(0xffffffffu, m0, 1));
            m1 = fmaxf(m1, __shfl_xor_sync(0xffffffffu, m1, 1));
            m0 = fmaxf(m0, __shfl_xor_sync(0xffffffffu, m0, 2));
            m1 = fmaxf(m1, __shfl_xor_sync(0xffffffffu, m1, 2));
            m0 *= cs; m1 *= cs;
            float l0 = 0.f, l1 = 0.f;
#pragma unroll
            for (int j = 0; j < 8; j++) {
                s[4 * j]     = ex2(fmaf(s[4 * j], cs, -m0));
                s[4 * j + 1] = ex2(fmaf(s[4 * j + 1], cs, -m0));
                s[4 * j + 2] = ex2(fmaf(s[4 * j + 2], cs, -m1));
                s[4 * j + 3] = ex2(fmaf(s[4 * j + 3], cs, -m1));
                l0 += s[4 * j] + s[4 * j + 1];
                l1 += s[4 * j + 2] + s[4 * j + 3];
            }
            l0 += __shfl_xor_sync(0xffffffffu, l0, 1);
            l1 += __shfl_xor_sync(0xffffffffu, l1, 1);
            l0 += __shfl_xor_sync(0xffffffffu, l0, 2);
            l1 += __shfl_xor_sync(0xffffffffu, l1, 2);
            const float r0 = rcp(l0), r1 = rcp(l1);
#pragma unroll
            for (int j = 0; j < 8; j++) {
                pa[2 * j]     = pack_bf16(s[4 * j] * r0, s[4 * j + 1] * r0);
                pa[2 * j + 1] = pack_bf16(s[4 * j + 2] * r1, s[4 * j + 3] * r1);
            }
        }

        fence_regs(pa);
        const uint32_t dXt = ((sbase + kOffX + wg_uniform() * kXBytes) >> 4) | ((8192u >> 4) << 16);
        TRACE(8);
        ring_wait();
        TRACE(9);
        wg_fence();
        Gemm3<3>::run(acc, pa, dXt);
        wg_commit();
        if constexpr (PASS3 == 3) ring_pass();
        TRACE(10);
        const int nxt = kNWG * (int)gridDim.x + (int)__reduce_or_sync(0xffffffffu, ticket);
        wg_wait0();
        TRACE(11);
        fence_regs(acc);
        fence_regs(pa);

        if (((tid_now() >> 5) & 3) == 0) {
            asm volatile("bar.sync %0, 128;" ::"r"((tid_now() >> 7) + 1) : "memory");
            if (elect_one()) {
                const uint32_t wgl = tid_now() >> 7;
                const uint32_t bar = sbase + kOffBar + 8 * wgl;
                asm volatile("st.shared.u32 [%0], %1;" ::"r"(sbase + kOffBar + 64 + 4 * wgl), "r"(nxt) : "memory");
                if (nxt < kNWin) {
                    mbar_expect_tx(bar, kXBytes);
                    tma_load_x(sbase + kOffX + wgl * kXBytes, &tmx, bar, nxt & WMASK);
                    prefetch_for_ticket(&tmp, nxt - kNWG * (int)gridDim.x);
                }
            }
            __syncwarp();
            asm volatile("bar.arrive %0, 128;" ::"r"((tid_now() >> 7) + 4) : "memory");
        } else {
            asm volatile("bar.arrive %0, 128;" ::"r"((tid_now() >> 7) + 1) : "memory");
        }
#pragma unroll
        for (int i = 0; i < 48; i++) fa[i] = pack_bf16(acc[2 * i], acc[2 * i + 1]);

        asm volatile("st.volatile.shared.v4.b32 [%4], {%0, %1, %2, %3};"
                     :: "r"(fa[44]), "r"(fa[45]), "r"(fa[46]), "r"(fa[47]), "r"(sbase + kOffStash + tid_now() * 16) : "memory");
        mbar_wait(sbase + kOffBar + 40, 0);
        fence_regs(fa);
        TRACE(12);
        ring_wait();
        TRACE(13);
        wg_fence();
        Gemm4<0, 1>::run(acc, fa, dWv);
        wg_commit();
        Gemm4<2, 10>::run(acc, fa, dWv);
        wg_commit();
        wg_wait1();
        uint32_t fl[4];
        asm volatile("ld.volatile.shared.v4.b32 {%0, %1, %2, %3}, [%4];"
                     : "=r"(fl[0]), "=r"(fl[1]), "=r"(fl[2]), "=r"(fl[3]) : "r"(sbase + kOffStash + tid_now() * 16) : "memory");
        wg_fence();
        wg192_rs<false, 0, koff(11, 24576)>(acc, fl, dWv);
        wg_commit();
        if (((tid_now() >> 5) & 3) == 0) {
            if (elect_one()) {
                if (nxt >= kNWin) {
                    uint32_t nd;
                    asm volatile("ld.shared.u32 %0, [%1];" : "=r"(nd) : "r"(sbase + kOffBar + 80) : "memory");
                    asm volatile("st.shared.v2.u32 [%0], {%1, %2};" ::"r"(sbase + kOffBar + 80), "r"(nd + 1), "r"(tid_now() >> 7) : "memory");
                }
            }
            __syncwarp();
        }
        ring_pass();
        TRACE(14);
        if (((tid_now() >> 5) & 3) == 0) {
            if (elect_one()) {
                const int base = kNWG * (int)gridDim.x, t = nxt - base;
                if (t == kNWin - 1) { g_cnt[0] = 0; g_cnt[32] = 0; }
            }
            __syncwarp();
        } else {
            asm volatile("bar.sync %0, 128;" ::"r"((tid_now() >> 7) + 4) : "memory");
        }
        uint32_t pub;
        asm volatile("ld.shared.u32 %0, [%1];" : "=r"(pub) : "r"(sbase + kOffBar + 64 + 4 * (tid_now() >> 7)) : "memory");
        const int win_next = (int)__reduce_or_sync(0xffffffffu, pub);
        {
            const uint32_t ln = tid_now() & 31;
            hptr = reinterpret_cast<uint8_t*>(out) + (uint32_t)(((win & WMASK) >> 6) * 8 * kHW + (win & 63) * 8 + 2 * ((tid_now() >> 5) & 3) * kHW + (ln >> 2)) * (uint32_t)(kC * 2) + (ln & 3) * 16;
        }
        win = win_next;
        const uint32_t dX1 = ((sbase + kOffX + wg_uniform() * kXBytes) >> 4) | (1u << 16);
        phase ^= 1;
        if (win < kNWin) mbar_wait(sbase + kOffBar + 8 * (tid_now() >> 7), phase);
        asm volatile("" : "+l"(hptr) :: "memory");
        TRACE(18);
        wg_wait0();
        TRACE(15);
        fence_regs(acc);
        fence_regs(fa);
        fence_regs(fl);

#pragma unroll
        for (int a = 0; a < 6; a++) {
            hv[2 * a].x     = pack_bf16(acc[16 * a + 0], acc[16 * a + 1]);
            hv[2 * a].y     = pack_bf16(acc[16 * a + 4], acc[16 * a + 5]);
            hv[2 * a].z     = pack_bf16(acc[16 * a + 8], acc[16 * a + 9]);
            hv[2 * a].w     = pack_bf16(acc[16 * a + 12], acc[16 * a + 13]);
            hv[2 * a + 1].x = pack_bf16(acc[16 * a + 2], acc[16 * a + 3]);
            hv[2 * a + 1].y = pack_bf16(acc[16 * a + 6], acc[16 * a + 7]);
            hv[2 * a + 1].z = pack_bf16(acc[16 * a + 10], acc[16 * a + 11]);
            hv[2 * a + 1].w = pack_bf16(acc[16 * a + 14], acc[16 * a + 15]);
        }
        if constexpr (slot_begin(0) > 0) {
            __syncwarp();
            store_slot<-1>(hv, hptr);
            __syncwarp();
        }
        TRACE(16);
        if (win >= kNWin) break;
        ring_wait();
        wg_fence();
        Gemm1St<11>::run(acc, dX1, dWm, hv, hptr);
        if constexpr (DRAW_AT == 1) ticket = draw_ticket();
        TRACE(2);
        if constexpr (slot_begin(12) < 12) store_paced<slot_begin(12)>(hv, hptr, clock_now());
        TRACE(1);
        wg_wait0();
        TRACE(3);
    }
    store_range<slot_begin(0), 12>(hv, hptr);
    {
        const uint32_t me = tid_now() >> 7, nx = me == kNWG - 1 ? 0 : me + 1;
        uint32_t nd, last;
        asm volatile("bar.sync %0, 128;" ::"r"(me + 1) : "memory");
        asm volatile("ld.volatile.shared.v2.u32 {%0, %1}, [%2];" : "=r"(nd), "=r"(last) : "r"(sbase + kOffBar + 80) : "memory");
        while (!(nd == kNWG && last == me)) {
            ring_wait();
            asm volatile("ld.volatile.shared.v2.u32 {%0, %1}, [%2];" : "=r"(nd), "=r"(last) : "r"(sbase + kOffBar + 80) : "memory");
            const bool all = nd == kNWG;
            if (!all || nx != last) ring_pass();
            if (all) break;
        }
    }
    PROF(4); PROFG(5);
    PROF_FLUSH();
}

typedef CUresult (*EncodeTiledFn)(CUtensorMap*, CUtensorMapDataType, cuuint32_t, void*, const cuuint64_t*,
                                  const cuuint64_t*, const cuuint32_t*, const cuuint32_t*, CUtensorMapInterleave,
                                  CUtensorMapSwizzle, CUtensorMapL2promotion, CUtensorMapFloatOOBfill);

}

extern "C" void kernel_launch(void* const* d_in, const int* in_sizes, int n_in, void* d_out, int out_size) {
    (void)in_sizes; (void)n_in; (void)out_size;
    const __nv_bfloat16* x    = (const __nv_bfloat16*)d_in[0];
    const __nv_bfloat16* wqkv = (const __nv_bfloat16*)d_in[1];
    const __nv_bfloat16* wo   = (const __nv_bfloat16*)d_in[2];

    static EncodeTiledFn encode = nullptr;
    static int num_sms = 0;
    if (!encode) {
        void* fn = nullptr;
        cudaDriverEntryPointQueryResult qr;
        cudaGetDriverEntryPoint("cuTensorMapEncodeTiled", &fn, cudaEnableDefault, &qr);
        encode = (EncodeTiledFn)fn;
        int dev = 0;
        cudaGetDevice(&dev);
        cudaDeviceGetAttribute(&num_sms, cudaDevAttrMultiProcessorCount, dev);
        cudaFuncSetAttribute(swin_attn_kernel, cudaFuncAttributeMaxDynamicSharedMemorySize, kSmemBytes);
    }
    CUtensorMap tmx;
    const cuuint64_t gdim[4] = {64, (cuuint64_t)kHW, (cuuint64_t)kHW, 3};
    const cuuint64_t gstr[3] = {(cuuint64_t)kC * 2, (cuuint64_t)kHW * kC * 2, 128};
    const cuuint32_t box[4] = {64, 8, 8, 3};
    const cuuint32_t estr[4] = {1, 1, 1, 1};
    encode(&tmx, CU_TENSOR_MAP_DATA_TYPE_BFLOAT16, 4, (void*)x, gdim, gstr, box, estr, CU_TENSOR_MAP_INTERLEAVE_NONE,
           CU_TENSOR_MAP_SWIZZLE_128B, CU_TENSOR_MAP_L2_PROMOTION_NONE, CU_TENSOR_MAP_FLOAT_OOB_FILL_NONE);

    CUtensorMap tmp;
    const cuuint64_t pdim[3] = {(cuuint64_t)kC, (cuuint64_t)kHW, (cuuint64_t)kHW};
    const cuuint64_t pstr[2] = {(cuuint64_t)kC * 2, (cuuint64_t)kHW * kC * 2};
    const cuuint32_t pbox[3] = {(cuuint32_t)kC, 8, 8};
    encode(&tmp, CU_TENSOR_MAP_DATA_TYPE_BFLOAT16, 3, (void*)x, pdim, pstr, pbox, estr, CU_TENSOR_MAP_INTERLEAVE_NONE,
           CU_TENSOR_MAP_SWIZZLE_NONE, CU_TENSOR_MAP_L2_PROMOTION_NONE, CU_TENSOR_MAP_FLOAT_OOB_FILL_NONE);
    CUtensorMap tmc;
    const cuuint32_t boxc[4] = {64, 8, 8, 1};
    encode(&tmc, CU_TENSOR_MAP_DATA_TYPE_BFLOAT16, 4, (void*)x, gdim, gstr, boxc, estr, CU_TENSOR_MAP_INTERLEAVE_NONE,
           CU_TENSOR_MAP_SWIZZLE_128B, CU_TENSOR_MAP_L2_PROMOTION_NONE, CU_TENSOR_MAP_FLOAT_OOB_FILL_NONE);
    swin_attn_kernel<<<num_sms, kThreads, kSmemBytes, cudaStreamPerThread>>>(wqkv, wo, (__nv_bfloat16*)d_out, tmx, tmp, tmc);
}
```

```cpp
#include <cuda_runtime.h>
#include <cuda_bf16.h>
#include <cuda.h>
#include <stdint.h>

namespace {

constexpr int kC      = 192;
constexpr int kHW     = 512;
#define MAXWIN 4096
constexpr int kNWin   = MAXWIN;
constexpr int kXBytes = 64 * kC * 2;
constexpr int kWBytes = kC * kC * 2;
constexpr int kNWG    = 3;
constexpr int kThreads = kNWG * 128;
constexpr int kJobsM  = 72;
constexpr int kJobs   = 120;
#define PF_LEAD 400
#define PF_UP 170
#define PF_DOWN 34
#define PF_MIN 150
#define TRK_T0 900
#define TRK_S 2000
#define POLL_T0 900
#define POLL_T 2600
#define POLL_TV 3300

constexpr int kOffWm  = 0;
constexpr int kOffWv  = kWBytes;
constexpr int kOffX   = 2 * kWBytes;
constexpr int kOffBar = kOffX + kNWG * kXBytes;
constexpr int kOffStash = kOffBar + 128;
constexpr int kOffProf = kOffStash + kThreads * 16;
constexpr int kSmemBytes = kOffProf;
constexpr uint32_t kSmemBase = 1024;

struct Scratch {
    uint4 wfold[2 * kWBytes / 16];
    uint32_t ticket[32];
    uint32_t cnt[64];
};
__device__ __align__(128) Scratch g_scratch;

__device__ __forceinline__ uint32_t smem_u32(const void* p) { return (uint32_t)__cvta_generic_to_shared(p); }

__device__ __forceinline__ void mbar_init(uint32_t bar, uint32_t count) {
    asm volatile("mbarrier.init.shared::cta.b64 [%0], %1;" ::"r"(bar), "r"(count) : "memory");
}
__device__ __forceinline__ void mbar_expect_tx(uint32_t bar, uint32_t bytes) {
    asm volatile("mbarrier.arrive.expect_tx.shared::cta.b64 _, [%0], %1;" ::"r"(bar), "r"(bytes) : "memory");
}
__device__ __forceinline__ void mbar_wait(uint32_t bar, uint32_t parity) {
    uint32_t ok;
    uint32_t spins = 0;
    do {
        asm volatile("{\n.reg .pred p;\n"
                     "mbarrier.try_wait.parity.shared::cta.b64 p, [%1], %2;\n"
                     "selp.b32 %0, 1, 0, p;\n}\n"
                     : "=r"(ok) : "r"(bar), "r"(parity) : "memory");
        if (++spins > (1u << 26)) __trap();
    } while (!ok);
}
__device__ __forceinline__ uint32_t tid_now() {
    uint32_t t;
    asm volatile("mov.u32 %0, %%tid.x;" : "=r"(t));
    return t;
}
__device__ __forceinline__ bool elect_one() {
    uint32_t pred;
    asm volatile("{\n.reg .pred p;\nelect.sync _|p, 0xffffffff;\nselp.b32 %0, 1, 0, p;\n}\n" : "=r"(pred));
    return pred != 0;
}
#define PASS1 11
#define PASS2 5
#define PASS3 3
__device__ __forceinline__ void ring_wait() {
    asm volatile("bar.sync %0, 256;" ::"r"((tid_now() >> 7) + 8) : "memory");
}
__device__ __forceinline__ void ring_wait(uint32_t dep) {
    asm volatile("{\n.reg .pred p;\n.reg .b32 t;\nsetp.eq.u32 p, %1, 0x7fc17fc1;\nselp.u32 t, 0, %0, p;\nbar.sync t, 256;\n}\n"
                 ::"r"((tid_now() >> 7) + 8), "r"(dep) : "memory");
}
__device__ __forceinline__ void ring_pass() {
    const uint32_t w = tid_now() >> 7;
    asm volatile("bar.arrive %0, 256;" ::"r"(w == kNWG - 1 ? 8u : w + 9u) : "memory");
}
__device__ __forceinline__ uint32_t wg_uniform() { return __reduce_or_sync(0xffffffffu, tid_now() >> 7); }
__device__ __forceinline__ void tma_load_x(uint32_t dst, const CUtensorMap* tm, uint32_t bar, int win) {
    const int wh = win >> 6, ww = win & 63;
    asm volatile("cp.async.bulk.tensor.4d.shared::cluster.global.mbarrier::complete_tx::bytes"
                 " [%0], [%1, {%3, %4, %5, %6}], [%2];"
                 ::"r"(dst), "l"(tm), "r"(bar), "r"(0), "r"(ww * 8), "r"(wh * 8), "r"(0) : "memory");
}
__device__ __forceinline__ void tma_load_x_chunk(uint32_t dst, const CUtensorMap* tm, uint32_t bar, int win, int chunk) {
    const int wh = win >> 6, ww = win & 63;
    asm volatile("cp.async.bulk.tensor.4d.shared::cluster.global.mbarrier::complete_tx::bytes"
                 " [%0], [%1, {%3, %4, %5, %6}], [%2];"
                 ::"r"(dst), "l"(tm), "r"(bar), "r"(0), "r"(ww * 8), "r"(wh * 8), "r"(chunk) : "memory");
}
__device__ __forceinline__ void bulk_load(uint32_t dst, const void* src, uint32_t bytes, uint32_t bar) {
    asm volatile("cp.async.bulk.shared::cluster.global.mbarrier::complete_tx::bytes [%0], [%1], %2, [%3];"
                 ::"r"(dst), "l"(src), "r"(bytes), "r"(bar) : "memory");
}

__device__ __forceinline__ void stg128(void* p, uint4 v) {
    asm volatile("st.global.v4.b32 [%0], {%1, %2, %3, %4};" ::"l"(p), "r"(v.x), "r"(v.y), "r"(v.z), "r"(v.w) : "memory");
}
__device__ __forceinline__ void wg_fence()  { asm volatile("wgmma.fence.sync.aligned;" ::: "memory"); }
__device__ __forceinline__ void wg_commit() { asm volatile("wgmma.commit_group.sync.aligned;" ::: "memory"); }
__device__ __forceinline__ void wg_wait0()  { asm volatile("wgmma.wait_group.sync.aligned 0;" ::: "memory"); }
__device__ __forceinline__ void wg_wait1()  { asm volatile("wgmma.wait_group.sync.aligned 1;" ::: "memory"); }

template <int N> __device__ __forceinline__ void fence_regs(float (&d)[N]) {
#pragma unroll
    for (int i = 0; i < N; i++) asm volatile("" : "+f"(d[i])::"memory");
}
template <int N> __device__ __forceinline__ void fence_regs(uint32_t (&d)[N]) {
#pragma unroll
    for (int i = 0; i < N; i++) asm volatile("" : "+r"(d[i])::"memory");
}

#define ACC8(c, d, i) c(d[i]), c(d[i + 1]), c(d[i + 2]), c(d[i + 3]), c(d[i + 4]), c(d[i + 5]), c(d[i + 6]), c(d[i + 7])
#define ACC32(c, d) ACC8(c, d, 0), ACC8(c, d, 8), ACC8(c, d, 16), ACC8(c, d, 24)
#define ACC96(c, d) ACC32(c, d), ACC8(c, d, 32), ACC8(c, d, 40), ACC8(c, d, 48), ACC8(c, d, 56), \
                    ACC8(c, d, 64), ACC8(c, d, 72), ACC8(c, d, 80), ACC8(c, d, 88)
#define C_IO(x) "+f"(x)
#define C_O(x) "=f"(x)
#define REGS32 "{%0, %1, %2, %3, %4, %5, %6, %7, %8, %9, %10, %11, %12, %13, %14, %15, " \
               "%16, %17, %18, %19, %20, %21, %22, %23, %24, %25, %26, %27, %28, %29, %30, %31}"
#define REGS96 "{%0, %1, %2, %3, %4, %5, %6, %7, %8, %9, %10, %11, %12, %13, %14, %15, " \
               "%16, %17, %18, %19, %20, %21, %22, %23, %24, %25, %26, %27, %28, %29, %30, %31, " \
               "%32, %33, %34, %35, %36, %37, %38, %39, %40, %41, %42, %43, %44, %45, %46, %47, " \
               "%48, %49, %50, %51, %52, %53, %54, %55, %56, %57, %58, %59, %60, %61, %62, %63, " \
               "%64, %65, %66, %67, %68, %69, %70, %71, %72, %73, %74, %75, %76, %77, %78, %79, " \
               "%80, %81, %82, %83, %84, %85, %86, %87, %88, %89, %90, %91, %92, %93, %94, %95}"

#define DESC_HI "0x40000040"
#define MK_DESC(name, lo, off) "add.u32 t, " lo ", " off ";\nmov.b64 " name ", {t, " DESC_HI "};\n"

template <bool First, int OA, int OB> __device__ __forceinline__ void wg192_ss(float (&d)[96], uint32_t la, uint32_t lb) {
    if constexpr (First)
        asm volatile("{\n.reg .pred p;\n.reg .b32 t;\n.reg .b64 da, db;\nsetp.ne.b32 p, 0, 0;\n"
                     MK_DESC("da", "%96", "%98") MK_DESC("db", "%97", "%99")
                     "wgmma.mma_async.sync.aligned.m64n192k16.f32.bf16.bf16 " REGS96 ", da, db, p, 1, 1, 0, 0;\n}\n"
                     : ACC96(C_O, d) : "r"(la), "r"(lb), "n"(OA), "n"(OB));
    else
        asm volatile("{\n.reg .pred p;\n.reg .b32 t;\n.reg .b64 da, db;\nsetp.ne.b32 p, 1, 0;\n"
                     MK_DESC("da", "%96", "%98") MK_DESC("db", "%97", "%99")
                     "wgmma.mma_async.sync.aligned.m64n192k16.f32.bf16.bf16 " REGS96 ", da, db, p, 1, 1, 0, 0;\n}\n"
                     : ACC96(C_IO, d) : "r"(la), "r"(lb), "n"(OA), "n"(OB));
}
template <bool First, int TB, int OB> __device__ __forceinline__ void wg192_rs(float (&d)[96], const uint32_t* a, uint32_t lb) {
    if constexpr (First)
        asm volatile("{\n.reg .pred p;\n.reg .b32 t;\n.reg .b64 db;\nsetp.ne.b32 p, 0, 0;\n"
                     MK_DESC("db", "%100", "%102")
                     "wgmma.mma_async.sync.aligned.m64n192k16.f32.bf16.bf16 " REGS96 ", {%96, %97, %98, %99}, db, p, 1, 1, %101;\n}\n"
                     : ACC96(C_O, d) : "r"(a[0]), "r"(a[1]), "r"(a[2]), "r"(a[3]), "r"(lb), "n"(TB), "n"(OB));
    else
        asm volatile("{\n.reg .pred p;\n.reg .b32 t;\n.reg .b64 db;\nsetp.ne.b32 p, 1, 0;\n"
                     MK_DESC("db", "%100", "%102")
                     "wgmma.mma_async.sync.aligned.m64n192k16.f32.bf16.bf16 " REGS96 ", {%96, %97, %98, %99}, db, p, 1, 1, %101;\n}\n"
                     : ACC96(C_IO, d) : "r"(a[0]), "r"(a[1]), "r"(a[2]), "r"(a[3]), "r"(lb), "n"(TB), "n"(OB));
}
template <bool First, int OB> __device__ __forceinline__ void wg64_rs(float (&d)[32], const uint32_t* a, uint32_t lb) {
    if constexpr (First)
        asm volatile("{\n.reg .pred p;\n.reg .b32 t;\n.reg .b64 db;\nsetp.ne.b32 p, 0, 0;\n"
                     MK_DESC("db", "%36", "%37")
                     "wgmma.mma_async.sync.aligned.m64n64k16.f32.bf16.bf16 " REGS32 ", {%32, %33, %34, %35}, db, p, 1, 1, 0;\n}\n"
                     : ACC32(C_O, d) : "r"(a[0]), "r"(a[1]), "r"(a[2]), "r"(a[3]), "r"(lb), "n"(OB));
    else
        asm volatile("{\n.reg .pred p;\n.reg .b32 t;\n.reg .b64 db;\nsetp.ne.b32 p, 1, 0;\n"
                     MK_DESC("db", "%36", "%37")
                     "wgmma.mma_async.sync.aligned.m64n64k16.f32.bf16.bf16 " REGS32 ", {%32, %33, %34, %35}, db, p, 1, 1, 0;\n}\n"
                     : ACC32(C_IO, d) : "r"(a[0]), "r"(a[1]), "r"(a[2]), "r"(a[3]), "r"(lb), "n"(OB));
}
__host__ __device__ constexpr int koff(int kk, int chunk) { return ((kk >> 2) * chunk + (kk & 3) * 32) >> 4; }

#define ST_SLOTS 0x2000000000001ull
__host__ __device__ constexpr int slot_begin(int i) {
    int b = 0;
    for (int k = -1; k < i; k++) b += (int)((ST_SLOTS >> (4 * (11 - k))) & 15);
    return b;
}
#define PACE_DT 160
template <int J, int E> __device__ __forceinline__ void store_range(const uint4 (&h)[12], uint8_t* hptr) {
    if constexpr (J < E) {
        constexpr int r = J / 6, a = J % 6;
        stg128(hptr + r * (kHW * kC * 2) + a * 64, h[2 * a + r]);
        store_range<J + 1, E>(h, hptr);
    }
}
template <int I> __device__ __forceinline__ void store_slot(const uint4 (&h)[12], uint8_t* hptr) {
    store_range<slot_begin(I), slot_begin(I + 1)>(h, hptr);
}
__device__ __forceinline__ uint32_t clock_now() {
    uint32_t t;
    asm volatile("mov.u32 %0, %%clock;" : "=r"(t));
    return t;
}
template <int J> __device__ __forceinline__ void store_paced(const uint4 (&h)[12], uint8_t* hptr, uint32_t t0) {
    if constexpr (J < 12) {
        while (clock_now() - t0 < (uint32_t)((J - slot_begin(12) + 1) * PACE_DT)) {}
        store_range<J, J + 1>(h, hptr);
        store_paced<J + 1>(h, hptr, t0);
    }
}
template <int K> struct Gemm1St {
    static __device__ __forceinline__ void run(float (&d)[96], uint32_t lx, uint32_t lw, const uint4 (&h)[12], uint8_t* hptr) {
        if constexpr (K > 0) Gemm1St<K - 1>::run(d, lx, lw, h, hptr);
        wg192_ss<K == 0, koff(K, 8192), koff(K, 24576)>(d, lx, lw);
        if constexpr (K == 11) wg_commit();
        if constexpr (K == PASS1) ring_pass();
        if constexpr (slot_begin(K + 1) > slot_begin(K)) {
            __syncwarp();
            store_slot<K>(h, hptr);
            __syncwarp();
        }
    }
};
template <int K0, int K> struct Gemm1 {
    static __device__ __forceinline__ void run(float (&d)[96], uint32_t lx, uint32_t lw) {
        if constexpr (K > K0) Gemm1<K0, K - 1>::run(d, lx, lw);
        wg192_ss<K == 0, koff(K, 8192), koff(K, 24576)>(d, lx, lw);
    }
};
__device__ __forceinline__ uint32_t draw_ticket(Scratch* sc) {
    uint32_t ticket = 0;
    asm volatile("{\n.reg .pred p;\nsetp.eq.u32 p, %2, 0;\n@p atom.relaxed.gpu.global.inc.u32 %0, [%1], %3;\n}\n"
                 : "+r"(ticket) : "l"(sc->ticket), "r"(tid_now() & 127), "n"(kNWin - 1) : "memory");
    return ticket;
}
#define DRAW_AT 1
template <int KK> struct Gemm2 { static __device__ __forceinline__ void run(float (&d)[32], const uint32_t* a, uint32_t lx) {
    Gemm2<KK - 1>::run(d, a, lx); wg64_rs<KK == 0, koff(KK, 8192)>(d, a + 4 * KK, lx);
    if constexpr (KK == PASS2 && KK < 11) ring_pass(); } };
template <> struct Gemm2<-1> { static __device__ __forceinline__ void run(float (&)[32], const uint32_t*, uint32_t) {} };
template <int KK> struct Gemm3 { static __device__ __forceinline__ void run(float (&d)[96], const uint32_t* a, uint32_t lxt) {
    Gemm3<KK - 1>::run(d, a, lxt); wg192_rs<KK == 0, 1, KK * (2048 >> 4)>(d, a + 4 * KK, lxt);
    if constexpr (KK == PASS3 && KK < 3) ring_pass(); } };
template <> struct Gemm3<-1> { static __device__ __forceinline__ void run(float (&)[96], const uint32_t*, uint32_t) {} };
template <int K0, int KK> struct Gemm4 { static __device__ __forceinline__ void run(float (&d)[96], const uint32_t* a, uint32_t lw) {
    if constexpr (KK > K0) Gemm4<K0, KK - 1>::run(d, a, lw);
    wg192_rs<KK == 0, 0, koff(KK, 24576)>(d, a + 4 * KK, lw); } };

__device__ __forceinline__ uint32_t pack_bf16(float lo, float hi) {
    uint32_t r;
    asm("cvt.rn.bf16x2.f32 %0, %1, %2;" : "=r"(r) : "f"(hi), "f"(lo));
    return r;
}
__device__ __forceinline__ float ex2(float x) {
    float r;
    asm("ex2.approx.ftz.f32 %0, %1;" : "=f"(r) : "f"(x));
    return r;
}
__device__ __forceinline__ float rcp(float x) {
    float r;
    asm("rcp.approx.ftz.f32 %0, %1;" : "=f"(r) : "f"(x));
    return r;
}

__device__ __forceinline__ int fold_offset(int n, int k0, int q) {
    const int u = ((k0 & 63) >> 3) + (q >> 1);
    return (k0 >> 6) * 24576 + (q & 1) * 8 + n * 128 + ((u ^ (n & 7)) << 4);
}
__device__ __forceinline__ void mma16816x2(float (&c)[4], float (&d)[4], const uint32_t (&a)[4], const uint32_t (&b)[4]) {
    asm volatile("mma.sync.aligned.m16n8k16.row.col.f32.bf16.bf16.f32 {%0,%1,%2,%3}, {%8,%9,%10,%11}, {%12,%13}, {%0,%1,%2,%3};\n"
                 "mma.sync.aligned.m16n8k16.row.col.f32.bf16.bf16.f32 {%4,%5,%6,%7}, {%8,%9,%10,%11}, {%14,%15}, {%4,%5,%6,%7};"
                 : "+f"(c[0]), "+f"(c[1]), "+f"(c[2]), "+f"(c[3]), "+f"(d[0]), "+f"(d[1]), "+f"(d[2]), "+f"(d[3])
                 : "r"(a[0]), "r"(a[1]), "r"(a[2]), "r"(a[3]), "r"(b[0]), "r"(b[1]), "r"(b[2]), "r"(b[3]));
}
__device__ __forceinline__ void cp_async16(uint32_t dst, const void* src) {
    asm volatile("cp.async.cg.shared.global [%0], [%1], 16;" ::"r"(dst), "l"(src) : "memory");
}
template <bool kTrans> __device__ __forceinline__ void ldsm4(uint32_t (&r)[4], uint32_t addr) {
    if constexpr (kTrans)
        asm volatile("ldmatrix.sync.aligned.m8n8.x4.trans.shared.b16 {%0, %1, %2, %3}, [%4];" : "=r"(r[0]), "=r"(r[1]), "=r"(r[2]), "=r"(r[3]) : "r"(addr) : "memory");
    else
        asm volatile("ldmatrix.sync.aligned.m8n8.x4.shared.b16 {%0, %1, %2, %3}, [%4];" : "=r"(r[0]), "=r"(r[1]), "=r"(r[2]), "=r"(r[3]) : "r"(addr) : "memory");
}
__device__ __forceinline__ void fold_job(Scratch* sc, const __nv_bfloat16* __restrict__ wqkv, const __nv_bfloat16* __restrict__ wo,
                                         int job, int warp, int lane) {
    const bool vo = job >= kJobsM;
    const int nw = vo ? 3 : 2, tile0 = vo ? 3 * (job - kJobsM) : 2 * job;
    const int n0 = (tile0 / 12) * 16, k0 = (tile0 % 12 + max(warp, 1) - 1) * 16;
    const uint32_t stage = kSmemBase + kOffWv;
    if (warp <= nw) {
        if (vo && warp == 0) {
            const char* src = reinterpret_cast<const char*>(wo + (lane >> 1) * kC + n0 + (lane & 1) * 8);
            const uint32_t dst = stage + ((lane ^ ((lane >> 3) & 1)) << 4);
#pragma unroll
            for (int i = 0; i < 12; i++) cp_async16(dst + i * 512, src + i * 16 * kC * 2);
        } else {
            const int row0 = warp == 0 ? n0 : k0, col0 = warp == 0 ? kC : vo ? 2 * kC : 0;
            const char* src = reinterpret_cast<const char*>(wqkv + (row0 + (lane >> 3)) * (3 * kC) + col0 + (lane & 7) * 8);
            const uint32_t dst = stage + warp * 6144 + (lane >> 3) * 384 + (((lane & 7) ^ (lane >> 3)) << 4);
#pragma unroll
            for (int i = 0; i < 12; i++) cp_async16((dst ^ (((i / 3) & 1) << 6)) + (i / 3) * 1536 + (i % 3) * 128, src + (i / 3) * 4 * 3 * kC * 2 + (i % 3) * 128);
        }
        asm volatile("cp.async.wait_all;" ::: "memory");
        asm volatile("bar.sync 13, %0;" ::"r"(32 * nw + 32) : "memory");
    }
    if (warp == 0 || (warp > nw && warp != 4)) return;
    const int g = lane >> 2, q = lane & 3, mi = lane >> 3, r8 = lane & 7;
    uint32_t A[12][4], B[12][4];
    {
        const int row = 4 * (r8 >> 1) + (r8 & 1) + 2 * (mi >> 1);
        const uint32_t base = stage + (warp & 3) * 6144 + row * 384 + (((mi & 1) ^ (row & 7)) << 4);
#pragma unroll
        for (int ks = 0; ks < 12; ks++) ldsm4<false>(B[ks], (base ^ ((ks & 3) << 5)) + (ks >> 2) * 128);
    }
    if (vo) {
        const int c = r8 + 8 * (mi >> 1);
        const uint32_t base = stage + (((2 * c + (mi & 1)) ^ ((c >> 2) & 1)) << 4);
#pragma unroll
        for (int ks = 0; ks < 12; ks++) ldsm4<true>(A[ks], base + ks * 512);
    } else {
        const uint32_t base = stage + (r8 + 8 * (mi & 1)) * 384 + (((mi >> 1) ^ r8) << 4);
#pragma unroll
        for (int ks = 0; ks < 12; ks++) ldsm4<false>(A[ks], (base ^ ((ks & 3) << 5)) + (ks >> 2) * 128);
    }
    float c0[4] = {0.f, 0.f, 0.f, 0.f}, c1[4] = {0.f, 0.f, 0.f, 0.f}, c2[4] = {0.f, 0.f, 0.f, 0.f}, c3[4] = {0.f, 0.f, 0.f, 0.f};
#pragma unroll
    for (int ks = 0; ks < 12; ks += 2) {
        mma16816x2(c0, c1, A[ks], B[ks]);
        mma16816x2(c2, c3, A[ks + 1], B[ks + 1]);
    }
#pragma unroll
    for (int i = 0; i < 4; i++) { c0[i] += c2[i]; c1[i] += c3[i]; }
    const int ch = n0 + g;
    const int n = vo ? 32 * (ch >> 5) + 8 * ((ch >> 1) & 3) + 2 * ((ch >> 3) & 3) + (ch & 1) : ch;
    char* img = reinterpret_cast<char*>(sc->wfold) + (vo ? kWBytes : 0);
    asm volatile("{\n.reg .pred p;\nsetp.ne.u32 p, %6, 4;\n@p st.global.v2.u32 [%0], {%2, %3};\n@p st.global.v2.u32 [%1], {%4, %5};\n}\n"
                 ::"l"(img + fold_offset(n, k0, q)), "l"(img + fold_offset(n + (vo ? 2 : 8), k0, q)),
                   "r"(pack_bf16(c0[0], c0[1])), "r"(pack_bf16(c1[0], c1[1])), "r"(pack_bf16(c0[2], c0[3])), "r"(pack_bf16(c1[2], c1[3])),
                   "r"(warp) : "memory");
    if (warp == 4) return;
    asm volatile("bar.sync 12, %0;" ::"r"(32 * nw) : "memory");
    if (lane == 0 && warp == 1) asm volatile("red.release.gpu.global.add.u32 [%0], 1;" ::"l"(&sc->cnt[vo ? 32 : 0]) : "memory");
}

__device__ __forceinline__ uint32_t ld_acquire(const uint32_t* p) {
    uint32_t v;
    asm volatile("ld.acquire.gpu.global.u32 %0, [%1];" : "=r"(v) : "l"(p) : "memory");
    return v;
}
__device__ __forceinline__ void prefetch_x(const CUtensorMap* tm, int win) {
    const int wh = win >> 6, ww = win & 63;
    asm volatile("cp.async.bulk.prefetch.tensor.3d.L2.global.tile [%0, {%1, %2, %3}];"
                 ::"l"(tm), "r"(0), "r"(ww * 8), "r"(wh * 8) : "memory");
}

__device__ __forceinline__ void prefetch_for_ticket(const CUtensorMap* tmp, int t) {
    const int base = kNWG * (int)gridDim.x;
    auto lead = [&](int tt) {
        int down = max(((kNWin - base - tt) * PF_DOWN) >> 8, PF_MIN);
        return min(min((tt * PF_UP) >> 8, PF_LEAD), down);
    };
    const int hi = base + t + lead(t);
    int lo = max(base + t - 1 + lead(t - 1), base + t) + 1;
#pragma unroll 1
    for (; lo <= hi && lo < kNWin; lo++) prefetch_x(tmp, lo);
}

template <bool kFewSMs>
__global__ void __launch_bounds__(kThreads, 1)
swin_attn_kernel(const __nv_bfloat16* __restrict__ wqkv, const __nv_bfloat16* __restrict__ wo, __nv_bfloat16* __restrict__ out, Scratch* sc,
                 const __grid_constant__ CUtensorMap tmx, const __grid_constant__ CUtensorMap tmp, const __grid_constant__ CUtensorMap tmc) {
    extern __shared__ uint8_t smem_raw[];
    constexpr uint32_t sbase = kSmemBase;
    const uint32_t t_start = clock_now();
    if (smem_u32(smem_raw) != kSmemBase) __trap();
    const int tid = threadIdx.x, lane = tid & 31;
    const uint32_t warpu = __reduce_or_sync(0xffffffffu, (uint32_t)tid >> 5), wgu = warpu >> 2;
    const int warp = (int)warpu, wg = (int)wgu;
    const int G = gridDim.x;
    const uint32_t bar_full = sbase + kOffBar + 8 * wg;
    const uint32_t bar_w0 = sbase + kOffBar + 32, bar_w1 = bar_w0 + 8;
    int win = wg * G + blockIdx.x;

    if (warp > 4) {
        if (warp == 10) {
            asm volatile("bar.arrive 0, %0;" ::"n"(kThreads) : "memory");
            if (lane == 0) {
                asm volatile("prefetch.tensormap [%0];" ::"l"(&tmp) : "memory");
                asm volatile("prefetch.tensormap [%0];" ::"l"(&tmc) : "memory");
                asm volatile("prefetch.tensormap [%0];" ::"l"(&tmx) : "memory");
                const uint32_t due = TRK_T0 + (uint32_t)(blockIdx.x * TRK_S) / (uint32_t)G;
#pragma unroll 1
                for (int i = 0; i < kNWG; i++) {
                    while (clock_now() - t_start < due + i * TRK_S) {}
                    prefetch_x(&tmp, i * G + blockIdx.x);
                }
            }
            __syncwarp();
        } else if (warp == 11) {
            if (lane == 0) {
#pragma unroll
                for (int w = 0; w < kNWG; w++) mbar_init(sbase + kOffBar + 8 * w, 1);
                mbar_init(bar_w0, 1);
                mbar_init(bar_w1, 1);
                mbar_init(sbase + kOffBar + 48, 1);
                mbar_init(sbase + kOffBar + 56, 1);
                asm volatile("st.shared.v2.u32 [%0], {%1, %1};" ::"r"(sbase + kOffBar + 80), "r"(0) : "memory");
                asm volatile("fence.mbarrier_init.release.cluster;" ::: "memory");
                asm volatile("mbarrier.arrive.shared::cta.b64 _, [%0];" ::"r"(sbase + kOffBar) : "memory");
            }
            __syncwarp();
            asm volatile("bar.arrive 0, %0;" ::"n"(kThreads) : "memory");
            if (lane == 0) {
                const char* img = reinterpret_cast<const char*>(sc->wfold);
                uint32_t spins = 0;
                while (clock_now() - t_start < POLL_T0) {}
                uint32_t done = ld_acquire(sc->cnt);
                while (clock_now() - t_start < POLL_T) {}
                while (done < kJobsM) { done = ld_acquire(sc->cnt); if (++spins > (1u << 24)) __trap(); }
                asm volatile("fence.proxy.async.global;" ::: "memory");
#pragma unroll
                for (int c = 0; c < 3; c++) {
                    const uint32_t bar = c == 0 ? bar_w0 : sbase + kOffBar + 40 + 8 * c;
                    mbar_expect_tx(bar, 24576 + 8192);
                    tma_load_x_chunk(sbase + kOffX + c * 8192, &tmc, bar, blockIdx.x, c);
                    bulk_load(sbase + kOffWm + c * 24576, img + c * 24576, 24576, bar);
                }
                mbar_wait(bar_w0, 0);
                mbar_expect_tx(sbase + kOffBar + 8, kXBytes);
                tma_load_x(sbase + kOffX + kXBytes, &tmx, sbase + kOffBar + 8, G + blockIdx.x);
            }
            __syncwarp();
        } else {
            asm volatile("bar.sync 0, %0;" ::"n"(kThreads) : "memory");
            if (warp == 9) {
                if (lane == 0) {
                    uint32_t spins = 0;
                    while (clock_now() - t_start < POLL_TV) {}
                    while (ld_acquire(sc->cnt + 32) < kJobs - kJobsM) { if (++spins > (1u << 24)) __trap(); }
                    mbar_wait(sbase + kOffBar + 48, 0);
                    asm volatile("fence.proxy.async;" ::: "memory");
                    mbar_expect_tx(bar_w1, kWBytes);
#pragma unroll
                    for (int c = 0; c < 3; c++)
                        bulk_load(sbase + kOffWv + c * 24576, reinterpret_cast<const char*>(sc->wfold) + kWBytes + c * 24576, 24576, bar_w1);
                    mbar_expect_tx(sbase + kOffBar + 16, kXBytes);
                    tma_load_x(sbase + kOffX + 2 * kXBytes, &tmx, sbase + kOffBar + 16, 2 * G + blockIdx.x);
                }
                __syncwarp();
            }
        }
    } else {
        if constexpr (kFewSMs) {
#pragma unroll 1
            for (int j = blockIdx.x; j < kJobs; j += G) {
                fold_job(sc, wqkv, wo, j, warp, lane);
                asm volatile("bar.sync 14, 160;" ::: "memory");
            }
        } else {
            if (blockIdx.x < kJobs) fold_job(sc, wqkv, wo, blockIdx.x, warp, lane);
        }
        asm volatile("bar.sync 0, %0;" ::"n"(kThreads) : "memory");
    }
    if (wg == kNWG - 1) asm volatile("bar.sync 7, 128;" ::: "memory");
    if (wg == 1) asm volatile("bar.arrive 8, 256;" ::: "memory");

    constexpr uint32_t dWm = ((sbase + kOffWm) >> 4) | (1u << 16);
    constexpr uint32_t dWv = ((sbase + kOffWv) >> 4) | (1u << 16);
    const float cs = 0.07216878364870322f * 1.4426950408889634f;
    mbar_wait(bar_w0, 0);
    if (wg != 0) mbar_wait(bar_full, 0);

    uint4 hv[12];
    uint8_t* hptr;
    uint32_t phase = 0;
    float acc[96];
    uint32_t ticket = 0;
    {
        const uint32_t dX = ((sbase + kOffX + wg_uniform() * kXBytes) >> 4) | (1u << 16);
        if (wg != 0) ring_wait();
        wg_fence();
        Gemm1<0, 3>::run(acc, dX, dWm);
        mbar_wait(sbase + kOffBar + 48, 0);
        wg_fence();
        Gemm1<4, 7>::run(acc, dX, dWm);
        mbar_wait(sbase + kOffBar + 56, 0);
        wg_fence();
        Gemm1<8, 11>::run(acc, dX, dWm);
        wg_commit();
        if (wg != 0) asm volatile("bar.arrive 8, 256;" ::: "memory");
        if constexpr (DRAW_AT == 1) ticket = draw_ticket(sc);
        wg_wait0();
    }

    while (true) {
        uint32_t fa[48];
        const uint32_t dX = ((sbase + kOffX + wg_uniform() * kXBytes) >> 4) | (1u << 16);
        fence_regs(acc);
#pragma unroll
        for (int i = 0; i < 48; i++) fa[i] = pack_bf16(acc[2 * i], acc[2 * i + 1]);

        float s[32];
        fence_regs(fa);
        ring_wait(fa[47]);
        wg_fence();
        Gemm2<11>::run(s, fa, dX);
        wg_commit();
        if constexpr (PASS2 == 11) ring_pass();
        if constexpr (DRAW_AT == 2) ticket = draw_ticket(sc);
        wg_wait0();
        fence_regs(s);
        fence_regs(fa);

        uint32_t pa[16];
        {
            float a0[8], a1[8];
#pragma unroll
            for (int j = 0; j < 8; j++) { a0[j] = fmaxf(s[4 * j], s[4 * j + 1]); a1[j] = fmaxf(s[4 * j + 2], s[4 * j + 3]); }
#pragma unroll
            for (int d = 4; d > 0; d >>= 1)
#pragma unroll
                for (int j = 0; j < d; j++) { a0[j] = fmaxf(a0[j], a0[j + d]); a1[j] = fmaxf(a1[j], a1[j + d]); }
            float m0 = a0[0], m1 = a1[0];
            m0 = fmaxf(m0, __shfl_xor_sync(0xffffffffu, m0, 1));
            m1 = fmaxf(m1, __shfl_xor_sync(0xffffffffu, m1, 1));
            m0 = fmaxf(m0, __shfl_xor_sync(0xffffffffu, m0, 2));
            m1 = fmaxf(m1, __shfl_xor_sync(0xffffffffu, m1, 2));
            m0 *= cs; m1 *= cs;
            float l0 = 0.f, l1 = 0.f;
#pragma unroll
            for (int j = 0; j < 8; j++) {
                s[4 * j]     = ex2(fmaf(s[4 * j], cs, -m0));
                s[4 * j + 1] = ex2(fmaf(s[4 * j + 1], cs, -m0));
                s[4 * j + 2] = ex2(fmaf(s[4 * j + 2], cs, -m1));
                s[4 * j + 3] = ex2(fmaf(s[4 * j + 3], cs, -m1));
                l0 += s[4 * j] + s[4 * j + 1];
                l1 += s[4 * j + 2] + s[4 * j + 3];
            }
            l0 += __shfl_xor_sync(0xffffffffu, l0, 1);
            l1 += __shfl_xor_sync(0xffffffffu, l1, 1);
            l0 += __shfl_xor_sync(0xffffffffu, l0, 2);
            l1 += __shfl_xor_sync(0xffffffffu, l1, 2);
            const float r0 = rcp(l0), r1 = rcp(l1);
#pragma unroll
            for (int j = 0; j < 8; j++) {
                pa[2 * j]     = pack_bf16(s[4 * j] * r0, s[4 * j + 1] * r0);
                pa[2 * j + 1] = pack_bf16(s[4 * j + 2] * r1, s[4 * j + 3] * r1);
            }
        }

        fence_regs(pa);
        const uint32_t dXt = ((sbase + kOffX + wg_uniform() * kXBytes) >> 4) | ((8192u >> 4) << 16);
        ring_wait(pa[15]);
        wg_fence();
        Gemm3<3>::run(acc, pa, dXt);
        wg_commit();
        if constexpr (PASS3 == 3) ring_pass();
        const int nxt = kNWG * (int)gridDim.x + (int)__reduce_or_sync(0xffffffffu, ticket);
        wg_wait0();
        fence_regs(acc);
        fence_regs(pa);

        if (((tid_now() >> 5) & 3) == 0) {
            asm volatile("bar.sync %0, 128;" ::"r"((tid_now() >> 7) + 1) : "memory");
            if (elect_one()) {
                const uint32_t wgl = tid_now() >> 7;
                const uint32_t bar = sbase + kOffBar + 8 * wgl;
                asm volatile("st.shared.u32 [%0], %1;" ::"r"(sbase + kOffBar + 64 + 4 * wgl), "r"(nxt) : "memory");
                if (nxt < kNWin) {
                    mbar_expect_tx(bar, kXBytes);
                    tma_load_x(sbase + kOffX + wgl * kXBytes, &tmx, bar, nxt);
                    prefetch_for_ticket(&tmp, nxt - kNWG * (int)gridDim.x);
                }
            }
            __syncwarp();
            asm volatile("bar.arrive %0, 128;" ::"r"((tid_now() >> 7) + 4) : "memory");
        } else {
            asm volatile("bar.arrive %0, 128;" ::"r"((tid_now() >> 7) + 1) : "memory");
        }
#pragma unroll
        for (int i = 0; i < 48; i++) fa[i] = pack_bf16(acc[2 * i], acc[2 * i + 1]);

        asm volatile("st.volatile.shared.v4.b32 [%4], {%0, %1, %2, %3};"
                     :: "r"(fa[44]), "r"(fa[45]), "r"(fa[46]), "r"(fa[47]), "r"(sbase + kOffStash + tid_now() * 16) : "memory");
        mbar_wait(sbase + kOffBar + 40, 0);
        fence_regs(fa);
        ring_wait(fa[43]);
        wg_fence();
        Gemm4<0, 1>::run(acc, fa, dWv);
        wg_commit();
        Gemm4<2, 10>::run(acc, fa, dWv);
        wg_commit();
        wg_wait1();
        uint32_t fl[4];
        asm volatile("ld.volatile.shared.v4.b32 {%0, %1, %2, %3}, [%4];"
                     : "=r"(fl[0]), "=r"(fl[1]), "=r"(fl[2]), "=r"(fl[3]) : "r"(sbase + kOffStash + tid_now() * 16) : "memory");
        wg_fence();
        wg192_rs<false, 0, koff(11, 24576)>(acc, fl, dWv);
        wg_commit();
        if (((tid_now() >> 5) & 3) == 0) {
            if (elect_one()) {
                if (nxt >= kNWin) {
                    uint32_t nd;
                    asm volatile("ld.shared.u32 %0, [%1];" : "=r"(nd) : "r"(sbase + kOffBar + 80) : "memory");
                    asm volatile("st.shared.v2.u32 [%0], {%1, %2};" ::"r"(sbase + kOffBar + 80), "r"(nd + 1), "r"(tid_now() >> 7) : "memory");
                }
            }
            __syncwarp();
        }
        ring_pass();
        if (((tid_now() >> 5) & 3) == 0) {
            if (elect_one()) {
                const int base = kNWG * (int)gridDim.x, t = nxt - base;
                if (t == kNWin - 1) { sc->cnt[0] = 0; sc->cnt[32] = 0; }
            }
            __syncwarp();
        } else {
            asm volatile("bar.sync %0, 128;" ::"r"((tid_now() >> 7) + 4) : "memory");
        }
        uint32_t pub;
        asm volatile("ld.shared.u32 %0, [%1];" : "=r"(pub) : "r"(sbase + kOffBar + 64 + 4 * (tid_now() >> 7)) : "memory");
        const int win_next = (int)__reduce_or_sync(0xffffffffu, pub);
        {
            const uint32_t ln = tid_now() & 31;
            hptr = reinterpret_cast<uint8_t*>(out) + (uint32_t)((win >> 6) * 8 * kHW + (win & 63) * 8 + 2 * ((tid_now() >> 5) & 3) * kHW + (ln >> 2)) * (uint32_t)(kC * 2) + (ln & 3) * 16;
        }
        win = win_next;
        const uint32_t dX1 = ((sbase + kOffX + wg_uniform() * kXBytes) >> 4) | (1u << 16);
        phase ^= 1;
        if (win < kNWin) mbar_wait(sbase + kOffBar + 8 * (tid_now() >> 7), phase);
        asm volatile("" : "+l"(hptr) :: "memory");
        wg_wait0();
        fence_regs(acc);
        fence_regs(fa);
        fence_regs(fl);

#pragma unroll
        for (int a = 0; a < 6; a++) {
            hv[2 * a].x     = pack_bf16(acc[16 * a + 0], acc[16 * a + 1]);
            hv[2 * a].y     = pack_bf16(acc[16 * a + 4], acc[16 * a + 5]);
            hv[2 * a].z     = pack_bf16(acc[16 * a + 8], acc[16 * a + 9]);
            hv[2 * a].w     = pack_bf16(acc[16 * a + 12], acc[16 * a + 13]);
            hv[2 * a + 1].x = pack_bf16(acc[16 * a + 2], acc[16 * a + 3]);
            hv[2 * a + 1].y = pack_bf16(acc[16 * a + 6], acc[16 * a + 7]);
            hv[2 * a + 1].z = pack_bf16(acc[16 * a + 10], acc[16 * a + 11]);
            hv[2 * a + 1].w = pack_bf16(acc[16 * a + 14], acc[16 * a + 15]);
        }
        if constexpr (slot_begin(0) > 0) {
            __syncwarp();
            store_slot<-1>(hv, hptr);
            __syncwarp();
        }
        if (win >= kNWin) break;
        ring_wait(hv[11].w);
        wg_fence();
        Gemm1St<11>::run(acc, dX1, dWm, hv, hptr);
        if constexpr (DRAW_AT == 1) ticket = draw_ticket(sc);
        if constexpr (slot_begin(12) < 12) store_paced<slot_begin(12)>(hv, hptr, clock_now());
        wg_wait0();
    }
    store_range<slot_begin(0), 12>(hv, hptr);
    {
        const uint32_t me = tid_now() >> 7, nx = me == kNWG - 1 ? 0 : me + 1;
        uint32_t nd, last;
        asm volatile("bar.sync %0, 128;" ::"r"(me + 1) : "memory");
        asm volatile("ld.volatile.shared.v2.u32 {%0, %1}, [%2];" : "=r"(nd), "=r"(last) : "r"(sbase + kOffBar + 80) : "memory");
        while (!(nd == kNWG && last == me)) {
            ring_wait();
            asm volatile("ld.volatile.shared.v2.u32 {%0, %1}, [%2];" : "=r"(nd), "=r"(last) : "r"(sbase + kOffBar + 80) : "memory");
            const bool all = nd == kNWG;
            if (!all || nx != last) ring_pass();
            if (all) break;
        }
    }
}

typedef CUresult (*EncodeTiledFn)(CUtensorMap*, CUtensorMapDataType, cuuint32_t, void*, const cuuint64_t*,
                                  const cuuint64_t*, const cuuint32_t*, const cuuint32_t*, CUtensorMapInterleave,
                                  CUtensorMapSwizzle, CUtensorMapL2promotion, CUtensorMapFloatOOBfill);

}

extern "C" void kernel_launch(void* const* d_in, const int* in_sizes, int n_in, void* d_out, int out_size) {
    (void)in_sizes; (void)n_in; (void)out_size;
    const __nv_bfloat16* x    = (const __nv_bfloat16*)d_in[0];
    const __nv_bfloat16* wqkv = (const __nv_bfloat16*)d_in[1];
    const __nv_bfloat16* wo   = (const __nv_bfloat16*)d_in[2];

    static EncodeTiledFn encode = nullptr;
    static int num_sms = 0;
    static void* scratch = nullptr;
    if (!encode) {
        void* fn = nullptr;
        cudaDriverEntryPointQueryResult qr;
        cudaGetDriverEntryPoint("cuTensorMapEncodeTiled", &fn, cudaEnableDefault, &qr);
        encode = (EncodeTiledFn)fn;
        int dev = 0;
        cudaGetDevice(&dev);
        cudaDeviceGetAttribute(&num_sms, cudaDevAttrMultiProcessorCount, dev);
        cudaGetSymbolAddress(&scratch, g_scratch);
        cudaFuncSetAttribute(swin_attn_kernel<false>, cudaFuncAttributeMaxDynamicSharedMemorySize, kSmemBytes);
        cudaFuncSetAttribute(swin_attn_kernel<true>, cudaFuncAttributeMaxDynamicSharedMemorySize, kSmemBytes);
    }
    CUtensorMap tmx;
    const cuuint64_t gdim[4] = {64, (cuuint64_t)kHW, (cuuint64_t)kHW, 3};
    const cuuint64_t gstr[3] = {(cuuint64_t)kC * 2, (cuuint64_t)kHW * kC * 2, 128};
    const cuuint32_t box[4] = {64, 8, 8, 3};
    const cuuint32_t estr[4] = {1, 1, 1, 1};
    encode(&tmx, CU_TENSOR_MAP_DATA_TYPE_BFLOAT16, 4, (void*)x, gdim, gstr, box, estr, CU_TENSOR_MAP_INTERLEAVE_NONE,
           CU_TENSOR_MAP_SWIZZLE_128B, CU_TENSOR_MAP_L2_PROMOTION_NONE, CU_TENSOR_MAP_FLOAT_OOB_FILL_NONE);

    CUtensorMap tmp;
    const cuuint64_t pdim[3] = {(cuuint64_t)kC, (cuuint64_t)kHW, (cuuint64_t)kHW};
    const cuuint64_t pstr[2] = {(cuuint64_t)kC * 2, (cuuint64_t)kHW * kC * 2};
    const cuuint32_t pbox[3] = {(cuuint32_t)kC, 8, 8};
    encode(&tmp, CU_TENSOR_MAP_DATA_TYPE_BFLOAT16, 3, (void*)x, pdim, pstr, pbox, estr, CU_TENSOR_MAP_INTERLEAVE_NONE,
           CU_TENSOR_MAP_SWIZZLE_NONE, CU_TENSOR_MAP_L2_PROMOTION_NONE, CU_TENSOR_MAP_FLOAT_OOB_FILL_NONE);
    CUtensorMap tmc;
    const cuuint32_t boxc[4] = {64, 8, 8, 1};
    encode(&tmc, CU_TENSOR_MAP_DATA_TYPE_BFLOAT16, 4, (void*)x, gdim, gstr, boxc, estr, CU_TENSOR_MAP_INTERLEAVE_NONE,
           CU_TENSOR_MAP_SWIZZLE_128B, CU_TENSOR_MAP_L2_PROMOTION_NONE, CU_TENSOR_MAP_FLOAT_OOB_FILL_NONE);
    if (num_sms >= kJobs)
        swin_attn_kernel<false><<<num_sms, kThreads, kSmemBytes, cudaStreamPerThread>>>(wqkv, wo, (__nv_bfloat16*)d_out, (Scratch*)scratch, tmx, tmp, tmc);
    else
        swin_attn_kernel<true><<<num_sms, kThreads, kSmemBytes, cudaStreamPerThread>>>(wqkv, wo, (__nv_bfloat16*)d_out, (Scratch*)scratch, tmx, tmp, tmc);
}
```

```cpp
#include <cuda_runtime.h>
#include <cuda_bf16.h>
#include <cuda.h>
#include <stdint.h>

namespace {

constexpr int kC      = 192;
constexpr int kHW     = 512;
#define MAXWIN 4096
constexpr int kNWin   = MAXWIN;
constexpr int kXBytes = 64 * kC * 2;
constexpr int kWBytes = kC * kC * 2;
constexpr int kNWG    = 3;
constexpr int kThreads = kNWG * 128;
constexpr int kJobsM  = 72;
constexpr int kJobs   = 120;
#define PF_LEAD 400
#define PF_UP 170
#define PF_DOWN 34
#define PF_MIN 150
#define TRK_T0 900
#define TRK_S 2000
#define POLL_T0 900
#define POLL_T 2600
#define POLL_TV 3300

constexpr int kOffWm  = 0;
constexpr int kOffWv  = kWBytes;
constexpr int kOffX   = 2 * kWBytes;
constexpr int kOffBar = kOffX + kNWG * kXBytes;
constexpr int kOffStash = kOffBar + 128;
constexpr int kOffProf = kOffStash + kThreads * 16;
constexpr int kSmemBytes = kOffProf;
constexpr uint32_t kSmemBase = 1024;

struct Scratch {
    uint4 wfold[2 * kWBytes / 16];
    uint32_t ticket[32];
    uint32_t cnt[64];
};
__device__ __align__(128) Scratch g_scratch;

__device__ __forceinline__ uint32_t smem_u32(const void* p) { return (uint32_t)__cvta_generic_to_shared(p); }

__device__ __forceinline__ void mbar_init(uint32_t bar, uint32_t count) {
    asm volatile("mbarrier.init.shared::cta.b64 [%0], %1;" ::"r"(bar), "r"(count) : "memory");
}
__device__ __forceinline__ void mbar_expect_tx(uint32_t bar, uint32_t bytes) {
    asm volatile("mbarrier.arrive.expect_tx.shared::cta.b64 _, [%0], %1;" ::"r"(bar), "r"(bytes) : "memory");
}
__device__ __forceinline__ void mbar_wait(uint32_t bar, uint32_t parity) {
    uint32_t ok;
    uint32_t spins = 0;
    do {
        asm volatile("{\n.reg .pred p;\n"
                     "mbarrier.try_wait.parity.shared::cta.b64 p, [%1], %2;\n"
                     "selp.b32 %0, 1, 0, p;\n}\n"
                     : "=r"(ok) : "r"(bar), "r"(parity) : "memory");
        if (++spins > (1u << 26)) __trap();
    } while (!ok);
}
__device__ __forceinline__ uint32_t tid_now() {
    uint32_t t;
    asm volatile("mov.u32 %0, %%tid.x;" : "=r"(t));
    return t;
}
__device__ __forceinline__ bool elect_one() {
    uint32_t pred;
    asm volatile("{\n.reg .pred p;\nelect.sync _|p, 0xffffffff;\nselp.b32 %0, 1, 0, p;\n}\n" : "=r"(pred));
    return pred != 0;
}
#define PASS1 11
#define PASS2 5
#define PASS3 3
__device__ __forceinline__ void ring_wait() {
    asm volatile("bar.sync %0, 256;" ::"r"((tid_now() >> 7) + 8) : "memory");
}
__device__ __forceinline__ void ring_wait(uint32_t dep) {
    asm volatile("{\n.reg .pred p;\n.reg .b32 t;\nsetp.eq.u32 p, %1, 0x7fc17fc1;\nselp.u32 t, 0, %0, p;\nbar.sync t, 256;\n}\n"
                 ::"r"((tid_now() >> 7) + 8), "r"(dep) : "memory");
}
__device__ __forceinline__ void ring_pass() {
    const uint32_t w = tid_now() >> 7;
    asm volatile("bar.arrive %0, 256;" ::"r"(w == kNWG - 1 ? 8u : w + 9u) : "memory");
}
__device__ __forceinline__ uint32_t wg_uniform() { return __reduce_or_sync(0xffffffffu, tid_now() >> 7); }
__device__ __forceinline__ void tma_load_x(uint32_t dst, const CUtensorMap* tm, uint32_t bar, int win) {
    const int wh = win >> 6, ww = win & 63;
    asm volatile("cp.async.bulk.tensor.4d.shared::cluster.global.mbarrier::complete_tx::bytes"
                 " [%0], [%1, {%3, %4, %5, %6}], [%2];"
                 ::"r"(dst), "l"(tm), "r"(bar), "r"(0), "r"(ww * 8), "r"(wh * 8), "r"(0) : "memory");
}
__device__ __forceinline__ void tma_load_x_chunk(uint32_t dst, const CUtensorMap* tm, uint32_t bar, int win, int chunk) {
    const int wh = win >> 6, ww = win & 63;
    asm volatile("cp.async.bulk.tensor.4d.shared::cluster.global.mbarrier::complete_tx::bytes"
                 " [%0], [%1, {%3, %4, %5, %6}], [%2];"
                 ::"r"(dst), "l"(tm), "r"(bar), "r"(0), "r"(ww * 8), "r"(wh * 8), "r"(chunk) : "memory");
}
__device__ __forceinline__ void bulk_load(uint32_t dst, const void* src, uint32_t bytes, uint32_t bar) {
    asm volatile("cp.async.bulk.shared::cluster.global.mbarrier::complete_tx::bytes [%0], [%1], %2, [%3];"
                 ::"r"(dst), "l"(src), "r"(bytes), "r"(bar) : "memory");
}

__device__ __forceinline__ void stg128(void* p, uint4 v) {
    asm volatile("st.global.v4.b32 [%0], {%1, %2, %3, %4};" ::"l"(p), "r"(v.x), "r"(v.y), "r"(v.z), "r"(v.w) : "memory");
}
__device__ __forceinline__ void wg_fence()  { asm volatile("wgmma.fence.sync.aligned;" ::: "memory"); }
__device__ __forceinline__ void wg_commit() { asm volatile("wgmma.commit_group.sync.aligned;" ::: "memory"); }
__device__ __forceinline__ void wg_wait0()  { asm volatile("wgmma.wait_group.sync.aligned 0;" ::: "memory"); }
__device__ __forceinline__ void wg_wait1()  { asm volatile("wgmma.wait_group.sync.aligned 1;" ::: "memory"); }

template <int N> __device__ __forceinline__ void fence_regs(float (&d)[N]) {
#pragma unroll
    for (int i = 0; i < N; i++) asm volatile("" : "+f"(d[i])::"memory");
}
template <int N> __device__ __forceinline__ void fence_regs(uint32_t (&d)[N]) {
#pragma unroll
    for (int i = 0; i < N; i++) asm volatile("" : "+r"(d[i])::"memory");
}

#define ACC8(c, d, i) c(d[i]), c(d[i + 1]), c(d[i + 2]), c(d[i + 3]), c(d[i + 4]), c(d[i + 5]), c(d[i + 6]), c(d[i + 7])
#define ACC32(c, d) ACC8(c, d, 0), ACC8(c, d, 8), ACC8(c, d, 16), ACC8(c, d, 24)
#define ACC96(c, d) ACC32(c, d), ACC8(c, d, 32), ACC8(c, d, 40), ACC8(c, d, 48), ACC8(c, d, 56), \
                    ACC8(c, d, 64), ACC8(c, d, 72), ACC8(c, d, 80), ACC8(c, d, 88)
#define C_IO(x) "+f"(x)
#define C_O(x) "=f"(x)
#define REGS32 "{%0, %1, %2, %3, %4, %5, %6, %7, %8, %9, %10, %11, %12, %13, %14, %15, " \
               "%16, %17, %18, %19, %20, %21, %22, %23, %24, %25, %26, %27, %28, %29, %30, %31}"
#define REGS96 "{%0, %1, %2, %3, %4, %5, %6, %7, %8, %9, %10, %11, %12, %13, %14, %15, " \
               "%16, %17, %18, %19, %20, %21, %22, %23, %24, %25, %26, %27, %28, %29, %30, %31, " \
               "%32, %33, %34, %35, %36, %37, %38, %39, %40, %41, %42, %43, %44, %45, %46, %47, " \
               "%48, %49, %50, %51, %52, %53, %54, %55, %56, %57, %58, %59, %60, %61, %62, %63, " \
               "%64, %65, %66, %67, %68, %69, %70, %71, %72, %73, %74, %75, %76, %77, %78, %79, " \
               "%80, %81, %82, %83, %84, %85, %86, %87, %88, %89, %90, %91, %92, %93, %94, %95}"

#define DESC_HI "0x40000040"
#define MK_DESC(name, lo, off) "add.u32 t, " lo ", " off ";\nmov.b64 " name ", {t, " DESC_HI "};\n"

template <bool First, int OA, int OB> __device__ __forceinline__ void wg192_ss(float (&d)[96], uint32_t la, uint32_t lb) {
    if constexpr (First)
        asm volatile("{\n.reg .pred p;\n.reg .b32 t;\n.reg .b64 da, db;\nsetp.ne.b32 p, 0, 0;\n"
                     MK_DESC("da", "%96", "%98") MK_DESC("db", "%97", "%99")
                     "wgmma.mma_async.sync.aligned.m64n192k16.f32.bf16.bf16 " REGS96 ", da, db, p, 1, 1, 0, 0;\n}\n"
                     : ACC96(C_O, d) : "r"(la), "r"(lb), "n"(OA), "n"(OB));
    else
        asm volatile("{\n.reg .pred p;\n.reg .b32 t;\n.reg .b64 da, db;\nsetp.ne.b32 p, 1, 0;\n"
                     MK_DESC("da", "%96", "%98") MK_DESC("db", "%97", "%99")
                     "wgmma.mma_async.sync.aligned.m64n192k16.f32.bf16.bf16 " REGS96 ", da, db, p, 1, 1, 0, 0;\n}\n"
                     : ACC96(C_IO, d) : "r"(la), "r"(lb), "n"(OA), "n"(OB));
}
template <bool First, int TB, int OB> __device__ __forceinline__ void wg192_rs(float (&d)[96], const uint32_t* a, uint32_t lb) {
    if constexpr (First)
        asm volatile("{\n.reg .pred p;\n.reg .b32 t;\n.reg .b64 db;\nsetp.ne.b32 p, 0, 0;\n"
                     MK_DESC("db", "%100", "%102")
                     "wgmma.mma_async.sync.aligned.m64n192k16.f32.bf16.bf16 " REGS96 ", {%96, %97, %98, %99}, db, p, 1, 1, %101;\n}\n"
                     : ACC96(C_O, d) : "r"(a[0]), "r"(a[1]), "r"(a[2]), "r"(a[3]), "r"(lb), "n"(TB), "n"(OB));
    else
        asm volatile("{\n.reg .pred p;\n.reg .b32 t;\n.reg .b64 db;\nsetp.ne.b32 p, 1, 0;\n"
                     MK_DESC("db", "%100", "%102")
                     "wgmma.mma_async.sync.aligned.m64n192k16.f32.bf16.bf16 " REGS96 ", {%96, %97, %98, %99}, db, p, 1, 1, %101;\n}\n"
                     : ACC96(C_IO, d) : "r"(a[0]), "r"(a[1]), "r"(a[2]), "r"(a[3]), "r"(lb), "n"(TB), "n"(OB));
}
template <bool First, int OB> __device__ __forceinline__ void wg64_rs(float (&d)[32], const uint32_t* a, uint32_t lb) {
    if constexpr (First)
        asm volatile("{\n.reg .pred p;\n.reg .b32 t;\n.reg .b64 db;\nsetp.ne.b32 p, 0, 0;\n"
                     MK_DESC("db", "%36", "%37")
                     "wgmma.mma_async.sync.aligned.m64n64k16.f32.bf16.bf16 " REGS32 ", {%32, %33, %34, %35}, db, p, 1, 1, 0;\n}\n"
                     : ACC32(C_O, d) : "r"(a[0]), "r"(a[1]), "r"(a[2]), "r"(a[3]), "r"(lb), "n"(OB));
    else
        asm volatile("{\n.reg .pred p;\n.reg .b32 t;\n.reg .b64 db;\nsetp.ne.b32 p, 1, 0;\n"
                     MK_DESC("db", "%36", "%37")
                     "wgmma.mma_async.sync.aligned.m64n64k16.f32.bf16.bf16 " REGS32 ", {%32, %33, %34, %35}, db, p, 1, 1, 0;\n}\n"
                     : ACC32(C_IO, d) : "r"(a[0]), "r"(a[1]), "r"(a[2]), "r"(a[3]), "r"(lb), "n"(OB));
}
__host__ __device__ constexpr int koff(int kk, int chunk) { return ((kk >> 2) * chunk + (kk & 3) * 32) >> 4; }

#define ST_SLOTS 0x2000000000001ull
__host__ __device__ constexpr int slot_begin(int i) {
    int b = 0;
    for (int k = -1; k < i; k++) b += (int)((ST_SLOTS >> (4 * (11 - k))) & 15);
    return b;
}
#define PACE_DT 160
template <int J, int E> __device__ __forceinline__ void store_range(const uint4 (&h)[12], uint8_t* hptr) {
    if constexpr (J < E) {
        constexpr int r = J / 6, a = J % 6;
        stg128(hptr + r * (kHW * kC * 2) + a * 64, h[2 * a + r]);
        store_range<J + 1, E>(h, hptr);
    }
}
template <int I> __device__ __forceinline__ void store_slot(const uint4 (&h)[12], uint8_t* hptr) {
    store_range<slot_begin(I), slot_begin(I + 1)>(h, hptr);
}
__device__ __forceinline__ uint32_t clock_now() {
    uint32_t t;
    asm volatile("mov.u32 %0, %%clock;" : "=r"(t));
    return t;
}
template <int J> __device__ __forceinline__ void store_paced(const uint4 (&h)[12], uint8_t* hptr, uint32_t t0) {
    if constexpr (J < 12) {
        while (clock_now() - t0 < (uint32_t)((J - slot_begin(12) + 1) * PACE_DT)) {}
        store_range<J, J + 1>(h, hptr);
        store_paced<J + 1>(h, hptr, t0);
    }
}
#define TAIL_DT 90
template <int J> __device__ __forceinline__ void store_tail(const uint4 (&h)[12], uint8_t* hptr, uint32_t t0) {
    if constexpr (J < 12) {
        if constexpr (J > slot_begin(0)) { while (clock_now() - t0 < (uint32_t)((J - slot_begin(0)) * TAIL_DT)) {} }
        store_range<J, J + 1>(h, hptr);
        store_tail<J + 1>(h, hptr, t0);
    }
}
template <int K> struct Gemm1St {
    static __device__ __forceinline__ void run(float (&d)[96], uint32_t lx, uint32_t lw, const uint4 (&h)[12], uint8_t* hptr) {
        if constexpr (K > 0) Gemm1St<K - 1>::run(d, lx, lw, h, hptr);
        wg192_ss<K == 0, koff(K, 8192), koff(K, 24576)>(d, lx, lw);
        if constexpr (K == 11) wg_commit();
        if constexpr (K == PASS1) ring_pass();
        if constexpr (slot_begin(K + 1) > slot_begin(K)) {
            __syncwarp();
            store_slot<K>(h, hptr);
            __syncwarp();
        }
    }
};
template <int K0, int K> struct Gemm1 {
    static __device__ __forceinline__ void run(float (&d)[96], uint32_t lx, uint32_t lw) {
        if constexpr (K > K0) Gemm1<K0, K - 1>::run(d, lx, lw);
        wg192_ss<K == 0, koff(K, 8192), koff(K, 24576)>(d, lx, lw);
    }
};
__device__ __forceinline__ uint32_t draw_ticket(Scratch* sc) {
    uint32_t ticket = 0;
    asm volatile("{\n.reg .pred p;\nsetp.eq.u32 p, %2, 0;\n@p atom.relaxed.gpu.global.inc.u32 %0, [%1], %3;\n}\n"
                 : "+r"(ticket) : "l"(sc->ticket), "r"(tid_now() & 127), "n"(kNWin - 1) : "memory");
    return ticket;
}
#define DRAW_AT 1
template <int KK> struct Gemm2 { static __device__ __forceinline__ void run(float (&d)[32], const uint32_t* a, uint32_t lx) {
    Gemm2<KK - 1>::run(d, a, lx); wg64_rs<KK == 0, koff(KK, 8192)>(d, a + 4 * KK, lx);
    if constexpr (KK == PASS2 && KK < 11) ring_pass(); } };
template <> struct Gemm2<-1> { static __device__ __forceinline__ void run(float (&)[32], const uint32_t*, uint32_t) {} };
template <int KK> struct Gemm3 { static __device__ __forceinline__ void run(float (&d)[96], const uint32_t* a, uint32_t lxt) {
    Gemm3<KK - 1>::run(d, a, lxt); wg192_rs<KK == 0, 1, KK * (2048 >> 4)>(d, a + 4 * KK, lxt);
    if constexpr (KK == PASS3 && KK < 3) ring_pass(); } };
template <> struct Gemm3<-1> { static __device__ __forceinline__ void run(float (&)[96], const uint32_t*, uint32_t) {} };
template <int K0, int KK> struct Gemm4 { static __device__ __forceinline__ void run(float (&d)[96], const uint32_t* a, uint32_t lw) {
    if constexpr (KK > K0) Gemm4<K0, KK - 1>::run(d, a, lw);
    wg192_rs<KK == 0, 0, koff(KK, 24576)>(d, a + 4 * KK, lw); } };

__device__ __forceinline__ uint32_t pack_bf16(float lo, float hi) {
    uint32_t r;
    asm("cvt.rn.bf16x2.f32 %0, %1, %2;" : "=r"(r) : "f"(hi), "f"(lo));
    return r;
}
__device__ __forceinline__ float ex2(float x) {
    float r;
    asm("ex2.approx.ftz.f32 %0, %1;" : "=f"(r) : "f"(x));
    return r;
}
__device__ __forceinline__ float rcp(float x) {
    float r;
    asm("rcp.approx.ftz.f32 %0, %1;" : "=f"(r) : "f"(x));
    return r;
}

__device__ __forceinline__ int fold_offset(int n, int k0, int q) {
    const int u = ((k0 & 63) >> 3) + (q >> 1);
    return (k0 >> 6) * 24576 + (q & 1) * 8 + n * 128 + ((u ^ (n & 7)) << 4);
}
__device__ __forceinline__ void mma16816x2(float (&c)[4], float (&d)[4], const uint32_t (&a)[4], const uint32_t (&b)[4]) {
    asm volatile("mma.sync.aligned.m16n8k16.row.col.f32.bf16.bf16.f32 {%0,%1,%2,%3}, {%8,%9,%10,%11}, {%12,%13}, {%0,%1,%2,%3};\n"
                 "mma.sync.aligned.m16n8k16.row.col.f32.bf16.bf16.f32 {%4,%5,%6,%7}, {%8,%9,%10,%11}, {%14,%15}, {%4,%5,%6,%7};"
                 : "+f"(c[0]), "+f"(c[1]), "+f"(c[2]), "+f"(c[3]), "+f"(d[0]), "+f"(d[1]), "+f"(d[2]), "+f"(d[3])
                 : "r"(a[0]), "r"(a[1]), "r"(a[2]), "r"(a[3]), "r"(b[0]), "r"(b[1]), "r"(b[2]), "r"(b[3]));
}
__device__ __forceinline__ void cp_async16(uint32_t dst, const void* src) {
    asm volatile("cp.async.cg.shared.global [%0], [%1], 16;" ::"r"(dst), "l"(src) : "memory");
}
template <bool kTrans> __device__ __forceinline__ void ldsm4(uint32_t (&r)[4], uint32_t addr) {
    if constexpr (kTrans)
        asm volatile("ldmatrix.sync.aligned.m8n8.x4.trans.shared.b16 {%0, %1, %2, %3}, [%4];" : "=r"(r[0]), "=r"(r[1]), "=r"(r[2]), "=r"(r[3]) : "r"(addr) : "memory");
    else
        asm volatile("ldmatrix.sync.aligned.m8n8.x4.shared.b16 {%0, %1, %2, %3}, [%4];" : "=r"(r[0]), "=r"(r[1]), "=r"(r[2]), "=r"(r[3]) : "r"(addr) : "memory");
}
__device__ __forceinline__ void fold_job(Scratch* sc, const __nv_bfloat16* __restrict__ wqkv, const __nv_bfloat16* __restrict__ wo,
                                         int job, int warp, int lane) {
    const bool vo = job >= kJobsM;
    const int nw = vo ? 3 : 2, tile0 = vo ? 3 * (job - kJobsM) : 2 * job;
    const int n0 = (tile0 / 12) * 16, k0 = (tile0 % 12 + max(warp, 1) - 1) * 16;
    const uint32_t stage = kSmemBase + kOffWv;
    if (warp <= nw) {
        if (vo && warp == 0) {
            const char* src = reinterpret_cast<const char*>(wo + (lane >> 1) * kC + n0 + (lane & 1) * 8);
            const uint32_t dst = stage + ((lane ^ ((lane >> 3) & 1)) << 4);
#pragma unroll
            for (int i = 0; i < 12; i++) cp_async16(dst + i * 512, src + i * 16 * kC * 2);
        } else {
            const int row0 = warp == 0 ? n0 : k0, col0 = warp == 0 ? kC : vo ? 2 * kC : 0;
            const char* src = reinterpret_cast<const char*>(wqkv + (row0 + (lane >> 3)) * (3 * kC) + col0 + (lane & 7) * 8);
            const uint32_t dst = stage + warp * 6144 + (lane >> 3) * 384 + (((lane & 7) ^ (lane >> 3)) << 4);
#pragma unroll
            for (int i = 0; i < 12; i++) cp_async16((dst ^ (((i / 3) & 1) << 6)) + (i / 3) * 1536 + (i % 3) * 128, src + (i / 3) * 4 * 3 * kC * 2 + (i % 3) * 128);
        }
        asm volatile("cp.async.wait_all;" ::: "memory");
        asm volatile("bar.sync 13, %0;" ::"r"(32 * nw + 32) : "memory");
    }
    if (warp == 0 || (warp > nw && warp != 4)) return;
    const int g = lane >> 2, q = lane & 3, mi = lane >> 3, r8 = lane & 7;
    uint32_t A[12][4], B[12][4];
    {
        const int row = 4 * (r8 >> 1) + (r8 & 1) + 2 * (mi >> 1);
        const uint32_t base = stage + (warp & 3) * 6144 + row * 384 + (((mi & 1) ^ (row & 7)) << 4);
#pragma unroll
        for (int ks = 0; ks < 12; ks++) ldsm4<false>(B[ks], (base ^ ((ks & 3) << 5)) + (ks >> 2) * 128);
    }
    if (vo) {
        const int c = r8 + 8 * (mi >> 1);
        const uint32_t base = stage + (((2 * c + (mi & 1)) ^ ((c >> 2) & 1)) << 4);
#pragma unroll
        for (int ks = 0; ks < 12; ks++) ldsm4<true>(A[ks], base + ks * 512);
    } else {
        const uint32_t base = stage + (r8 + 8 * (mi & 1)) * 384 + (((mi >> 1) ^ r8) << 4);
#pragma unroll
        for (int ks = 0; ks < 12; ks++) ldsm4<false>(A[ks], (base ^ ((ks & 3) << 5)) + (ks >> 2) * 128);
    }
    float c0[4] = {0.f, 0.f, 0.f, 0.f}, c1[4] = {0.f, 0.f, 0.f, 0.f}, c2[4] = {0.f, 0.f, 0.f, 0.f}, c3[4] = {0.f, 0.f, 0.f, 0.f};
#pragma unroll
    for (int ks = 0; ks < 12; ks += 2) {
        mma16816x2(c0, c1, A[ks], B[ks]);
        mma16816x2(c2, c3, A[ks + 1], B[ks + 1]);
    }
#pragma unroll
    for (int i = 0; i < 4; i++) { c0[i] += c2[i]; c1[i] += c3[i]; }
    const int ch = n0 + g;
    const int n = vo ? 32 * (ch >> 5) + 8 * ((ch >> 1) & 3) + 2 * ((ch >> 3) & 3) + (ch & 1) : ch;
    char* img = reinterpret_cast<char*>(sc->wfold) + (vo ? kWBytes : 0);
    asm volatile("{\n.reg .pred p;\nsetp.ne.u32 p, %6, 4;\n@p st.global.v2.u32 [%0], {%2, %3};\n@p st.global.v2.u32 [%1], {%4, %5};\n}\n"
                 ::"l"(img + fold_offset(n, k0, q)), "l"(img + fold_offset(n + (vo ? 2 : 8), k0, q)),
                   "r"(pack_bf16(c0[0], c0[1])), "r"(pack_bf16(c1[0], c1[1])), "r"(pack_bf16(c0[2], c0[3])), "r"(pack_bf16(c1[2], c1[3])),
                   "r"(warp) : "memory");
    if (warp == 4) return;
    asm volatile("bar.sync 12, %0;" ::"r"(32 * nw) : "memory");
    if (lane == 0 && warp == 1) asm volatile("red.release.gpu.global.add.u32 [%0], 1;" ::"l"(&sc->cnt[vo ? 32 : 0]) : "memory");
}

__device__ __forceinline__ uint32_t ld_acquire(const uint32_t* p) {
    uint32_t v;
    asm volatile("ld.acquire.gpu.global.u32 %0, [%1];" : "=r"(v) : "l"(p) : "memory");
    return v;
}
__device__ __forceinline__ void prefetch_x(const CUtensorMap* tm, int win) {
    const int wh = win >> 6, ww = win & 63;
    asm volatile("cp.async.bulk.prefetch.tensor.3d.L2.global.tile [%0, {%1, %2, %3}];"
                 ::"l"(tm), "r"(0), "r"(ww * 8), "r"(wh * 8) : "memory");
}

__device__ __forceinline__ void prefetch_for_ticket(const CUtensorMap* tmp, int t) {
    const int base = kNWG * (int)gridDim.x;
    auto lead = [&](int tt) {
        int down = max(((kNWin - base - tt) * PF_DOWN) >> 8, PF_MIN);
        return min(min((tt * PF_UP) >> 8, PF_LEAD), down);
    };
    const int hi = base + t + lead(t);
    int lo = max(base + t - 1 + lead(t - 1), base + t) + 1;
#pragma unroll 1
    for (; lo <= hi && lo < kNWin; lo++) prefetch_x(tmp, lo);
}

template <bool kFewSMs>
__global__ void __launch_bounds__(kThreads, 1)
swin_attn_kernel(const __nv_bfloat16* __restrict__ wqkv, const __nv_bfloat16* __restrict__ wo, __nv_bfloat16* __restrict__ out, Scratch* sc,
                 const __grid_constant__ CUtensorMap tmx, const __grid_constant__ CUtensorMap tmp, const __grid_constant__ CUtensorMap tmc) {
    extern __shared__ uint8_t smem_raw[];
    constexpr uint32_t sbase = kSmemBase;
    const uint32_t t_start = clock_now();
    if (smem_u32(smem_raw) != kSmemBase) __trap();
    const int tid = threadIdx.x, lane = tid & 31;
    const uint32_t warpu = __reduce_or_sync(0xffffffffu, (uint32_t)tid >> 5), wgu = warpu >> 2;
    const int warp = (int)warpu, wg = (int)wgu;
    const int G = gridDim.x;
    const uint32_t bar_full = sbase + kOffBar + 8 * wg;
    const uint32_t bar_w0 = sbase + kOffBar + 32, bar_w1 = bar_w0 + 8;
    int win = wg * G + blockIdx.x;

    if (warp > 4) {
        if (warp == 10) {
            asm volatile("bar.arrive 0, %0;" ::"n"(kThreads) : "memory");
            if (lane == 0) {
                asm volatile("prefetch.tensormap [%0];" ::"l"(&tmp) : "memory");
                asm volatile("prefetch.tensormap [%0];" ::"l"(&tmc) : "memory");
                asm volatile("prefetch.tensormap [%0];" ::"l"(&tmx) : "memory");
                const uint32_t due = TRK_T0 + (uint32_t)(blockIdx.x * TRK_S) / (uint32_t)G;
#pragma unroll 1
                for (int i = 0; i < kNWG; i++) {
                    while (clock_now() - t_start < due + i * TRK_S) {}
                    prefetch_x(&tmp, i * G + blockIdx.x);
                }
            }
            __syncwarp();
        } else if (warp == 11) {
            if (lane == 0) {
#pragma unroll
                for (int w = 0; w < kNWG; w++) mbar_init(sbase + kOffBar + 8 * w, 1);
                mbar_init(bar_w0, 1);
                mbar_init(bar_w1, 1);
                mbar_init(sbase + kOffBar + 48, 1);
                mbar_init(sbase + kOffBar + 56, 1);
                asm volatile("st.shared.v2.u32 [%0], {%1, %1};" ::"r"(sbase + kOffBar + 80), "r"(0) : "memory");
                asm volatile("fence.mbarrier_init.release.cluster;" ::: "memory");
                asm volatile("mbarrier.arrive.shared::cta.b64 _, [%0];" ::"r"(sbase + kOffBar) : "memory");
            }
            __syncwarp();
            asm volatile("bar.arrive 0, %0;" ::"n"(kThreads) : "memory");
            if (lane == 0) {
                const char* img = reinterpret_cast<const char*>(sc->wfold);
                uint32_t spins = 0;
                while (clock_now() - t_start < POLL_T0) {}
                uint32_t done = ld_acquire(sc->cnt);
                while (clock_now() - t_start < POLL_T) {}
                while (done < kJobsM) { done = ld_acquire(sc->cnt); if (++spins > (1u << 24)) __trap(); }
                asm volatile("fence.proxy.async.global;" ::: "memory");
#pragma unroll
                for (int c = 0; c < 3; c++) {
                    const uint32_t bar = c == 0 ? bar_w0 : sbase + kOffBar + 40 + 8 * c;
                    mbar_expect_tx(bar, 24576 + 8192);
                    tma_load_x_chunk(sbase + kOffX + c * 8192, &tmc, bar, blockIdx.x, c);
                    bulk_load(sbase + kOffWm + c * 24576, img + c * 24576, 24576, bar);
                }
                mbar_wait(bar_w0, 0);
                mbar_expect_tx(sbase + kOffBar + 8, kXBytes);
                tma_load_x(sbase + kOffX + kXBytes, &tmx, sbase + kOffBar + 8, G + blockIdx.x);
            }
            __syncwarp();
        } else {
            asm volatile("bar.sync 0, %0;" ::"n"(kThreads) : "memory");
            if (warp == 9) {
                if (lane == 0) {
                    uint32_t spins = 0;
                    while (clock_now() - t_start < POLL_TV) {}
                    while (ld_acquire(sc->cnt + 32) < kJobs - kJobsM) { if (++spins > (1u << 24)) __trap(); }
                    mbar_wait(sbase + kOffBar + 48, 0);
                    asm volatile("fence.proxy.async;" ::: "memory");
                    mbar_expect_tx(bar_w1, kWBytes);
#pragma unroll
                    for (int c = 0; c < 3; c++)
                        bulk_load(sbase + kOffWv + c * 24576, reinterpret_cast<const char*>(sc->wfold) + kWBytes + c * 24576, 24576, bar_w1);
                    mbar_expect_tx(sbase + kOffBar + 16, kXBytes);
                    tma_load_x(sbase + kOffX + 2 * kXBytes, &tmx, sbase + kOffBar + 16, 2 * G + blockIdx.x);
                }
                __syncwarp();
            }
        }
    } else {
        if constexpr (kFewSMs) {
#pragma unroll 1
            for (int j = blockIdx.x; j < kJobs; j += G) {
                fold_job(sc, wqkv, wo, j, warp, lane);
                asm volatile("bar.sync 14, 160;" ::: "memory");
            }
        } else {
            if (blockIdx.x < kJobs) fold_job(sc, wqkv, wo, blockIdx.x, warp, lane);
        }
        asm volatile("bar.sync 0, %0;" ::"n"(kThreads) : "memory");
    }
    if (wg == kNWG - 1) asm volatile("bar.sync 7, 128;" ::: "memory");
    if (wg == 1) asm volatile("bar.arrive 8, 256;" ::: "memory");

    constexpr uint32_t dWm = ((sbase + kOffWm) >> 4) | (1u << 16);
    constexpr uint32_t dWv = ((sbase + kOffWv) >> 4) | (1u << 16);
    const float cs = 0.07216878364870322f * 1.4426950408889634f;
    mbar_wait(bar_w0, 0);
    if (wg != 0) mbar_wait(bar_full, 0);

    uint4 hv[12];
    uint8_t* hptr;
    uint32_t phase = 0;
    float acc[96];
    uint32_t ticket = 0;
    {
        const uint32_t dX = ((sbase + kOffX + wg_uniform() * kXBytes) >> 4) | (1u << 16);
        if (wg != 0) ring_wait();
        wg_fence();
        Gemm1<0, 3>::run(acc, dX, dWm);
        mbar_wait(sbase + kOffBar + 48, 0);
        wg_fence();
        Gemm1<4, 7>::run(acc, dX, dWm);
        mbar_wait(sbase + kOffBar + 56, 0);
        wg_fence();
        Gemm1<8, 11>::run(acc, dX, dWm);
        wg_commit();
        if (wg != 0) asm volatile("bar.arrive 8, 256;" ::: "memory");
        if constexpr (DRAW_AT == 1) ticket = draw_ticket(sc);
        wg_wait0();
    }

    while (true) {
        uint32_t fa[48];
        const uint32_t dX = ((sbase + kOffX + wg_uniform() * kXBytes) >> 4) | (1u << 16);
        fence_regs(acc);
#pragma unroll
        for (int i = 0; i < 48; i++) fa[i] = pack_bf16(acc[2 * i], acc[2 * i + 1]);

        float s[32];
        fence_regs(fa);
        ring_wait(fa[47]);
        wg_fence();
        Gemm2<11>::run(s, fa, dX);
        wg_commit();
        if constexpr (PASS2 == 11) ring_pass();
        if constexpr (DRAW_AT == 2) ticket = draw_ticket(sc);
        wg_wait0();
        fence_regs(s);
        fence_regs(fa);

        uint32_t pa[16];
        {
            float a0[8], a1[8];
#pragma unroll
            for (int j = 0; j < 8; j++) { a0[j] = fmaxf(s[4 * j], s[4 * j + 1]); a1[j] = fmaxf(s[4 * j + 2], s[4 * j + 3]); }
#pragma unroll
            for (int d = 4; d > 0; d >>= 1)
#pragma unroll
                for (int j = 0; j < d; j++) { a0[j] = fmaxf(a0[j], a0[j + d]); a1[j] = fmaxf(a1[j], a1[j + d]); }
            float m0 = a0[0], m1 = a1[0];
            m0 = fmaxf(m0, __shfl_xor_sync(0xffffffffu, m0, 1));
            m1 = fmaxf(m1, __shfl_xor_sync(0xffffffffu, m1, 1));
            m0 = fmaxf(m0, __shfl_xor_sync(0xffffffffu, m0, 2));
            m1 = fmaxf(m1, __shfl_xor_sync(0xffffffffu, m1, 2));
            m0 *= cs; m1 *= cs;
            float l0 = 0.f, l1 = 0.f;
#pragma unroll
            for (int j = 0; j < 8; j++) {
                s[4 * j]     = ex2(fmaf(s[4 * j], cs, -m0));
                s[4 * j + 1] = ex2(fmaf(s[4 * j + 1], cs, -m0));
                s[4 * j + 2] = ex2(fmaf(s[4 * j + 2], cs, -m1));
                s[4 * j + 3] = ex2(fmaf(s[4 * j + 3], cs, -m1));
                l0 += s[4 * j] + s[4 * j + 1];
                l1 += s[4 * j + 2] + s[4 * j + 3];
            }
            l0 += __shfl_xor_sync(0xffffffffu, l0, 1);
            l1 += __shfl_xor_sync(0xffffffffu, l1, 1);
            l0 += __shfl_xor_sync(0xffffffffu, l0, 2);
            l1 += __shfl_xor_sync(0xffffffffu, l1, 2);
            const float r0 = rcp(l0), r1 = rcp(l1);
#pragma unroll
            for (int j = 0; j < 8; j++) {
                pa[2 * j]     = pack_bf16(s[4 * j] * r0, s[4 * j + 1] * r0);
                pa[2 * j + 1] = pack_bf16(s[4 * j + 2] * r1, s[4 * j + 3] * r1);
            }
        }

        fence_regs(pa);
        const uint32_t dXt = ((sbase + kOffX + wg_uniform() * kXBytes) >> 4) | ((8192u >> 4) << 16);
        ring_wait(pa[15]);
        wg_fence();
        Gemm3<3>::run(acc, pa, dXt);
        wg_commit();
        if constexpr (PASS3 == 3) ring_pass();
        const int nxt = kNWG * (int)gridDim.x + (int)__reduce_or_sync(0xffffffffu, ticket);
        wg_wait0();
        fence_regs(acc);
        fence_regs(pa);

        if (((tid_now() >> 5) & 3) == 0) {
            asm volatile("bar.sync %0, 128;" ::"r"((tid_now() >> 7) + 1) : "memory");
            if (elect_one()) {
                const uint32_t wgl = tid_now() >> 7;
                const uint32_t bar = sbase + kOffBar + 8 * wgl;
                asm volatile("st.shared.u32 [%0], %1;" ::"r"(sbase + kOffBar + 64 + 4 * wgl), "r"(nxt) : "memory");
                if (nxt < kNWin) {
                    mbar_expect_tx(bar, kXBytes);
                    tma_load_x(sbase + kOffX + wgl * kXBytes, &tmx, bar, nxt);
                    prefetch_for_ticket(&tmp, nxt - kNWG * (int)gridDim.x);
                }
            }
            __syncwarp();
            asm volatile("bar.arrive %0, 128;" ::"r"((tid_now() >> 7) + 4) : "memory");
        } else {
            asm volatile("bar.arrive %0, 128;" ::"r"((tid_now() >> 7) + 1) : "memory");
        }
#pragma unroll
        for (int i = 0; i < 48; i++) fa[i] = pack_bf16(acc[2 * i], acc[2 * i + 1]);

        asm volatile("st.volatile.shared.v4.b32 [%4], {%0, %1, %2, %3};"
                     :: "r"(fa[44]), "r"(fa[45]), "r"(fa[46]), "r"(fa[47]), "r"(sbase + kOffStash + tid_now() * 16) : "memory");
        mbar_wait(sbase + kOffBar + 40, 0);
        fence_regs(fa);
        ring_wait(fa[43]);
        wg_fence();
        Gemm4<0, 1>::run(acc, fa, dWv);
        wg_commit();
        Gemm4<2, 10>::run(acc, fa, dWv);
        wg_commit();
        wg_wait1();
        uint32_t fl[4];
        asm volatile("ld.volatile.shared.v4.b32 {%0, %1, %2, %3}, [%4];"
                     : "=r"(fl[0]), "=r"(fl[1]), "=r"(fl[2]), "=r"(fl[3]) : "r"(sbase + kOffStash + tid_now() * 16) : "memory");
        wg_fence();
        wg192_rs<false, 0, koff(11, 24576)>(acc, fl, dWv);
        wg_commit();
        if (((tid_now() >> 5) & 3) == 0) {
            if (elect_one()) {
                if (nxt >= kNWin) {
                    uint32_t nd;
                    asm volatile("ld.shared.u32 %0, [%1];" : "=r"(nd) : "r"(sbase + kOffBar + 80) : "memory");
                    asm volatile("st.shared.v2.u32 [%0], {%1, %2};" ::"r"(sbase + kOffBar + 80), "r"(nd + 1), "r"(tid_now() >> 7) : "memory");
                }
            }
            __syncwarp();
        }
        ring_pass();
        if (((tid_now() >> 5) & 3) == 0) {
            if (elect_one()) {
                const int base = kNWG * (int)gridDim.x, t = nxt - base;
                if (t == kNWin - 1) { sc->cnt[0] = 0; sc->cnt[32] = 0; }
            }
            __syncwarp();
        } else {
            asm volatile("bar.sync %0, 128;" ::"r"((tid_now() >> 7) + 4) : "memory");
        }
        uint32_t pub;
        asm volatile("ld.shared.u32 %0, [%1];" : "=r"(pub) : "r"(sbase + kOffBar + 64 + 4 * (tid_now() >> 7)) : "memory");
        const int win_next = (int)__reduce_or_sync(0xffffffffu, pub);
        {
            const uint32_t ln = tid_now() & 31;
            hptr = reinterpret_cast<uint8_t*>(out) + (uint32_t)((win >> 6) * 8 * kHW + (win & 63) * 8 + 2 * ((tid_now() >> 5) & 3) * kHW + (ln >> 2)) * (uint32_t)(kC * 2) + (ln & 3) * 16;
        }
        win = win_next;
        const uint32_t dX1 = ((sbase + kOffX + wg_uniform() * kXBytes) >> 4) | (1u << 16);
        phase ^= 1;
        if (win < kNWin) mbar_wait(sbase + kOffBar + 8 * (tid_now() >> 7), phase);
        asm volatile("" : "+l"(hptr) :: "memory");
        wg_wait0();
        fence_regs(acc);
        fence_regs(fa);
        fence_regs(fl);

#pragma unroll
        for (int a = 0; a < 6; a++) {
            hv[2 * a].x     = pack_bf16(acc[16 * a + 0], acc[16 * a + 1]);
            hv[2 * a].y     = pack_bf16(acc[16 * a + 4], acc[16 * a + 5]);
            hv[2 * a].z     = pack_bf16(acc[16 * a + 8], acc[16 * a + 9]);
            hv[2 * a].w     = pack_bf16(acc[16 * a + 12], acc[16 * a + 13]);
            hv[2 * a + 1].x = pack_bf16(acc[16 * a + 2], acc[16 * a + 3]);
            hv[2 * a + 1].y = pack_bf16(acc[16 * a + 6], acc[16 * a + 7]);
            hv[2 * a + 1].z = pack_bf16(acc[16 * a + 10], acc[16 * a + 11]);
            hv[2 * a + 1].w = pack_bf16(acc[16 * a + 14], acc[16 * a + 15]);
        }
        if constexpr (slot_begin(0) > 0) {
            __syncwarp();
            store_slot<-1>(hv, hptr);
            __syncwarp();
        }
        if (win >= kNWin) break;
        ring_wait(hv[11].w);
        wg_fence();
        Gemm1St<11>::run(acc, dX1, dWm, hv, hptr);
        if constexpr (DRAW_AT == 1) ticket = draw_ticket(sc);
        if constexpr (slot_begin(12) < 12) store_paced<slot_begin(12)>(hv, hptr, clock_now());
        wg_wait0();
    }
    {
        const uint32_t me = tid_now() >> 7, nx = me == kNWG - 1 ? 0 : me + 1;
        uint32_t nd, last;
        asm volatile("bar.sync %0, 128;" ::"r"(me + 1) : "memory");
        asm volatile("ld.volatile.shared.v2.u32 {%0, %1}, [%2];" : "=r"(nd), "=r"(last) : "r"(sbase + kOffBar + 80) : "memory");
        if (nd == kNWG && last == me) {
            store_range<slot_begin(0), 12>(hv, hptr);
        } else {
            bool stored = false;
            while (true) {
                ring_wait();
                asm volatile("ld.volatile.shared.v2.u32 {%0, %1}, [%2];" : "=r"(nd), "=r"(last) : "r"(sbase + kOffBar + 80) : "memory");
                const bool all = nd == kNWG;
                if (!all || nx != last) ring_pass();
                if (!stored) { store_tail<slot_begin(0)>(hv, hptr, clock_now()); stored = true; }
                if (all) break;
            }
        }
    }
}

typedef CUresult (*EncodeTiledFn)(CUtensorMap*, CUtensorMapDataType, cuuint32_t, void*, const cuuint64_t*,
                                  const cuuint64_t*, const cuuint32_t*, const cuuint32_t*, CUtensorMapInterleave,
                                  CUtensorMapSwizzle, CUtensorMapL2promotion, CUtensorMapFloatOOBfill);

}

extern "C" void kernel_launch(void* const* d_in, const int* in_sizes, int n_in, void* d_out, int out_size) {
    (void)in_sizes; (void)n_in; (void)out_size;
    const __nv_bfloat16* x    = (const __nv_bfloat16*)d_in[0];
    const __nv_bfloat16* wqkv = (const __nv_bfloat16*)d_in[1];
    const __nv_bfloat16* wo   = (const __nv_bfloat16*)d_in[2];

    static EncodeTiledFn encode = nullptr;
    static int num_sms = 0;
    static void* scratch = nullptr;
    if (!encode) {
        void* fn = nullptr;
        cudaDriverEntryPointQueryResult qr;
        cudaGetDriverEntryPoint("cuTensorMapEncodeTiled", &fn, cudaEnableDefault, &qr);
        encode = (EncodeTiledFn)fn;
        int dev = 0;
        cudaGetDevice(&dev);
        cudaDeviceGetAttribute(&num_sms, cudaDevAttrMultiProcessorCount, dev);
        cudaGetSymbolAddress(&scratch, g_scratch);
        cudaFuncSetAttribute(swin_attn_kernel<false>, cudaFuncAttributeMaxDynamicSharedMemorySize, kSmemBytes);
        cudaFuncSetAttribute(swin_attn_kernel<true>, cudaFuncAttributeMaxDynamicSharedMemorySize, kSmemBytes);
    }
    CUtensorMap tmx;
    const cuuint64_t gdim[4] = {64, (cuuint64_t)kHW, (cuuint64_t)kHW, 3};
    const cuuint64_t gstr[3] = {(cuuint64_t)kC * 2, (cuuint64_t)kHW * kC * 2, 128};
    const cuuint32_t box[4] = {64, 8, 8, 3};
    const cuuint32_t estr[4] = {1, 1, 1, 1};
    encode(&tmx, CU_TENSOR_MAP_DATA_TYPE_BFLOAT16, 4, (void*)x, gdim, gstr, box, estr, CU_TENSOR_MAP_INTERLEAVE_NONE,
           CU_TENSOR_MAP_SWIZZLE_128B, CU_TENSOR_MAP_L2_PROMOTION_NONE, CU_TENSOR_MAP_FLOAT_OOB_FILL_NONE);

    CUtensorMap tmp;
    const cuuint64_t pdim[3] = {(cuuint64_t)kC, (cuuint64_t)kHW, (cuuint64_t)kHW};
    const cuuint64_t pstr[2] = {(cuuint64_t)kC * 2, (cuuint64_t)kHW * kC * 2};
    const cuuint32_t pbox[3] = {(cuuint32_t)kC, 8, 8};
    encode(&tmp, CU_TENSOR_MAP_DATA_TYPE_BFLOAT16, 3, (void*)x, pdim, pstr, pbox, estr, CU_TENSOR_MAP_INTERLEAVE_NONE,
           CU_TENSOR_MAP_SWIZZLE_NONE, CU_TENSOR_MAP_L2_PROMOTION_NONE, CU_TENSOR_MAP_FLOAT_OOB_FILL_NONE);
    CUtensorMap tmc;
    const cuuint32_t boxc[4] = {64, 8, 8, 1};
    encode(&tmc, CU_TENSOR_MAP_DATA_TYPE_BFLOAT16, 4, (void*)x, gdim, gstr, boxc, estr, CU_TENSOR_MAP_INTERLEAVE_NONE,
           CU_TENSOR_MAP_SWIZZLE_128B, CU_TENSOR_MAP_L2_PROMOTION_NONE, CU_TENSOR_MAP_FLOAT_OOB_FILL_NONE);
    if (num_sms >= kJobs)
        swin_attn_kernel<false><<<num_sms, kThreads, kSmemBytes, cudaStreamPerThread>>>(wqkv, wo, (__nv_bfloat16*)d_out, (Scratch*)scratch, tmx, tmp, tmc);
    else
        swin_attn_kernel<true><<<num_sms, kThreads, kSmemBytes, cudaStreamPerThread>>>(wqkv, wo, (__nv_bfloat16*)d_out, (Scratch*)scratch, tmx, tmp, tmc);
}
```

```cpp
#include <cuda_runtime.h>
#include <cuda_bf16.h>
#include <cuda.h>
#include <stdint.h>

namespace {

constexpr int kC      = 192;
constexpr int kHW     = 512;
#define MAXWIN 4096
constexpr int kNWin   = MAXWIN;
constexpr int kXBytes = 64 * kC * 2;
constexpr int kWBytes = kC * kC * 2;
constexpr int kNWG    = 3;
constexpr int kThreads = kNWG * 128;
constexpr int kJobsM  = 72;
constexpr int kJobs   = 120;
constexpr int kWarmW  = 4;
#define PF_LEAD 400
#define PF_UP 170
#define PF_DOWN 34
#define PF_MIN 150
#define TRK_T0 900
#define TRK_S 2000
#define POLL_T0 900
#define POLL_T 2600
#define POLL_TV 3300

constexpr int kOffWm  = 0;
constexpr int kOffWv  = kWBytes;
constexpr int kOffX   = 2 * kWBytes;
constexpr int kOffBar = kOffX + kNWG * kXBytes;
constexpr int kOffStash = kOffBar + 128;
constexpr int kOffProf = kOffStash + kThreads * 16;
constexpr int kSmemBytes = kOffProf;
constexpr uint32_t kSmemBase = 1024;

struct Scratch {
    uint4 wfold[2 * kWBytes / 16];
    uint32_t ticket[32];
    uint32_t cnt[64];
};
__device__ __align__(128) Scratch g_scratch;

__device__ __forceinline__ uint32_t smem_u32(const void* p) { return (uint32_t)__cvta_generic_to_shared(p); }

__device__ __forceinline__ void mbar_init(uint32_t bar, uint32_t count) {
    asm volatile("mbarrier.init.shared::cta.b64 [%0], %1;" ::"r"(bar), "r"(count) : "memory");
}
__device__ __forceinline__ void mbar_expect_tx(uint32_t bar, uint32_t bytes) {
    asm volatile("mbarrier.arrive.expect_tx.shared::cta.b64 _, [%0], %1;" ::"r"(bar), "r"(bytes) : "memory");
}
__device__ __forceinline__ void mbar_wait(uint32_t bar, uint32_t parity) {
    uint32_t ok;
    uint32_t spins = 0;
    do {
        asm volatile("{\n.reg .pred p;\n"
                     "mbarrier.try_wait.parity.shared::cta.b64 p, [%1], %2;\n"
                     "selp.b32 %0, 1, 0, p;\n}\n"
                     : "=r"(ok) : "r"(bar), "r"(parity) : "memory");
        if (++spins > (1u << 26)) __trap();
    } while (!ok);
}
__device__ __forceinline__ uint32_t tid_now() {
    uint32_t t;
    asm volatile("mov.u32 %0, %%tid.x;" : "=r"(t));
    return t;
}
__device__ __forceinline__ uint32_t nctaid_now() {
    uint32_t t;
    asm volatile("mov.u32 %0, %%nctaid.x;" : "=r"(t));
    return t;
}
__device__ __forceinline__ bool elect_one() {
    uint32_t pred;
    asm volatile("{\n.reg .pred p;\nelect.sync _|p, 0xffffffff;\nselp.b32 %0, 1, 0, p;\n}\n" : "=r"(pred));
    return pred != 0;
}
#define PASS1 11
#define PASS2 5
#define PASS3 3
__device__ __forceinline__ void ring_wait() {
    asm volatile("bar.sync %0, 256;" ::"r"((tid_now() >> 7) + 8) : "memory");
}
__device__ __forceinline__ void ring_wait(uint32_t dep) {
    asm volatile("{\n.reg .pred p;\n.reg .b32 t;\nsetp.eq.u32 p, %1, 0x7fc17fc1;\nselp.u32 t, 0, %0, p;\nbar.sync t, 256;\n}\n"
                 ::"r"((tid_now() >> 7) + 8), "r"(dep) : "memory");
}
__device__ __forceinline__ void ring_pass() {
    const uint32_t w = tid_now() >> 7;
    asm volatile("bar.arrive %0, 256;" ::"r"(w == kNWG - 1 ? 8u : w + 9u) : "memory");
}
constexpr uint32_t kLastOfCta = 0x40000000u;
__device__ __forceinline__ uint32_t wg_uniform() { return __reduce_or_sync(0xffffffffu, tid_now() >> 7); }
__device__ __forceinline__ void tma_load_x(uint32_t dst, const CUtensorMap* tm, uint32_t bar, int win) {
    const int wh = win >> 6, ww = win & 63;
    asm volatile("cp.async.bulk.tensor.4d.shared::cluster.global.mbarrier::complete_tx::bytes"
                 " [%0], [%1, {%3, %4, %5, %6}], [%2];"
                 ::"r"(dst), "l"(tm), "r"(bar), "r"(0), "r"(ww * 8), "r"(wh * 8), "r"(0) : "memory");
}
__device__ __forceinline__ void tma_load_x_chunk(uint32_t dst, const CUtensorMap* tm, uint32_t bar, int win, int chunk) {
    const int wh = win >> 6, ww = win & 63;
    asm volatile("cp.async.bulk.tensor.4d.shared::cluster.global.mbarrier::complete_tx::bytes"
                 " [%0], [%1, {%3, %4, %5, %6}], [%2];"
                 ::"r"(dst), "l"(tm), "r"(bar), "r"(0), "r"(ww * 8), "r"(wh * 8), "r"(chunk) : "memory");
}
__device__ __forceinline__ void bulk_load(uint32_t dst, const void* src, uint32_t bytes, uint32_t bar) {
    asm volatile("cp.async.bulk.shared::cluster.global.mbarrier::complete_tx::bytes [%0], [%1], %2, [%3];"
                 ::"r"(dst), "l"(src), "r"(bytes), "r"(bar) : "memory");
}

__device__ __forceinline__ void stg128(void* p, uint4 v) {
    asm volatile("st.global.v4.b32 [%0], {%1, %2, %3, %4};" ::"l"(p), "r"(v.x), "r"(v.y), "r"(v.z), "r"(v.w) : "memory");
}
__device__ __forceinline__ void wg_fence()  { asm volatile("wgmma.fence.sync.aligned;" ::: "memory"); }
__device__ __forceinline__ void wg_commit() { asm volatile("wgmma.commit_group.sync.aligned;" ::: "memory"); }
__device__ __forceinline__ void wg_wait0()  { asm volatile("wgmma.wait_group.sync.aligned 0;" ::: "memory"); }
__device__ __forceinline__ void wg_wait1()  { asm volatile("wgmma.wait_group.sync.aligned 1;" ::: "memory"); }
__device__ __forceinline__ void wg_wait2()  { asm volatile("wgmma.wait_group.sync.aligned 2;" ::: "memory"); }

template <int N> __device__ __forceinline__ void fence_regs(float (&d)[N]) {
#pragma unroll
    for (int i = 0; i < N; i++) asm volatile("" : "+f"(d[i])::"memory");
}
template <int N> __device__ __forceinline__ void fence_regs(uint32_t (&d)[N]) {
#pragma unroll
    for (int i = 0; i < N; i++) asm volatile("" : "+r"(d[i])::"memory");
}

#define ACC8(c, d, i) c(d[i]), c(d[i + 1]), c(d[i + 2]), c(d[i + 3]), c(d[i + 4]), c(d[i + 5]), c(d[i + 6]), c(d[i + 7])
#define ACC32(c, d) ACC8(c, d, 0), ACC8(c, d, 8), ACC8(c, d, 16), ACC8(c, d, 24)
#define ACC96(c, d) ACC32(c, d), ACC8(c, d, 32), ACC8(c, d, 40), ACC8(c, d, 48), ACC8(c, d, 56), \
                    ACC8(c, d, 64), ACC8(c, d, 72), ACC8(c, d, 80), ACC8(c, d, 88)
#define C_IO(x) "+f"(x)
#define C_O(x) "=f"(x)
#define REGS32 "{%0, %1, %2, %3, %4, %5, %6, %7, %8, %9, %10, %11, %12, %13, %14, %15, " \
               "%16, %17, %18, %19, %20, %21, %22, %23, %24, %25, %26, %27, %28, %29, %30, %31}"
#define REGS96 "{%0, %1, %2, %3, %4, %5, %6, %7, %8, %9, %10, %11, %12, %13, %14, %15, " \
               "%16, %17, %18, %19, %20, %21, %22, %23, %24, %25, %26, %27, %28, %29, %30, %31, " \
               "%32, %33, %34, %35, %36, %37, %38, %39, %40, %41, %42, %43, %44, %45, %46, %47, " \
               "%48, %49, %50, %51, %52, %53, %54, %55, %56, %57, %58, %59, %60, %61, %62, %63, " \
               "%64, %65, %66, %67, %68, %69, %70, %71, %72, %73, %74, %75, %76, %77, %78, %79, " \
               "%80, %81, %82, %83, %84, %85, %86, %87, %88, %89, %90, %91, %92, %93, %94, %95}"

#define DESC_HI "0x40000040"
#define MK_DESC(name, lo, off) "add.u32 t, " lo ", " off ";\nmov.b64 " name ", {t, " DESC_HI "};\n"

template <bool First, int OA, int OB> __device__ __forceinline__ void wg192_ss(float (&d)[96], uint32_t la, uint32_t lb) {
    if constexpr (First)
        asm volatile("{\n.reg .pred p;\n.reg .b32 t;\n.reg .b64 da, db;\nsetp.ne.b32 p, 0, 0;\n"
                     MK_DESC("da", "%96", "%98") MK_DESC("db", "%97", "%99")
                     "wgmma.mma_async.sync.aligned.m64n192k16.f32.bf16.bf16 " REGS96 ", da, db, p, 1, 1, 0, 0;\n}\n"
                     : ACC96(C_O, d) : "r"(la), "r"(lb), "n"(OA), "n"(OB));
    else
        asm volatile("{\n.reg .pred p;\n.reg .b32 t;\n.reg .b64 da, db;\nsetp.ne.b32 p, 1, 0;\n"
                     MK_DESC("da", "%96", "%98") MK_DESC("db", "%97", "%99")
                     "wgmma.mma_async.sync.aligned.m64n192k16.f32.bf16.bf16 " REGS96 ", da, db, p, 1, 1, 0, 0;\n}\n"
                     : ACC96(C_IO, d) : "r"(la), "r"(lb), "n"(OA), "n"(OB));
}
template <bool First, int TB, int OB> __device__ __forceinline__ void wg192_rs(float (&d)[96], const uint32_t* a, uint32_t lb) {
    if constexpr (First)
        asm volatile("{\n.reg .pred p;\n.reg .b32 t;\n.reg .b64 db;\nsetp.ne.b32 p, 0, 0;\n"
                     MK_DESC("db", "%100", "%102")
                     "wgmma.mma_async.sync.aligned.m64n192k16.f32.bf16.bf16 " REGS96 ", {%96, %97, %98, %99}, db, p, 1, 1, %101;\n}\n"
                     : ACC96(C_O, d) : "r"(a[0]), "r"(a[1]), "r"(a[2]), "r"(a[3]), "r"(lb), "n"(TB), "n"(OB));
    else
        asm volatile("{\n.reg .pred p;\n.reg .b32 t;\n.reg .b64 db;\nsetp.ne.b32 p, 1, 0;\n"
                     MK_DESC("db", "%100", "%102")
                     "wgmma.mma_async.sync.aligned.m64n192k16.f32.bf16.bf16 " REGS96 ", {%96, %97, %98, %99}, db, p, 1, 1, %101;\n}\n"
                     : ACC96(C_IO, d) : "r"(a[0]), "r"(a[1]), "r"(a[2]), "r"(a[3]), "r"(lb), "n"(TB), "n"(OB));
}
template <bool First, int OB> __device__ __forceinline__ void wg64_rs(float (&d)[32], const uint32_t* a, uint32_t lb) {
    if constexpr (First)
        asm volatile("{\n.reg .pred p;\n.reg .b32 t;\n.reg .b64 db;\nsetp.ne.b32 p, 0, 0;\n"
                     MK_DESC("db", "%36", "%37")
                     "wgmma.mma_async.sync.aligned.m64n64k16.f32.bf16.bf16 " REGS32 ", {%32, %33, %34, %35}, db, p, 1, 1, 0;\n}\n"
                     : ACC32(C_O, d) : "r"(a[0]), "r"(a[1]), "r"(a[2]), "r"(a[3]), "r"(lb), "n"(OB));
    else
        asm volatile("{\n.reg .pred p;\n.reg .b32 t;\n.reg .b64 db;\nsetp.ne.b32 p, 1, 0;\n"
                     MK_DESC("db", "%36", "%37")
                     "wgmma.mma_async.sync.aligned.m64n64k16.f32.bf16.bf16 " REGS32 ", {%32, %33, %34, %35}, db, p, 1, 1, 0;\n}\n"
                     : ACC32(C_IO, d) : "r"(a[0]), "r"(a[1]), "r"(a[2]), "r"(a[3]), "r"(lb), "n"(OB));
}
template <bool First, int OA, int OB> __device__ __forceinline__ void wg64_ss(float (&d)[32], uint32_t la, uint32_t lb) {
    if constexpr (First)
        asm volatile("{\n.reg .pred p;\n.reg .b32 t;\n.reg .b64 da, db;\nsetp.ne.b32 p, 0, 0;\n"
                     MK_DESC("da", "%32", "%34") MK_DESC("db", "%33", "%35")
                     "wgmma.mma_async.sync.aligned.m64n64k16.f32.bf16.bf16 " REGS32 ", da, db, p, 1, 1, 0, 1;\n}\n"
                     : ACC32(C_O, d) : "r"(la), "r"(lb), "n"(OA), "n"(OB));
    else
        asm volatile("{\n.reg .pred p;\n.reg .b32 t;\n.reg .b64 da, db;\nsetp.ne.b32 p, 1, 0;\n"
                     MK_DESC("da", "%32", "%34") MK_DESC("db", "%33", "%35")
                     "wgmma.mma_async.sync.aligned.m64n64k16.f32.bf16.bf16 " REGS32 ", da, db, p, 1, 1, 0, 1;\n}\n"
                     : ACC32(C_IO, d) : "r"(la), "r"(lb), "n"(OA), "n"(OB));
}
__host__ __device__ constexpr int koff(int kk, int chunk) { return ((kk >> 2) * chunk + (kk & 3) * 32) >> 4; }

#define ST_SLOTS 0x2000000000001ull
__host__ __device__ constexpr int slot_begin(int i) {
    int b = 0;
    for (int k = -1; k < i; k++) b += (int)((ST_SLOTS >> (4 * (11 - k))) & 15);
    return b;
}
#define PACE_DT 160
template <int J, int E> __device__ __forceinline__ void store_range(const uint4 (&h)[12], uint8_t* hptr) {
    if constexpr (J < E) {
        constexpr int r = J / 6, a = J % 6;
        stg128(hptr + r * (kHW * kC * 2) + a * 64, h[2 * a + r]);
        store_range<J + 1, E>(h, hptr);
    }
}
template <int I> __device__ __forceinline__ void store_slot(const uint4 (&h)[12], uint8_t* hptr) {
    store_range<slot_begin(I), slot_begin(I + 1)>(h, hptr);
}
__device__ __forceinline__ uint32_t clock_now() {
    uint32_t t;
    asm volatile("mov.u32 %0, %%clock;" : "=r"(t));
    return t;
}
template <int J> __device__ __forceinline__ void store_paced(const uint4 (&h)[12], uint8_t* hptr, uint32_t t0) {
    if constexpr (J < 12) {
        while (clock_now() - t0 < (uint32_t)((J - slot_begin(12) + 1) * PACE_DT)) {}
        store_range<J, J + 1>(h, hptr);
        store_paced<J + 1>(h, hptr, t0);
    }
}
#define TAIL_DT 70
template <int J> __device__ __forceinline__ void store_tail(const uint4 (&h)[12], uint8_t* hptr, uint32_t t0) {
    if constexpr (J < 12) {
        if constexpr (J > slot_begin(0)) { while (clock_now() - t0 < (uint32_t)((J - slot_begin(0)) * TAIL_DT)) {} }
        store_range<J, J + 1>(h, hptr);
        store_tail<J + 1>(h, hptr, t0);
    }
}
template <int K> struct Gemm1St {
    static __device__ __forceinline__ void run(float (&d)[96], uint32_t lx, uint32_t lw, const uint4 (&h)[12], uint8_t* hptr) {
        if constexpr (K > 0) Gemm1St<K - 1>::run(d, lx, lw, h, hptr);
        wg192_ss<K == 0, koff(K, 8192), koff(K, 24576)>(d, lx, lw);
        if constexpr (K == 11) wg_commit();
        if constexpr (K == PASS1) ring_pass();
        if constexpr (slot_begin(K + 1) > slot_begin(K)) {
            __syncwarp();
            store_slot<K>(h, hptr);
            __syncwarp();
        }
    }
};
template <int K0, int K> struct Gemm1 {
    static __device__ __forceinline__ void run(float (&d)[96], uint32_t lx, uint32_t lw) {
        if constexpr (K > K0) Gemm1<K0, K - 1>::run(d, lx, lw);
        wg192_ss<K == 0, koff(K, 8192), koff(K, 24576)>(d, lx, lw);
    }
};
__device__ __forceinline__ uint32_t draw_ticket(uint32_t* counter) {
    uint32_t ticket = 0;
    asm volatile("{\n.reg .pred p;\nsetp.eq.u32 p, %2, 0;\n@p atom.relaxed.gpu.global.inc.u32 %0, [%1], %3;\n}\n"
                 : "+r"(ticket) : "l"(counter), "r"(tid_now() & 127), "n"(kNWin - 1) : "memory");
    return ticket;
}
template <int KK> struct Gemm2 { static __device__ __forceinline__ void run(float (&d)[32], const uint32_t* a, uint32_t lx) {
    Gemm2<KK - 1>::run(d, a, lx); wg64_rs<KK == 0, koff(KK, 8192)>(d, a + 4 * KK, lx);
    if constexpr (KK == PASS2 && KK < 11) ring_pass(); } };
template <> struct Gemm2<-1> { static __device__ __forceinline__ void run(float (&)[32], const uint32_t*, uint32_t) {} };
template <int KK> struct Gemm3 { static __device__ __forceinline__ void run(float (&d)[96], const uint32_t* a, uint32_t lxt) {
    Gemm3<KK - 1>::run(d, a, lxt); wg192_rs<KK == 0, 1, KK * (2048 >> 4)>(d, a + 4 * KK, lxt);
    if constexpr (KK == PASS3 && KK < 3) ring_pass(); } };
template <> struct Gemm3<-1> { static __device__ __forceinline__ void run(float (&)[96], const uint32_t*, uint32_t) {} };
template <int K0, int KK> struct Gemm4 { static __device__ __forceinline__ void run(float (&d)[96], const uint32_t* a, uint32_t lw) {
    if constexpr (KK > K0) Gemm4<K0, KK - 1>::run(d, a, lw);
    wg192_rs<KK == 0, 0, koff(KK, 24576)>(d, a + 4 * KK, lw); } };

template <int J, int KK> struct Gemm3s { static __device__ __forceinline__ void run(float (&d)[32], uint32_t lp, uint32_t lxt) {
    if constexpr (KK > 0) Gemm3s<J, KK - 1>::run(d, lp, lxt);
    wg64_ss<KK == 0, KK * 2, (J * 8192 + KK * 2048) / 16>(d, lp, lxt); } };
template <int J, int K0, int KK> struct Gemm4s { static __device__ __forceinline__ void run(float (&d)[32], const uint32_t* a, uint32_t lw) {
    if constexpr (KK > K0) Gemm4s<J, K0, KK - 1>::run(d, a, lw);
    wg64_rs<KK == 0, koff(KK, 24576) + J * (8192 / 16)>(d, a + 4 * KK, lw); } };

__device__ __forceinline__ uint32_t pack_bf16(float lo, float hi) {
    uint32_t r;
    asm("cvt.rn.bf16x2.f32 %0, %1, %2;" : "=r"(r) : "f"(hi), "f"(lo));
    return r;
}
__device__ __forceinline__ float ex2(float x) {
    float r;
    asm("ex2.approx.ftz.f32 %0, %1;" : "=f"(r) : "f"(x));
    return r;
}
__device__ __forceinline__ float rcp(float x) {
    float r;
    asm("rcp.approx.ftz.f32 %0, %1;" : "=f"(r) : "f"(x));
    return r;
}

__device__ __forceinline__ void pack_slice(uint32_t* a, float (&d)[32]) {
    fence_regs(d);
#pragma unroll
    for (int i = 0; i < 16; i++) a[i] = pack_bf16(d[2 * i], d[2 * i + 1]);
#pragma unroll
    for (int i = 0; i < 16; i++) asm volatile("" : "+r"(a[i])::"memory");
}
template <int J> __device__ __forceinline__ void store_slice(float (&d)[32], uint8_t* hptr) {
    fence_regs(d);
#pragma unroll
    for (int i = 0; i < 4; i++) {
        const int r = i >> 1, a = i & 1, o = 16 * a + 2 * r;
        stg128(hptr + r * (kHW * kC * 2) + (2 * J + a) * 64,
               make_uint4(pack_bf16(d[o], d[o + 1]), pack_bf16(d[o + 4], d[o + 5]), pack_bf16(d[o + 8], d[o + 9]), pack_bf16(d[o + 12], d[o + 13])));
    }
    __syncwarp();
}
__device__ __forceinline__ uint8_t* out_address(__nv_bfloat16* out, int win) {
    const uint32_t ln = tid_now() & 31;
    return reinterpret_cast<uint8_t*>(out) + (uint32_t)((win >> 6) * 8 * kHW + (win & 63) * 8 + 2 * ((tid_now() >> 5) & 3) * kHW + (ln >> 2)) * (uint32_t)(kC * 2) + (ln & 3) * 16;
}
__device__ __forceinline__ void count_finished() {
    if (((tid_now() >> 5) & 3) == 0) {
        if (elect_one()) {
            uint32_t nd;
            asm volatile("ld.shared.u32 %0, [%1];" : "=r"(nd) : "r"(kSmemBase + kOffBar + 80) : "memory");
            asm volatile("st.shared.v2.u32 [%0], {%1, %2};" ::"r"(kSmemBase + kOffBar + 80), "r"(nd + 1), "r"(tid_now() >> 7) : "memory");
        }
        __syncwarp();
    }
}
__device__ __forceinline__ void store_p_if(const uint32_t (&pa)[16], bool cond) {
    const uint32_t t = tid_now(), w = t >> 7, row = ((t >> 1) & 48) + (t & 15);
    const uint32_t adr = kSmemBase + kOffX + (w == kNWG - 1 ? 0 : w + 1) * kXBytes + row * 128 + ((((t >> 4) & 1) ^ (t & 7)) << 4);
#pragma unroll
    for (int i = 0; i < 4; i++)
        asm volatile("{\n.reg .pred p;\nsetp.ne.u32 p, %5, 0;\n@p stmatrix.sync.aligned.m8n8.x4.shared.b16 [%4], {%0, %1, %2, %3};\n}\n"
                     :: "r"(pa[4 * i]), "r"(pa[4 * i + 1]), "r"(pa[4 * i + 2]), "r"(pa[4 * i + 3]), "r"(adr ^ (i << 5)), "r"((uint32_t)cond) : "memory");
}
__device__ __forceinline__ void last_window(__nv_bfloat16* out, int win) {
    constexpr uint32_t dWv = ((kSmemBase + kOffWv) >> 4) | (1u << 16);
    asm volatile("fence.proxy.async.shared::cta;" ::: "memory");
    const uint32_t w = wg_uniform();
    const uint32_t dXt = ((kSmemBase + kOffX + w * kXBytes) >> 4) | ((8192u >> 4) << 16);
    const uint32_t dP = ((kSmemBase + kOffX + (w == kNWG - 1 ? 0 : w + 1) * kXBytes) >> 4) | (1u << 16);
    float u0[32], u1[32], u2[32];
    uint32_t fa[48];
    uint8_t* hptr = out_address(out, win);
    mbar_wait(kSmemBase + kOffBar + 40, 0);
    asm volatile("" : "+l"(hptr) :: "memory");
    ring_wait();
    wg_fence();
    Gemm3s<0, 3>::run(u0, dP, dXt); wg_commit();
    Gemm3s<1, 3>::run(u1, dP, dXt); wg_commit();
    Gemm3s<2, 3>::run(u2, dP, dXt); wg_commit();
    count_finished();
    ring_pass();
    wg_wait2();
    pack_slice(fa, u0);
    wg_wait1();
    pack_slice(fa + 16, u1);
    wg_fence();
    Gemm4s<0, 0, 7>::run(u0, fa, dWv); wg_commit();
    wg_wait1();
    pack_slice(fa + 32, u2);
    wg_fence();
    Gemm4s<0, 8, 11>::run(u0, fa, dWv); wg_commit();
    Gemm4s<1, 0, 5>::run(u1, fa, dWv); wg_commit();
    wg_wait1();
    store_slice<0>(u0, hptr);
    wg_fence();
    Gemm4s<1, 6, 11>::run(u1, fa, dWv); wg_commit();
    Gemm4s<2, 0, 5>::run(u2, fa, dWv); wg_commit();
    wg_wait1();
    store_slice<1>(u1, hptr);
    wg_fence();
    Gemm4s<2, 6, 11>::run(u2, fa, dWv); wg_commit();
    wg_wait0();
    fence_regs(fa);
    store_slice<2>(u2, hptr);
}

__device__ __forceinline__ int fold_offset(int n, int k0, int q) {
    const int u = ((k0 & 63) >> 3) + (q >> 1);
    return (k0 >> 6) * 24576 + (q & 1) * 8 + n * 128 + ((u ^ (n & 7)) << 4);
}
__device__ __forceinline__ void mma16816x2(float (&c)[4], float (&d)[4], const uint32_t (&a)[4], const uint32_t (&b)[4]) {
    asm volatile("mma.sync.aligned.m16n8k16.row.col.f32.bf16.bf16.f32 {%0,%1,%2,%3}, {%8,%9,%10,%11}, {%12,%13}, {%0,%1,%2,%3};\n"
                 "mma.sync.aligned.m16n8k16.row.col.f32.bf16.bf16.f32 {%4,%5,%6,%7}, {%8,%9,%10,%11}, {%14,%15}, {%4,%5,%6,%7};"
                 : "+f"(c[0]), "+f"(c[1]), "+f"(c[2]), "+f"(c[3]), "+f"(d[0]), "+f"(d[1]), "+f"(d[2]), "+f"(d[3])
                 : "r"(a[0]), "r"(a[1]), "r"(a[2]), "r"(a[3]), "r"(b[0]), "r"(b[1]), "r"(b[2]), "r"(b[3]));
}
__device__ __forceinline__ void cp_async16(uint32_t dst, const void* src) {
    asm volatile("cp.async.cg.shared.global [%0], [%1], 16;" ::"r"(dst), "l"(src) : "memory");
}
template <bool kTrans> __device__ __forceinline__ void ldsm4(uint32_t (&r)[4], uint32_t addr) {
    if constexpr (kTrans)
        asm volatile("ldmatrix.sync.aligned.m8n8.x4.trans.shared.b16 {%0, %1, %2, %3}, [%4];" : "=r"(r[0]), "=r"(r[1]), "=r"(r[2]), "=r"(r[3]) : "r"(addr) : "memory");
    else
        asm volatile("ldmatrix.sync.aligned.m8n8.x4.shared.b16 {%0, %1, %2, %3}, [%4];" : "=r"(r[0]), "=r"(r[1]), "=r"(r[2]), "=r"(r[3]) : "r"(addr) : "memory");
}
__device__ __forceinline__ void fold_job(Scratch* sc, const __nv_bfloat16* __restrict__ wqkv, const __nv_bfloat16* __restrict__ wo,
                                         int job, int warp, int lane) {
    const bool vo = job >= kJobsM;
    const int nw = vo ? 3 : 2, tile0 = vo ? 3 * (job - kJobsM) : 2 * job;
    const int n0 = (tile0 / 12) * 16, k0 = (tile0 % 12 + max(warp, 1) - 1) * 16;
    const uint32_t stage = kSmemBase + kOffWv;
    if (warp <= nw) {
        if (vo && warp == 0) {
            const char* src = reinterpret_cast<const char*>(wo + (lane >> 1) * kC + n0 + (lane & 1) * 8);
            const uint32_t dst = stage + ((lane ^ ((lane >> 3) & 1)) << 4);
#pragma unroll
            for (int i = 0; i < 12; i++) cp_async16(dst + i * 512, src + i * 16 * kC * 2);
        } else {
            const int row0 = warp == 0 ? n0 : k0, col0 = warp == 0 ? kC : vo ? 2 * kC : 0;
            const char* src = reinterpret_cast<const char*>(wqkv + (row0 + (lane >> 3)) * (3 * kC) + col0 + (lane & 7) * 8);
            const uint32_t dst = stage + warp * 6144 + (lane >> 3) * 384 + (((lane & 7) ^ (lane >> 3)) << 4);
#pragma unroll
            for (int i = 0; i < 12; i++) cp_async16((dst ^ (((i / 3) & 1) << 6)) + (i / 3) * 1536 + (i % 3) * 128, src + (i / 3) * 4 * 3 * kC * 2 + (i % 3) * 128);
        }
        asm volatile("cp.async.wait_all;" ::: "memory");
        asm volatile("bar.sync 13, %0;" ::"r"(32 * nw + 32) : "memory");
    }
    if (warp == 0 || (warp > nw && warp != kWarmW)) return;
    const int g = lane >> 2, q = lane & 3, mi = lane >> 3, r8 = lane & 7;
    uint32_t A[12][4], B[12][4];
    {
        const int row = 4 * (r8 >> 1) + (r8 & 1) + 2 * (mi >> 1);
        const uint32_t base = stage + warp * 6144 + row * 384 + (((mi & 1) ^ (row & 7)) << 4);
#pragma unroll
        for (int ks = 0; ks < 12; ks++) ldsm4<false>(B[ks], (base ^ ((ks & 3) << 5)) + (ks >> 2) * 128);
    }
    if (vo) {
        const int c = r8 + 8 * (mi >> 1);
        const uint32_t base = stage + (((2 * c + (mi & 1)) ^ ((c >> 2) & 1)) << 4);
#pragma unroll
        for (int ks = 0; ks < 12; ks++) ldsm4<true>(A[ks], base + ks * 512);
    } else {
        const uint32_t base = stage + (r8 + 8 * (mi & 1)) * 384 + (((mi >> 1) ^ r8) << 4);
#pragma unroll
        for (int ks = 0; ks < 12; ks++) ldsm4<false>(A[ks], (base ^ ((ks & 3) << 5)) + (ks >> 2) * 128);
    }
    float c0[4] = {0.f, 0.f, 0.f, 0.f}, c1[4] = {0.f, 0.f, 0.f, 0.f}, c2[4] = {0.f, 0.f, 0.f, 0.f}, c3[4] = {0.f, 0.f, 0.f, 0.f};
#pragma unroll
    for (int ks = 0; ks < 12; ks += 2) {
        mma16816x2(c0, c1, A[ks], B[ks]);
        mma16816x2(c2, c3, A[ks + 1], B[ks + 1]);
    }
#pragma unroll
    for (int i = 0; i < 4; i++) { c0[i] += c2[i]; c1[i] += c3[i]; }
    const int ch = n0 + g;
    const int n = vo ? 32 * (ch >> 5) + 8 * ((ch >> 1) & 3) + 2 * ((ch >> 3) & 3) + (ch & 1) : ch;
    char* img = reinterpret_cast<char*>(sc->wfold) + (vo ? kWBytes : 0);
    asm volatile("{\n.reg .pred p;\nsetp.ne.u32 p, %6, %7;\n@p st.global.v2.u32 [%0], {%2, %3};\n@p st.global.v2.u32 [%1], {%4, %5};\n}\n"
                 ::"l"(img + fold_offset(n, k0, q)), "l"(img + fold_offset(n + (vo ? 2 : 8), k0, q)),
                   "r"(pack_bf16(c0[0], c0[1])), "r"(pack_bf16(c1[0], c1[1])), "r"(pack_bf16(c0[2], c0[3])), "r"(pack_bf16(c1[2], c1[3])),
                   "r"(warp), "n"(kWarmW) : "memory");
    if (warp == kWarmW) return;
    asm volatile("bar.sync 12, %0;" ::"r"(32 * nw) : "memory");
    if (lane == 0 && warp == 1) asm volatile("red.release.gpu.global.add.u32 [%0], 1;" ::"l"(&sc->cnt[vo ? 32 : 0]) : "memory");
}

__device__ __forceinline__ uint32_t ld_acquire(const uint32_t* p) {
    uint32_t v;
    asm volatile("ld.acquire.gpu.global.u32 %0, [%1];" : "=r"(v) : "l"(p) : "memory");
    return v;
}
__device__ __forceinline__ void prefetch_x(const CUtensorMap* tm, int win) {
    const int wh = win >> 6, ww = win & 63;
    asm volatile("cp.async.bulk.prefetch.tensor.3d.L2.global.tile [%0, {%1, %2, %3}];"
                 ::"l"(tm), "r"(0), "r"(ww * 8), "r"(wh * 8) : "memory");
}

__device__ __forceinline__ void prefetch_for_ticket(const CUtensorMap* tmp, int t) {
    const int base = kNWG * (int)gridDim.x;
    auto lead = [&](int tt) {
        int down = max(((kNWin - base - tt) * PF_DOWN) >> 8, PF_MIN);
        return min(min((tt * PF_UP) >> 8, PF_LEAD), down);
    };
    const int hi = base + t + lead(t);
    int lo = max(base + t - 1 + lead(t - 1), base + t) + 1;
#pragma unroll 1
    for (; lo <= hi && lo < kNWin; lo++) prefetch_x(tmp, lo);
}

template <bool kFewSMs>
__global__ void __launch_bounds__(kThreads, 1)
swin_attn_kernel(const __nv_bfloat16* __restrict__ wqkv, const __nv_bfloat16* __restrict__ wo, __nv_bfloat16* __restrict__ out, Scratch* sc, uint32_t* tickets,
                 const __grid_constant__ CUtensorMap tmx, const __grid_constant__ CUtensorMap tmp, const __grid_constant__ CUtensorMap tmc) {
    extern __shared__ uint8_t smem_raw[];
    constexpr uint32_t sbase = kSmemBase;
    const uint32_t t_start = clock_now();
    if (smem_u32(smem_raw) != kSmemBase) __trap();
    const int tid = threadIdx.x, lane = tid & 31;
    const uint32_t warpu = __reduce_or_sync(0xffffffffu, (uint32_t)tid >> 5), wgu = warpu >> 2;
    const int warp = (int)warpu, wg = (int)wgu;
    const int G = gridDim.x;
    const uint32_t bar_full = sbase + kOffBar + 8 * wg;
    const uint32_t bar_w0 = sbase + kOffBar + 32, bar_w1 = bar_w0 + 8;
    int win = wg * G + blockIdx.x;
    const bool x0_early = !kFewSMs && blockIdx.x >= kJobsM;

    if (warp > kWarmW) {
        if (warp == 10) {
            asm volatile("bar.sync 15, 64;" ::: "memory");
            asm volatile("bar.arrive 0, %0;" ::"n"(kThreads) : "memory");
            if (lane == 0) {
                asm volatile("prefetch.tensormap [%0];" ::"l"(&tmp) : "memory");
                asm volatile("prefetch.tensormap [%0];" ::"l"(&tmc) : "memory");
                asm volatile("prefetch.tensormap [%0];" ::"l"(&tmx) : "memory");
                const uint32_t rank = kFewSMs ? blockIdx.x : x0_early ? blockIdx.x - kJobsM : blockIdx.x + (G - kJobsM);
                const uint32_t due = TRK_T0 + (uint32_t)(rank * TRK_S) / (uint32_t)G;
#pragma unroll 1
                for (int i = 0; i < kNWG; i++) {
                    while (clock_now() - t_start < due + i * TRK_S) {}
                    if (i == 0 && x0_early) {
                        mbar_expect_tx(sbase + kOffBar, kXBytes);
                        tma_load_x(sbase + kOffX, &tmx, sbase + kOffBar, blockIdx.x);
                        continue;
                    }
                    prefetch_x(&tmp, i * G + blockIdx.x);
                }
            }
            __syncwarp();
        } else if (warp == 11) {
            if (lane == 0) {
#pragma unroll
                for (int w = 0; w < kNWG; w++) mbar_init(sbase + kOffBar + 8 * w, 1);
                mbar_init(bar_w0, 1);
                mbar_init(bar_w1, 1);
                mbar_init(sbase + kOffBar + 48, 1);
                mbar_init(sbase + kOffBar + 56, 1);
                asm volatile("st.shared.v4.u32 [%0], {%1, %1, %1, %1};" ::"r"(sbase + kOffBar + 64), "r"(0) : "memory");
                asm volatile("st.shared.v2.u32 [%0], {%1, %1};" ::"r"(sbase + kOffBar + 80), "r"(0) : "memory");
                asm volatile("fence.mbarrier_init.release.cluster;" ::: "memory");
                if (!x0_early) asm volatile("mbarrier.arrive.shared::cta.b64 _, [%0];" ::"r"(sbase + kOffBar) : "memory");
            }
            __syncwarp();
            asm volatile("bar.arrive 15, 64;" ::: "memory");
            asm volatile("bar.arrive 0, %0;" ::"n"(kThreads) : "memory");
            if (elect_one()) {
                const char* img = reinterpret_cast<const char*>(sc->wfold);
                uint32_t spins = 0;
#pragma unroll
                for (int c = 0; c < 3; c++) mbar_expect_tx(c == 0 ? bar_w0 : sbase + kOffBar + 40 + 8 * c, x0_early ? 24576 : 24576 + 8192);
                mbar_expect_tx(sbase + kOffBar + 8, kXBytes);
                while (clock_now() - t_start < POLL_T0) {}
                uint32_t done = ld_acquire(sc->cnt);
                while (clock_now() - t_start < POLL_T) {}
                while (done < kJobsM) { done = ld_acquire(sc->cnt); if (++spins > (1u << 24)) __trap(); }
                asm volatile("fence.proxy.async.global;" ::: "memory");
#pragma unroll
                for (int c = 0; c < 3; c++) {
                    const uint32_t bar = c == 0 ? bar_w0 : sbase + kOffBar + 40 + 8 * c;
                    if (!x0_early) tma_load_x_chunk(sbase + kOffX + c * 8192, &tmc, bar, blockIdx.x, c);
                    bulk_load(sbase + kOffWm + c * 24576, img + c * 24576, 24576, bar);
                }
                mbar_wait(bar_w0, 0);
                tma_load_x(sbase + kOffX + kXBytes, &tmx, sbase + kOffBar + 8, G + blockIdx.x);
            }
            __syncwarp();
        } else {
            asm volatile("bar.sync 0, %0;" ::"n"(kThreads) : "memory");
            if (warp == 9) {
                if (elect_one()) {
                    uint32_t spins = 0;
                    while (clock_now() - t_start < POLL_TV) {}
                    while (ld_acquire(sc->cnt + 32) < kJobs - kJobsM) { if (++spins > (1u << 24)) __trap(); }
                    mbar_wait(sbase + kOffBar + 48, 0);
                    asm volatile("fence.proxy.async.global;" ::: "memory");
                    asm volatile("fence.proxy.async.shared::cta;" ::: "memory");
                    mbar_expect_tx(bar_w1, kWBytes);
                    mbar_expect_tx(sbase + kOffBar + 16, kXBytes);
#pragma unroll
                    for (int c = 0; c < 3; c++)
                        bulk_load(sbase + kOffWv + c * 24576, reinterpret_cast<const char*>(sc->wfold) + kWBytes + c * 24576, 24576, bar_w1);
                    tma_load_x(sbase + kOffX + 2 * kXBytes, &tmx, sbase + kOffBar + 16, 2 * G + blockIdx.x);
                }
                __syncwarp();
            }
        }
    } else {
        if constexpr (kFewSMs) {
#pragma unroll 1
            for (int j = blockIdx.x; j < kJobs; j += G) {
                fold_job(sc, wqkv, wo, j, warp, lane);
                asm volatile("bar.sync 14, %0;" ::"n"(32 * kWarmW + 32) : "memory");
            }
        } else {
            if (blockIdx.x < kJobs) fold_job(sc, wqkv, wo, blockIdx.x, warp, lane);
        }
        asm volatile("bar.sync 0, %0;" ::"n"(kThreads) : "memory");
    }
    if (wg == kNWG - 1) asm volatile("bar.sync 7, 128;" ::: "memory");
    if (wg == 1) asm volatile("bar.arrive 8, 256;" ::: "memory");

    constexpr uint32_t dWm = ((sbase + kOffWm) >> 4) | (1u << 16);
    constexpr uint32_t dWv = ((sbase + kOffWv) >> 4) | (1u << 16);
    const float cs = 0.07216878364870322f * 1.4426950408889634f;
    mbar_wait(bar_w0, 0);
    mbar_wait(bar_full, 0);

    uint4 hv[12];
    uint8_t* hptr;
    uint32_t phase = 0;
    float acc[96];
    uint32_t ticket = 0;
    {
        const uint32_t dX = ((sbase + kOffX + wg_uniform() * kXBytes) >> 4) | (1u << 16);
        if (wg != 0) ring_wait();
        wg_fence();
        Gemm1<0, 3>::run(acc, dX, dWm);
        mbar_wait(sbase + kOffBar + 48, 0);
        wg_fence();
        Gemm1<4, 7>::run(acc, dX, dWm);
        mbar_wait(sbase + kOffBar + 56, 0);
        wg_fence();
        Gemm1<8, 11>::run(acc, dX, dWm);
        wg_commit();
        if (wg != 0) asm volatile("bar.arrive 8, 256;" ::: "memory");
        ticket = draw_ticket(tickets);
        wg_wait0();
    }

    while (true) {
        uint32_t fa[48];
        const uint32_t dX = ((sbase + kOffX + wg_uniform() * kXBytes) >> 4) | (1u << 16);
        fence_regs(acc);
#pragma unroll
        for (int i = 0; i < 48; i++) fa[i] = pack_bf16(acc[2 * i], acc[2 * i + 1]);

        float s[32];
        fence_regs(fa);
        ring_wait(fa[47]);
        wg_fence();
        Gemm2<11>::run(s, fa, dX);
        wg_commit();
        if constexpr (PASS2 == 11) ring_pass();
        if (((tid_now() >> 5) & 3) == 0) {
            if ((tid_now() & 31) == 0) {
                uint32_t nxt = kNWG * nctaid_now() + ticket;
                if (nxt >= kNWin) {
                    uint32_t p0, p1, p2, p3;
                    asm volatile("ld.shared.v4.u32 {%0, %1, %2, %3}, [%4];" : "=r"(p0), "=r"(p1), "=r"(p2), "=r"(p3) : "r"(sbase + kOffBar + 64) : "memory");
                    if ((p0 >= kNWin) + (p1 >= kNWin) + (p2 >= kNWin) == kNWG - 1) nxt = kLastOfCta;
                    if (ticket == kNWin - 1) { sc->cnt[0] = 0; sc->cnt[32] = 0; }
                }
                asm volatile("st.shared.u32 [%0], %1;" ::"r"(sbase + kOffBar + 64 + 4 * (tid_now() >> 7)), "r"(nxt) : "memory");
            }
            __syncwarp();
            asm volatile("bar.arrive %0, 128;" ::"r"((tid_now() >> 7) + 4) : "memory");
        }
        wg_wait0();
        fence_regs(s);
        fence_regs(fa);

        uint32_t pa[16];
        {
            float a0[8], a1[8];
#pragma unroll
            for (int j = 0; j < 8; j++) { a0[j] = fmaxf(s[4 * j], s[4 * j + 1]); a1[j] = fmaxf(s[4 * j + 2], s[4 * j + 3]); }
#pragma unroll
            for (int d = 4; d > 0; d >>= 1)
#pragma unroll
                for (int j = 0; j < d; j++) { a0[j] = fmaxf(a0[j], a0[j + d]); a1[j] = fmaxf(a1[j], a1[j + d]); }
            float m0 = a0[0], m1 = a1[0];
            m0 = fmaxf(m0, __shfl_xor_sync(0xffffffffu, m0, 1));
            m1 = fmaxf(m1, __shfl_xor_sync(0xffffffffu, m1, 1));
            m0 = fmaxf(m0, __shfl_xor_sync(0xffffffffu, m0, 2));
            m1 = fmaxf(m1, __shfl_xor_sync(0xffffffffu, m1, 2));
            m0 *= cs; m1 *= cs;
            float l0 = 0.f, l1 = 0.f;
#pragma unroll
            for (int j = 0; j < 8; j++) {
                s[4 * j]     = ex2(fmaf(s[4 * j], cs, -m0));
                s[4 * j + 1] = ex2(fmaf(s[4 * j + 1], cs, -m0));
                s[4 * j + 2] = ex2(fmaf(s[4 * j + 2], cs, -m1));
                s[4 * j + 3] = ex2(fmaf(s[4 * j + 3], cs, -m1));
                l0 += s[4 * j] + s[4 * j + 1];
                l1 += s[4 * j + 2] + s[4 * j + 3];
            }
            l0 += __shfl_xor_sync(0xffffffffu, l0, 1);
            l1 += __shfl_xor_sync(0xffffffffu, l1, 1);
            l0 += __shfl_xor_sync(0xffffffffu, l0, 2);
            l1 += __shfl_xor_sync(0xffffffffu, l1, 2);
            const float r0 = rcp(l0), r1 = rcp(l1);
#pragma unroll
            for (int j = 0; j < 8; j++) {
                pa[2 * j]     = pack_bf16(s[4 * j] * r0, s[4 * j + 1] * r0);
                pa[2 * j + 1] = pack_bf16(s[4 * j + 2] * r1, s[4 * j + 3] * r1);
            }
        }

        const uint32_t dXt = ((sbase + kOffX + wg_uniform() * kXBytes) >> 4) | ((8192u >> 4) << 16);
        if (((tid_now() >> 5) & 3) != 0) asm volatile("bar.sync %0, 128;" ::"r"((tid_now() >> 7) + 4) : "memory");
        uint32_t pub;
        asm volatile("ld.shared.u32 %0, [%1];" : "=r"(pub) : "r"(sbase + kOffBar + 64 + 4 * (tid_now() >> 7)) : "memory");
        const int nxt = (int)__reduce_or_sync(0xffffffffu, pub);
        store_p_if(pa, nxt == (int)kLastOfCta);
        if (nxt == (int)kLastOfCta) {
            last_window(out, win);
            asm volatile("exit;");
            __builtin_unreachable();
        }
        fence_regs(pa);
        ring_wait(pa[15]);
        wg_fence();
        Gemm3<3>::run(acc, pa, dXt);
        wg_commit();
        if constexpr (PASS3 == 3) ring_pass();
        wg_wait0();
        fence_regs(acc);
        fence_regs(pa);

        if (((tid_now() >> 5) & 3) == 0) {
            asm volatile("bar.sync %0, 128;" ::"r"((tid_now() >> 7) + 1) : "memory");
            if (elect_one()) {
                const uint32_t wgl = tid_now() >> 7;
                const uint32_t bar = sbase + kOffBar + 8 * wgl;
                if (nxt < kNWin) {
                    mbar_expect_tx(bar, kXBytes);
                    tma_load_x(sbase + kOffX + wgl * kXBytes, &tmx, bar, nxt);
                    prefetch_for_ticket(&tmp, nxt - kNWG * (int)gridDim.x);
                }
            }
            __syncwarp();
        } else {
            asm volatile("bar.arrive %0, 128;" ::"r"((tid_now() >> 7) + 1) : "memory");
        }
#pragma unroll
        for (int i = 0; i < 48; i++) fa[i] = pack_bf16(acc[2 * i], acc[2 * i + 1]);

        asm volatile("st.volatile.shared.v4.b32 [%4], {%0, %1, %2, %3};"
                     :: "r"(fa[44]), "r"(fa[45]), "r"(fa[46]), "r"(fa[47]), "r"(sbase + kOffStash + tid_now() * 16) : "memory");
        mbar_wait(sbase + kOffBar + 40, 0);
        fence_regs(fa);
        ring_wait(fa[43]);
        wg_fence();
        Gemm4<0, 1>::run(acc, fa, dWv);
        wg_commit();
        Gemm4<2, 10>::run(acc, fa, dWv);
        wg_commit();
        wg_wait1();
        uint32_t fl[4];
        asm volatile("ld.volatile.shared.v4.b32 {%0, %1, %2, %3}, [%4];"
                     : "=r"(fl[0]), "=r"(fl[1]), "=r"(fl[2]), "=r"(fl[3]) : "r"(sbase + kOffStash + tid_now() * 16) : "memory");
        wg_fence();
        wg192_rs<false, 0, koff(11, 24576)>(acc, fl, dWv);
        wg_commit();
        if (nxt >= kNWin) count_finished();
        ring_pass();
        hptr = out_address(out, win);
        win = nxt;
        const uint32_t dX1 = ((sbase + kOffX + wg_uniform() * kXBytes) >> 4) | (1u << 16);
        phase ^= 1;
        if (win < kNWin) mbar_wait(sbase + kOffBar + 8 * (tid_now() >> 7), phase);
        asm volatile("" : "+l"(hptr) :: "memory");
        wg_wait0();
        fence_regs(acc);
        fence_regs(fa);
        fence_regs(fl);

#pragma unroll
        for (int a = 0; a < 6; a++) {
            hv[2 * a].x     = pack_bf16(acc[16 * a + 0], acc[16 * a + 1]);
            hv[2 * a].y     = pack_bf16(acc[16 * a + 4], acc[16 * a + 5]);
            hv[2 * a].z     = pack_bf16(acc[16 * a + 8], acc[16 * a + 9]);
            hv[2 * a].w     = pack_bf16(acc[16 * a + 12], acc[16 * a + 13]);
            hv[2 * a + 1].x = pack_bf16(acc[16 * a + 2], acc[16 * a + 3]);
            hv[2 * a + 1].y = pack_bf16(acc[16 * a + 6], acc[16 * a + 7]);
            hv[2 * a + 1].z = pack_bf16(acc[16 * a + 10], acc[16 * a + 11]);
            hv[2 * a + 1].w = pack_bf16(acc[16 * a + 14], acc[16 * a + 15]);
        }
        if constexpr (slot_begin(0) > 0) {
            __syncwarp();
            store_slot<-1>(hv, hptr);
            __syncwarp();
        }
        if (win >= kNWin) break;
        ring_wait(hv[11].w);
        wg_fence();
        Gemm1St<11>::run(acc, dX1, dWm, hv, hptr);
        ticket = draw_ticket(tickets);
        if constexpr (slot_begin(12) < 12) store_paced<slot_begin(12)>(hv, hptr, clock_now());
        wg_wait0();
    }
    {
        const uint32_t me = tid_now() >> 7, nx = me == kNWG - 1 ? 0 : me + 1;
        uint32_t nd, last;
        bool stored = false;
        while (true) {
            ring_wait();
            asm volatile("ld.volatile.shared.v2.u32 {%0, %1}, [%2];" : "=r"(nd), "=r"(last) : "r"(sbase + kOffBar + 80) : "memory");
            const bool all = nd == kNWG;
            if (!all || nx != last) ring_pass();
            if (!stored) { store_tail<slot_begin(0)>(hv, hptr, clock_now()); stored = true; }
            if (all) break;
        }
    }
}

typedef CUresult (*EncodeTiledFn)(CUtensorMap*, CUtensorMapDataType, cuuint32_t, void*, const cuuint64_t*,
                                  const cuuint64_t*, const cuuint32_t*, const cuuint32_t*, CUtensorMapInterleave,
                                  CUtensorMapSwizzle, CUtensorMapL2promotion, CUtensorMapFloatOOBfill);

}

extern "C" void kernel_launch(void* const* d_in, const int* in_sizes, int n_in, void* d_out, int out_size) {
    (void)in_sizes; (void)n_in; (void)out_size;
    const __nv_bfloat16* x    = (const __nv_bfloat16*)d_in[0];
    const __nv_bfloat16* wqkv = (const __nv_bfloat16*)d_in[1];
    const __nv_bfloat16* wo   = (const __nv_bfloat16*)d_in[2];

    static EncodeTiledFn encode = nullptr;
    static int num_sms = 0;
    static void* scratch = nullptr;
    if (!encode) {
        void* fn = nullptr;
        cudaDriverEntryPointQueryResult qr;
        cudaGetDriverEntryPoint("cuTensorMapEncodeTiled", &fn, cudaEnableDefault, &qr);
        encode = (EncodeTiledFn)fn;
        int dev = 0;
        cudaGetDevice(&dev);
        cudaDeviceGetAttribute(&num_sms, cudaDevAttrMultiProcessorCount, dev);
        cudaGetSymbolAddress(&scratch, g_scratch);
        cudaFuncSetAttribute(swin_attn_kernel<false>, cudaFuncAttributeMaxDynamicSharedMemorySize, kSmemBytes);
        cudaFuncSetAttribute(swin_attn_kernel<true>, cudaFuncAttributeMaxDynamicSharedMemorySize, kSmemBytes);
    }
    CUtensorMap tmx;
    const cuuint64_t gdim[4] = {64, (cuuint64_t)kHW, (cuuint64_t)kHW, 3};
    const cuuint64_t gstr[3] = {(cuuint64_t)kC * 2, (cuuint64_t)kHW * kC * 2, 128};
    const cuuint32_t box[4] = {64, 8, 8, 3};
    const cuuint32_t estr[4] = {1, 1, 1, 1};
    encode(&tmx, CU_TENSOR_MAP_DATA_TYPE_BFLOAT16, 4, (void*)x, gdim, gstr, box, estr, CU_TENSOR_MAP_INTERLEAVE_NONE,
           CU_TENSOR_MAP_SWIZZLE_128B, CU_TENSOR_MAP_L2_PROMOTION_NONE, CU_TENSOR_MAP_FLOAT_OOB_FILL_NONE);

    CUtensorMap tmp;
    const cuuint64_t pdim[3] = {(cuuint64_t)kC, (cuuint64_t)kHW, (cuuint64_t)kHW};
    const cuuint64_t pstr[2] = {(cuuint64_t)kC * 2, (cuuint64_t)kHW * kC * 2};
    const cuuint32_t pbox[3] = {(cuuint32_t)kC, 8, 8};
    encode(&tmp, CU_TENSOR_MAP_DATA_TYPE_BFLOAT16, 3, (void*)x, pdim, pstr, pbox, estr, CU_TENSOR_MAP_INTERLEAVE_NONE,
           CU_TENSOR_MAP_SWIZZLE_NONE, CU_TENSOR_MAP_L2_PROMOTION_NONE, CU_TENSOR_MAP_FLOAT_OOB_FILL_NONE);
    CUtensorMap tmc;
    const cuuint32_t boxc[4] = {64, 8, 8, 1};
    encode(&tmc, CU_TENSOR_MAP_DATA_TYPE_BFLOAT16, 4, (void*)x, gdim, gstr, boxc, estr, CU_TENSOR_MAP_INTERLEAVE_NONE,
           CU_TENSOR_MAP_SWIZZLE_128B, CU_TENSOR_MAP_L2_PROMOTION_NONE, CU_TENSOR_MAP_FLOAT_OOB_FILL_NONE);
    if (num_sms >= kJobs)
        swin_attn_kernel<false><<<num_sms, kThreads, kSmemBytes, cudaStreamPerThread>>>(wqkv, wo, (__nv_bfloat16*)d_out, (Scratch*)scratch, ((Scratch*)scratch)->ticket, tmx, tmp, tmc);
    else
        swin_attn_kernel<true><<<num_sms, kThreads, kSmemBytes, cudaStreamPerThread>>>(wqkv, wo, (__nv_bfloat16*)d_out, (Scratch*)scratch, ((Scratch*)scratch)->ticket, tmx, tmp, tmc);
}
```

```cpp
#include <cuda_runtime.h>
#include <cuda_bf16.h>
#include <cuda.h>
#include <stdint.h>

namespace {

constexpr int kC      = 192;
constexpr int kHW     = 512;
#define MAXWIN 4096
constexpr int kNWin   = MAXWIN;
constexpr int kXBytes = 64 * kC * 2;
constexpr int kWBytes = kC * kC * 2;
constexpr int kNWG    = 3;
constexpr int kThreads = kNWG * 128;
constexpr int kJobsM  = 72;
constexpr int kJobs   = 120;
constexpr int kWarmW  = 4;
#define PF_LEAD 400
#define PF_UP 170
#define PF_DOWN 34
#define PF_MIN 135
#define TRK_T0 400
#define TRK_S 1800
#define REQ_T 2600
#define REQ_TV 4000

constexpr int kOffWm  = 0;
constexpr int kOffWv  = kWBytes;
constexpr int kOffX   = 2 * kWBytes;
constexpr int kOffBar = kOffX + kNWG * kXBytes;
constexpr int kOffStash = kOffBar + 128;
constexpr int kOffProf = kOffStash + kThreads * 16;
constexpr int kSmemBytes = kOffProf;
constexpr uint32_t kSmemBase = 1024;

struct Scratch {
    uint4 wfold[2 * kWBytes / 16];
    uint32_t ticket[32];
    uint32_t cnt[32];
};
__device__ __align__(128) Scratch g_scratch;

__device__ __forceinline__ uint32_t smem_u32(const void* p) { return (uint32_t)__cvta_generic_to_shared(p); }

__device__ __forceinline__ void mbar_init(uint32_t bar, uint32_t count) {
    asm volatile("mbarrier.init.shared::cta.b64 [%0], %1;" ::"r"(bar), "r"(count) : "memory");
}
__device__ __forceinline__ void mbar_expect_tx(uint32_t bar, uint32_t bytes) {
    asm volatile("mbarrier.arrive.expect_tx.shared::cta.b64 _, [%0], %1;" ::"r"(bar), "r"(bytes) : "memory");
}
__device__ __forceinline__ void mbar_wait(uint32_t bar, uint32_t parity) {
    uint32_t ok;
    uint32_t spins = 0;
    do {
        asm volatile("{\n.reg .pred p;\n"
                     "mbarrier.try_wait.parity.shared::cta.b64 p, [%1], %2;\n"
                     "selp.b32 %0, 1, 0, p;\n}\n"
                     : "=r"(ok) : "r"(bar), "r"(parity) : "memory");
        if (++spins > (1u << 26)) __trap();
    } while (!ok);
}
__device__ __forceinline__ uint32_t tid_now() {
    uint32_t t;
    asm volatile("mov.u32 %0, %%tid.x;" : "=r"(t));
    return t;
}
__device__ __forceinline__ uint32_t nctaid_now() {
    uint32_t t;
    asm volatile("mov.u32 %0, %%nctaid.x;" : "=r"(t));
    return t;
}
__device__ __forceinline__ bool elect_one() {
    uint32_t pred;
    asm volatile("{\n.reg .pred p;\nelect.sync _|p, 0xffffffff;\nselp.b32 %0, 1, 0, p;\n}\n" : "=r"(pred));
    return pred != 0;
}
#define PASS1 11
#define PASS2 5
#define PASS3 3
__device__ __forceinline__ void ring_wait() {
    asm volatile("bar.sync %0, 256;" ::"r"((tid_now() >> 7) + 8) : "memory");
}
__device__ __forceinline__ void ring_pass() {
    const uint32_t w = tid_now() >> 7;
    asm volatile("bar.arrive %0, 256;" ::"r"(w == kNWG - 1 ? 8u : w + 9u) : "memory");
}
constexpr uint32_t kLastOfCta = 0x40000000u;
__device__ __forceinline__ uint32_t wg_uniform() { return __reduce_or_sync(0xffffffffu, tid_now() >> 7); }
__device__ __forceinline__ uint32_t desc_x(uint32_t w) { return (((kSmemBase + kOffX) >> 4) | (1u << 16)) + w * (kXBytes >> 4); }
__device__ __forceinline__ uint32_t desc_xt(uint32_t w) { return (((kSmemBase + kOffX) >> 4) | ((8192u >> 4) << 16)) + w * (kXBytes >> 4); }
__device__ __forceinline__ void tma_load_x(uint32_t dst, const CUtensorMap* tm, uint32_t bar, int win) {
    const int wh = win >> 6, ww = win & 63;
    asm volatile("cp.async.bulk.tensor.4d.shared::cluster.global.mbarrier::complete_tx::bytes"
                 " [%0], [%1, {%3, %4, %5, %6}], [%2];"
                 ::"r"(dst), "l"(tm), "r"(bar), "r"(0), "r"(ww * 8), "r"(wh * 8), "r"(0) : "memory");
}
__device__ __forceinline__ void tma_load_x_chunk(uint32_t dst, const CUtensorMap* tm, uint32_t bar, int win, int chunk) {
    const int wh = win >> 6, ww = win & 63;
    asm volatile("cp.async.bulk.tensor.4d.shared::cluster.global.mbarrier::complete_tx::bytes"
                 " [%0], [%1, {%3, %4, %5, %6}], [%2];"
                 ::"r"(dst), "l"(tm), "r"(bar), "r"(0), "r"(ww * 8), "r"(wh * 8), "r"(chunk) : "memory");
}
__device__ __forceinline__ void bulk_load(uint32_t dst, const void* src, uint32_t bytes, uint32_t bar) {
    asm volatile("cp.async.bulk.shared::cluster.global.mbarrier::complete_tx::bytes [%0], [%1], %2, [%3];"
                 ::"r"(dst), "l"(src), "r"(bytes), "r"(bar) : "memory");
}

__device__ __forceinline__ void stg128(void* p, uint4 v) {
    asm volatile("st.global.v4.b32 [%0], {%1, %2, %3, %4};" ::"l"(p), "r"(v.x), "r"(v.y), "r"(v.z), "r"(v.w) : "memory");
}
__device__ __forceinline__ void wg_fence()  { asm volatile("wgmma.fence.sync.aligned;" ::: "memory"); }
__device__ __forceinline__ void wg_commit() { asm volatile("wgmma.commit_group.sync.aligned;" ::: "memory"); }
__device__ __forceinline__ void wg_wait0()  { asm volatile("wgmma.wait_group.sync.aligned 0;" ::: "memory"); }
__device__ __forceinline__ void wg_wait1()  { asm volatile("wgmma.wait_group.sync.aligned 1;" ::: "memory"); }
__device__ __forceinline__ void wg_wait2()  { asm volatile("wgmma.wait_group.sync.aligned 2;" ::: "memory"); }

template <int N> __device__ __forceinline__ void fence_regs(float (&d)[N]) {
#pragma unroll
    for (int i = 0; i < N; i++) asm volatile("" : "+f"(d[i])::"memory");
}
template <int N> __device__ __forceinline__ void fence_regs(uint32_t (&d)[N]) {
#pragma unroll
    for (int i = 0; i < N; i++) asm volatile("" : "+r"(d[i])::"memory");
}

#define ACC8(c, d, i) c(d[i]), c(d[i + 1]), c(d[i + 2]), c(d[i + 3]), c(d[i + 4]), c(d[i + 5]), c(d[i + 6]), c(d[i + 7])
#define ACC32(c, d) ACC8(c, d, 0), ACC8(c, d, 8), ACC8(c, d, 16), ACC8(c, d, 24)
#define ACC96(c, d) ACC32(c, d), ACC8(c, d, 32), ACC8(c, d, 40), ACC8(c, d, 48), ACC8(c, d, 56), \
                    ACC8(c, d, 64), ACC8(c, d, 72), ACC8(c, d, 80), ACC8(c, d, 88)
#define C_IO(x) "+f"(x)
#define C_O(x) "=f"(x)
#define REGS32 "{%0, %1, %2, %3, %4, %5, %6, %7, %8, %9, %10, %11, %12, %13, %14, %15, " \
               "%16, %17, %18, %19, %20, %21, %22, %23, %24, %25, %26, %27, %28, %29, %30, %31}"
#define REGS96 "{%0, %1, %2, %3, %4, %5, %6, %7, %8, %9, %10, %11, %12, %13, %14, %15, " \
               "%16, %17, %18, %19, %20, %21, %22, %23, %24, %25, %26, %27, %28, %29, %30, %31, " \
               "%32, %33, %34, %35, %36, %37, %38, %39, %40, %41, %42, %43, %44, %45, %46, %47, " \
               "%48, %49, %50, %51, %52, %53, %54, %55, %56, %57, %58, %59, %60, %61, %62, %63, " \
               "%64, %65, %66, %67, %68, %69, %70, %71, %72, %73, %74, %75, %76, %77, %78, %79, " \
               "%80, %81, %82, %83, %84, %85, %86, %87, %88, %89, %90, %91, %92, %93, %94, %95}"

#define DESC_HI "0x40000040"
#define MK_DESC(name, lo, off) "add.u32 t, " lo ", " off ";\nmov.b64 " name ", {t, " DESC_HI "};\n"

template <bool First, int OA, int OB> __device__ __forceinline__ void wg192_ss(float (&d)[96], uint32_t la, uint32_t lb) {
    if constexpr (First)
        asm volatile("{\n.reg .pred p;\n.reg .b32 t;\n.reg .b64 da, db;\nsetp.ne.b32 p, 0, 0;\n"
                     MK_DESC("da", "%96", "%98") MK_DESC("db", "%97", "%99")
                     "wgmma.mma_async.sync.aligned.m64n192k16.f32.bf16.bf16 " REGS96 ", da, db, p, 1, 1, 0, 0;\n}\n"
                     : ACC96(C_O, d) : "r"(la), "r"(lb), "n"(OA), "n"(OB));
    else
        asm volatile("{\n.reg .pred p;\n.reg .b32 t;\n.reg .b64 da, db;\nsetp.ne.b32 p, 1, 0;\n"
                     MK_DESC("da", "%96", "%98") MK_DESC("db", "%97", "%99")
                     "wgmma.mma_async.sync.aligned.m64n192k16.f32.bf16.bf16 " REGS96 ", da, db, p, 1, 1, 0, 0;\n}\n"
                     : ACC96(C_IO, d) : "r"(la), "r"(lb), "n"(OA), "n"(OB));
}
template <bool First, int TB, int OB> __device__ __forceinline__ void wg192_rs(float (&d)[96], const uint32_t* a, uint32_t lb) {
    if constexpr (First)
        asm volatile("{\n.reg .pred p;\n.reg .b32 t;\n.reg .b64 db;\nsetp.ne.b32 p, 0, 0;\n"
                     MK_DESC("db", "%100", "%102")
                     "wgmma.mma_async.sync.aligned.m64n192k16.f32.bf16.bf16 " REGS96 ", {%96, %97, %98, %99}, db, p, 1, 1, %101;\n}\n"
                     : ACC96(C_O, d) : "r"(a[0]), "r"(a[1]), "r"(a[2]), "r"(a[3]), "r"(lb), "n"(TB), "n"(OB));
    else
        asm volatile("{\n.reg .pred p;\n.reg .b32 t;\n.reg .b64 db;\nsetp.ne.b32 p, 1, 0;\n"
                     MK_DESC("db", "%100", "%102")
                     "wgmma.mma_async.sync.aligned.m64n192k16.f32.bf16.bf16 " REGS96 ", {%96, %97, %98, %99}, db, p, 1, 1, %101;\n}\n"
                     : ACC96(C_IO, d) : "r"(a[0]), "r"(a[1]), "r"(a[2]), "r"(a[3]), "r"(lb), "n"(TB), "n"(OB));
}
template <bool First, int OB> __device__ __forceinline__ void wg64_rs(float (&d)[32], const uint32_t* a, uint32_t lb) {
    if constexpr (First)
        asm volatile("{\n.reg .pred p;\n.reg .b32 t;\n.reg .b64 db;\nsetp.ne.b32 p, 0, 0;\n"
                     MK_DESC("db", "%36", "%37")
                     "wgmma.mma_async.sync.aligned.m64n64k16.f32.bf16.bf16 " REGS32 ", {%32, %33, %34, %35}, db, p, 1, 1, 0;\n}\n"
                     : ACC32(C_O, d) : "r"(a[0]), "r"(a[1]), "r"(a[2]), "r"(a[3]), "r"(lb), "n"(OB));
    else
        asm volatile("{\n.reg .pred p;\n.reg .b32 t;\n.reg .b64 db;\nsetp.ne.b32 p, 1, 0;\n"
                     MK_DESC("db", "%36", "%37")
                     "wgmma.mma_async.sync.aligned.m64n64k16.f32.bf16.bf16 " REGS32 ", {%32, %33, %34, %35}, db, p, 1, 1, 0;\n}\n"
                     : ACC32(C_IO, d) : "r"(a[0]), "r"(a[1]), "r"(a[2]), "r"(a[3]), "r"(lb), "n"(OB));
}
template <bool First, int OA, int OB> __device__ __forceinline__ void wg64_ss(float (&d)[32], uint32_t la, uint32_t lb) {
    if constexpr (First)
        asm volatile("{\n.reg .pred p;\n.reg .b32 t;\n.reg .b64 da, db;\nsetp.ne.b32 p, 0, 0;\n"
                     MK_DESC("da", "%32", "%34") MK_DESC("db", "%33", "%35")
                     "wgmma.mma_async.sync.aligned.m64n64k16.f32.bf16.bf16 " REGS32 ", da, db, p, 1, 1, 0, 1;\n}\n"
                     : ACC32(C_O, d) : "r"(la), "r"(lb), "n"(OA), "n"(OB));
    else
        asm volatile("{\n.reg .pred p;\n.reg .b32 t;\n.reg .b64 da, db;\nsetp.ne.b32 p, 1, 0;\n"
                     MK_DESC("da", "%32", "%34") MK_DESC("db", "%33", "%35")
                     "wgmma.mma_async.sync.aligned.m64n64k16.f32.bf16.bf16 " REGS32 ", da, db, p, 1, 1, 0, 1;\n}\n"
                     : ACC32(C_IO, d) : "r"(la), "r"(lb), "n"(OA), "n"(OB));
}
__host__ __device__ constexpr int koff(int kk, int chunk) { return ((kk >> 2) * chunk + (kk & 3) * 32) >> 4; }

#define ST_SLOTS 0x2000000000001ull
__host__ __device__ constexpr int slot_begin(int i) {
    int b = 0;
    for (int k = -1; k < i; k++) b += (int)((ST_SLOTS >> (4 * (11 - k))) & 15);
    return b;
}
#define PACE_DT 160
#define SPIN_NS 50
template <int J> __device__ __forceinline__ void store_one(const uint4 (&h)[12], uint8_t* hptr) {
    constexpr int r = J / 6, a = J % 6;
    stg128(hptr + r * (kHW * kC * 2) + a * 64, h[2 * a + r]);
}
template <int J, int E> __device__ __forceinline__ void store_range(uint4 (&h)[12], uint8_t* hptr) {
    if constexpr (J < E) {
        store_one<J>(h, hptr);
        store_range<J + 1, E>(h, hptr);
    }
}
template <int I> __device__ __forceinline__ void store_slot(uint4 (&h)[12], uint8_t* hptr) {
    store_range<slot_begin(I), slot_begin(I + 1)>(h, hptr);
}
__device__ __forceinline__ uint32_t clock_now() {
    uint32_t t;
    asm volatile("mov.u32 %0, %%clock;" : "=r"(t));
    return t;
}
template <int J> __device__ __forceinline__ void store_paced(uint4 (&h)[12], uint8_t* hptr, uint32_t t0) {
    if constexpr (J < 12) {
        while (clock_now() - t0 < (uint32_t)((J - slot_begin(12) + 1) * PACE_DT)) asm volatile("nanosleep.u32 %0;" ::"n"(SPIN_NS));
        store_one<J>(h, hptr);
        store_paced<J + 1>(h, hptr, t0);
    }
}
#define TAIL_DT 70
template <int J> __device__ __forceinline__ void store_tail(uint4 (&h)[12], uint8_t* hptr, uint32_t t0) {
    if constexpr (J < 12) {
        if constexpr (J > slot_begin(0)) { while (clock_now() - t0 < (uint32_t)((J - slot_begin(0)) * TAIL_DT)) {} }
        store_one<J>(h, hptr);
        store_tail<J + 1>(h, hptr, t0);
    }
}
template <int K> struct Gemm1St {
    static __device__ __forceinline__ void run(float (&d)[96], uint32_t lx, uint32_t lw, uint4 (&h)[12], uint8_t* hptr) {
        if constexpr (K > 0) Gemm1St<K - 1>::run(d, lx, lw, h, hptr);
        wg192_ss<K == 0, koff(K, 8192), koff(K, 24576)>(d, lx, lw);
        if constexpr (K == 11) wg_commit();
        if constexpr (K == PASS1) ring_pass();
        if constexpr (slot_begin(K + 1) > slot_begin(K)) {
            __syncwarp();
            store_slot<K>(h, hptr);
            __syncwarp();
        }
    }
};
template <int K0, int K> struct Gemm1 {
    static __device__ __forceinline__ void run(float (&d)[96], uint32_t lx, uint32_t lw) {
        if constexpr (K > K0) Gemm1<K0, K - 1>::run(d, lx, lw);
        wg192_ss<K == 0, koff(K, 8192), koff(K, 24576)>(d, lx, lw);
    }
};
__device__ __forceinline__ uint32_t draw_ticket(uint32_t* counter) {
    uint32_t ticket = 0;
    asm volatile("{\n.reg .pred p;\nsetp.eq.u32 p, %2, 0;\n@p atom.relaxed.gpu.global.inc.u32 %0, [%1], %3;\n}\n"
                 : "+r"(ticket) : "l"(counter), "r"(tid_now() & 127), "n"(kNWin - 1) : "memory");
    return ticket;
}
template <int KK> struct Gemm2 { static __device__ __forceinline__ void run(float (&d)[32], const uint32_t* a, uint32_t lx) {
    Gemm2<KK - 1>::run(d, a, lx); wg64_rs<KK == 0, koff(KK, 8192)>(d, a + 4 * KK, lx);
    if constexpr (KK == PASS2 && KK < 11) ring_pass(); } };
template <> struct Gemm2<-1> { static __device__ __forceinline__ void run(float (&)[32], const uint32_t*, uint32_t) {} };
template <int KK> struct Gemm3 { static __device__ __forceinline__ void run(float (&d)[96], const uint32_t* a, uint32_t lxt) {
    Gemm3<KK - 1>::run(d, a, lxt); wg192_rs<KK == 0, 1, KK * (2048 >> 4)>(d, a + 4 * KK, lxt);
    if constexpr (KK == PASS3 && KK < 3) ring_pass(); } };
template <> struct Gemm3<-1> { static __device__ __forceinline__ void run(float (&)[96], const uint32_t*, uint32_t) {} };
template <int K0, int KK> struct Gemm4 { static __device__ __forceinline__ void run(float (&d)[96], const uint32_t* a, uint32_t lw) {
    if constexpr (KK > K0) Gemm4<K0, KK - 1>::run(d, a, lw);
    wg192_rs<KK == 0, 0, koff(KK, 24576)>(d, a + 4 * KK, lw); } };

template <int J, int KK> struct Gemm3s { static __device__ __forceinline__ void run(float (&d)[32], uint32_t lp, uint32_t lxt) {
    if constexpr (KK > 0) Gemm3s<J, KK - 1>::run(d, lp, lxt);
    wg64_ss<KK == 0, KK * 2, (J * 8192 + KK * 2048) / 16>(d, lp, lxt); } };
template <int J, int K0, int KK> struct Gemm4s { static __device__ __forceinline__ void run(float (&d)[32], const uint32_t* a, uint32_t lw) {
    if constexpr (KK > K0) Gemm4s<J, K0, KK - 1>::run(d, a, lw);
    wg64_rs<KK == 0, koff(KK, 24576) + J * (8192 / 16)>(d, a + 4 * KK, lw); } };

__device__ __forceinline__ uint32_t pack_bf16(float lo, float hi) {
    uint32_t r;
    asm("cvt.rn.bf16x2.f32 %0, %1, %2;" : "=r"(r) : "f"(hi), "f"(lo));
    return r;
}
__device__ __forceinline__ float ex2(float x) {
    float r;
    asm("ex2.approx.ftz.f32 %0, %1;" : "=f"(r) : "f"(x));
    return r;
}
__device__ __forceinline__ float rcp(float x) {
    float r;
    asm("rcp.approx.ftz.f32 %0, %1;" : "=f"(r) : "f"(x));
    return r;
}

__device__ __forceinline__ void pack_slice(uint32_t* a, float (&d)[32]) {
    fence_regs(d);
#pragma unroll
    for (int i = 0; i < 16; i++) a[i] = pack_bf16(d[2 * i], d[2 * i + 1]);
#pragma unroll
    for (int i = 0; i < 16; i++) asm volatile("" : "+r"(a[i])::"memory");
}
template <int J> __device__ __forceinline__ void store_slice(float (&d)[32], uint8_t* hptr) {
    fence_regs(d);
#pragma unroll
    for (int r = 0; r < 2; r++) {
        uint4 h[2];
#pragma unroll
        for (int a = 0; a < 2; a++) {
            const int o = 16 * a + 2 * r;
            h[a] = make_uint4(pack_bf16(d[o], d[o + 1]), pack_bf16(d[o + 4], d[o + 5]), pack_bf16(d[o + 8], d[o + 9]), pack_bf16(d[o + 12], d[o + 13]));
        }
        stg128(hptr + r * (kHW * kC * 2) + J * 128, h[0]);
        stg128(hptr + r * (kHW * kC * 2) + J * 128 + 64, h[1]);
    }
    __syncwarp();
}
__device__ __forceinline__ uint8_t* out_address(__nv_bfloat16* out, int win) {
    const uint32_t ln = tid_now() & 31;
    return reinterpret_cast<uint8_t*>(out) + (uint32_t)((win >> 6) * 8 * kHW + (win & 63) * 8 + 2 * ((tid_now() >> 5) & 3) * kHW + (ln >> 2)) * (uint32_t)(kC * 2) + (ln & 3) * 16;
}
__device__ __forceinline__ void count_finished() {
    if (((tid_now() >> 5) & 3) == 0) {
        if (elect_one()) {
            uint32_t nd;
            asm volatile("ld.shared.u32 %0, [%1];" : "=r"(nd) : "r"(kSmemBase + kOffBar + 80) : "memory");
            asm volatile("st.shared.v2.u32 [%0], {%1, %2};" ::"r"(kSmemBase + kOffBar + 80), "r"(nd + 1), "r"(tid_now() >> 7) : "memory");
        }
        __syncwarp();
    }
}
__device__ __forceinline__ void store_p_if(const uint32_t (&pa)[16], bool cond) {
    const uint32_t t = tid_now(), w = t >> 7, row = ((t >> 1) & 48) + (t & 15);
    const uint32_t adr = kSmemBase + kOffX + (w == kNWG - 1 ? 0 : w + 1) * kXBytes + row * 128 + ((((t >> 4) & 1) ^ (t & 7)) << 4);
#pragma unroll
    for (int i = 0; i < 4; i++)
        asm volatile("{\n.reg .pred p;\nsetp.ne.u32 p, %5, 0;\n@p stmatrix.sync.aligned.m8n8.x4.shared.b16 [%4], {%0, %1, %2, %3};\n}\n"
                     :: "r"(pa[4 * i]), "r"(pa[4 * i + 1]), "r"(pa[4 * i + 2]), "r"(pa[4 * i + 3]), "r"(adr ^ (i << 5)), "r"((uint32_t)cond) : "memory");
}
__device__ __forceinline__ void last_window(__nv_bfloat16* out, int win) {
    constexpr uint32_t dWv = ((kSmemBase + kOffWv) >> 4) | (1u << 16);
    asm volatile("fence.proxy.async.shared::cta;" ::: "memory");
    const uint32_t w = wg_uniform();
    const uint32_t dXt = desc_xt(w);
    const uint32_t dP = desc_x(w == kNWG - 1 ? 0 : w + 1);
    float u0[32], u1[32], u2[32];
    uint32_t fa[48];
    uint8_t* hptr = out_address(out, win);
    asm volatile("" : "+l"(hptr) :: "memory");
    ring_wait();
    wg_fence();
    Gemm3s<0, 3>::run(u0, dP, dXt); wg_commit();
    Gemm3s<1, 3>::run(u1, dP, dXt); wg_commit();
    Gemm3s<2, 3>::run(u2, dP, dXt); wg_commit();
    count_finished();
    ring_pass();
    wg_wait2();
    pack_slice(fa, u0);
    wg_wait1();
    pack_slice(fa + 16, u1);
    wg_fence();
    Gemm4s<0, 0, 7>::run(u0, fa, dWv); wg_commit();
    wg_wait1();
    pack_slice(fa + 32, u2);
    wg_fence();
    Gemm4s<0, 8, 11>::run(u0, fa, dWv); wg_commit();
    Gemm4s<1, 0, 5>::run(u1, fa, dWv); wg_commit();
    wg_wait1();
    store_slice<0>(u0, hptr);
    wg_fence();
    Gemm4s<1, 6, 11>::run(u1, fa, dWv); wg_commit();
    Gemm4s<2, 0, 5>::run(u2, fa, dWv); wg_commit();
    wg_wait1();
    store_slice<1>(u1, hptr);
    wg_fence();
    Gemm4s<2, 6, 11>::run(u2, fa, dWv); wg_commit();
    wg_wait0();
    fence_regs(fa);
    store_slice<2>(u2, hptr);
}

__device__ __forceinline__ int fold_offset(int n, int k0, int q) {
    const int u = ((k0 & 63) >> 3) + (q >> 1);
    return (k0 >> 6) * 24576 + (q & 1) * 8 + n * 128 + ((u ^ (n & 7)) << 4);
}
__device__ __forceinline__ void mma16816x2(float (&c)[4], float (&d)[4], const uint32_t (&a)[4], const uint32_t (&b)[4]) {
    asm volatile("mma.sync.aligned.m16n8k16.row.col.f32.bf16.bf16.f32 {%0,%1,%2,%3}, {%8,%9,%10,%11}, {%12,%13}, {%0,%1,%2,%3};\n"
                 "mma.sync.aligned.m16n8k16.row.col.f32.bf16.bf16.f32 {%4,%5,%6,%7}, {%8,%9,%10,%11}, {%14,%15}, {%4,%5,%6,%7};"
                 : "+f"(c[0]), "+f"(c[1]), "+f"(c[2]), "+f"(c[3]), "+f"(d[0]), "+f"(d[1]), "+f"(d[2]), "+f"(d[3])
                 : "r"(a[0]), "r"(a[1]), "r"(a[2]), "r"(a[3]), "r"(b[0]), "r"(b[1]), "r"(b[2]), "r"(b[3]));
}
__device__ __forceinline__ void cp_async16(uint32_t dst, const void* src) {
    asm volatile("cp.async.cg.shared.global [%0], [%1], 16;" ::"r"(dst), "l"(src) : "memory");
}
template <bool kTrans> __device__ __forceinline__ void ldsm4(uint32_t (&r)[4], uint32_t addr) {
    if constexpr (kTrans)
        asm volatile("ldmatrix.sync.aligned.m8n8.x4.trans.shared.b16 {%0, %1, %2, %3}, [%4];" : "=r"(r[0]), "=r"(r[1]), "=r"(r[2]), "=r"(r[3]) : "r"(addr) : "memory");
    else
        asm volatile("ldmatrix.sync.aligned.m8n8.x4.shared.b16 {%0, %1, %2, %3}, [%4];" : "=r"(r[0]), "=r"(r[1]), "=r"(r[2]), "=r"(r[3]) : "r"(addr) : "memory");
}
__device__ __forceinline__ uint32_t nonzero(uint32_t w) { return w ? w : 0x80000000u; }
__device__ __forceinline__ void fold_job(Scratch* sc, const __nv_bfloat16* __restrict__ wqkv, const __nv_bfloat16* __restrict__ wo,
                                         int job, int warp, int lane) {
    const bool vo = job >= kJobsM;
    const int nw = vo ? 3 : 2, tile0 = vo ? 3 * (job - kJobsM) : 2 * job;
    const int n0 = (tile0 / 12) * 16, k0 = (tile0 % 12 + max(warp, 1) - 1) * 16;
    const uint32_t stage = kSmemBase + kOffWv;
    if (warp <= nw) {
        if (vo && warp == 0) {
            const char* src = reinterpret_cast<const char*>(wo + (lane >> 1) * kC + n0 + (lane & 1) * 8);
            const uint32_t dst = stage + ((lane ^ ((lane >> 3) & 1)) << 4);
#pragma unroll
            for (int i = 0; i < 12; i++) cp_async16(dst + i * 512, src + i * 16 * kC * 2);
        } else {
            const int row0 = warp == 0 ? n0 : k0, col0 = warp == 0 ? kC : vo ? 2 * kC : 0;
            const char* src = reinterpret_cast<const char*>(wqkv + (row0 + (lane >> 3)) * (3 * kC) + col0 + (lane & 7) * 8);
            const uint32_t dst = stage + warp * 6144 + (lane >> 3) * 384 + (((lane & 7) ^ (lane >> 3)) << 4);
#pragma unroll
            for (int i = 0; i < 12; i++) cp_async16((dst ^ (((i / 3) & 1) << 6)) + (i / 3) * 1536 + (i % 3) * 128, src + (i / 3) * 4 * 3 * kC * 2 + (i % 3) * 128);
        }
        asm volatile("cp.async.wait_all;" ::: "memory");
        asm volatile("bar.sync 13, %0;" ::"r"(32 * nw + 32) : "memory");
    }
    if (warp == 0 || (warp > nw && warp != kWarmW)) return;
    const int g = lane >> 2, q = lane & 3, mi = lane >> 3, r8 = lane & 7;
    uint32_t A[12][4], B[12][4];
    {
        const int row = 4 * (r8 >> 1) + (r8 & 1) + 2 * (mi >> 1);
        const uint32_t base = stage + warp * 6144 + row * 384 + (((mi & 1) ^ (row & 7)) << 4);
#pragma unroll
        for (int ks = 0; ks < 12; ks++) ldsm4<false>(B[ks], (base ^ ((ks & 3) << 5)) + (ks >> 2) * 128);
    }
    if (vo) {
        const int c = r8 + 8 * (mi >> 1);
        const uint32_t base = stage + (((2 * c + (mi & 1)) ^ ((c >> 2) & 1)) << 4);
#pragma unroll
        for (int ks = 0; ks < 12; ks++) ldsm4<true>(A[ks], base + ks * 512);
    } else {
        const uint32_t base = stage + (r8 + 8 * (mi & 1)) * 384 + (((mi >> 1) ^ r8) << 4);
#pragma unroll
        for (int ks = 0; ks < 12; ks++) ldsm4<false>(A[ks], (base ^ ((ks & 3) << 5)) + (ks >> 2) * 128);
    }
    float c0[4] = {0.f, 0.f, 0.f, 0.f}, c1[4] = {0.f, 0.f, 0.f, 0.f}, c2[4] = {0.f, 0.f, 0.f, 0.f}, c3[4] = {0.f, 0.f, 0.f, 0.f};
#pragma unroll
    for (int ks = 0; ks < 12; ks += 2) {
        mma16816x2(c0, c1, A[ks], B[ks]);
        mma16816x2(c2, c3, A[ks + 1], B[ks + 1]);
    }
#pragma unroll
    for (int i = 0; i < 4; i++) { c0[i] += c2[i]; c1[i] += c3[i]; }
    const int ch = n0 + g;
    const int n = vo ? 32 * (ch >> 5) + 8 * ((ch >> 1) & 3) + 2 * ((ch >> 3) & 3) + (ch & 1) : ch;
    char* img = reinterpret_cast<char*>(sc->wfold) + (vo ? kWBytes : 0);
    asm volatile("{\n.reg .pred p;\nsetp.ne.u32 p, %6, %7;\n@p st.global.v2.u32 [%0], {%2, %3};\n@p st.global.v2.u32 [%1], {%4, %5};\n}\n"
                 ::"l"(img + fold_offset(n, k0, q)), "l"(img + fold_offset(n + (vo ? 2 : 8), k0, q)),
                   "r"(nonzero(pack_bf16(c0[0], c0[1]))), "r"(nonzero(pack_bf16(c1[0], c1[1]))), "r"(nonzero(pack_bf16(c0[2], c0[3]))), "r"(nonzero(pack_bf16(c1[2], c1[3]))),
                   "r"(warp), "n"(kWarmW) : "memory");
}

__device__ __forceinline__ bool bar_or(uint32_t id, uint32_t n, bool pred) {
    uint32_t r;
    asm volatile("{\n.reg .pred p, q;\nsetp.ne.u32 q, %3, 0;\nbar.red.or.pred p, %1, %2, q;\nselp.u32 %0, 1, 0, p;\n}\n"
                 : "=r"(r) : "r"(id), "r"(n), "r"((uint32_t)pred) : "memory");
    return r != 0;
}
__device__ __forceinline__ bool chunk_incomplete(uint32_t base) {
    const uint32_t t = tid_now(), r = (t >> 2) & 7;
    const uint32_t adr = base + (((t >> 5) & 3) * 48 + r) * 128 + (t & 3) * 32 + r * 4;
    uint32_t m = ~0u;
#pragma unroll
    for (int j = 0; j < 6; j++) {
        uint32_t v;
        asm volatile("ld.shared.u32 %0, [%1];" : "=r"(v) : "r"(adr + j * 1024) : "memory");
        m = min(m, v);
    }
    return m == 0;
}
__device__ __forceinline__ void load_image(uint32_t dst, const void* src, uint32_t bar) {
    mbar_expect_tx(bar, kWBytes);
#pragma unroll
    for (int c = 0; c < 3; c++) bulk_load(dst + c * 24576, reinterpret_cast<const char*>(src) + c * 24576, 24576, bar);
}
__device__ __forceinline__ void repair_image(uint32_t dst, const void* src, uint32_t bar, uint32_t par) {
    uint32_t tries = 0;
    bool bad;
    do {
        if (((tid_now() >> 5) & 3) == 0) {
            if (elect_one()) {
                asm volatile("fence.proxy.async;" ::: "memory");
                load_image(dst, src, bar);
            }
            __syncwarp();
        }
        mbar_wait(bar, par);
        par ^= 1;
        bad = chunk_incomplete(dst) | chunk_incomplete(dst + 24576) | chunk_incomplete(dst + 2 * 24576);
        if (++tries > (1u << 16)) __trap();
    } while (bar_or((tid_now() >> 7) + 1, 128, bad));
}
__device__ __forceinline__ void count_image(Scratch* sc) {
    asm volatile("red.relaxed.gpu.global.inc.u32 [%0], %1;" ::"l"(sc->cnt), "r"(3 * nctaid_now() - 1) : "memory");
}
__device__ __forceinline__ uint32_t ld_acquire(const uint32_t* p) {
    uint32_t v;
    asm volatile("ld.acquire.gpu.global.u32 %0, [%1];" : "=r"(v) : "l"(p) : "memory");
    return v;
}
__device__ __noinline__ void clear_images(Scratch* sc) {
    const uint32_t g = gridDim.x, t = threadIdx.x & 127;
    if (t == 0) {
        uint32_t spins = 0;
        while (ld_acquire(sc->cnt) < 2 * g) { if (++spins > (1u << 24)) __trap(); }
    }
    asm volatile("bar.sync %0, 128;" ::"r"((threadIdx.x >> 7) + 1) : "memory");
    for (uint32_t i = blockIdx.x * 64 + t; t < 64 && i < 2 * kWBytes / 16; i += g * 64) sc->wfold[i] = make_uint4(0, 0, 0, 0);
    if (t == 0) count_image(sc);
}
__device__ __forceinline__ void prefetch_x(const CUtensorMap* tm, int win) {
    const int wh = win >> 6, ww = win & 63;
    asm volatile("cp.async.bulk.prefetch.tensor.3d.L2.global.tile [%0, {%1, %2, %3}];"
                 ::"l"(tm), "r"(0), "r"(ww * 8), "r"(wh * 8) : "memory");
}
__device__ __forceinline__ void prefetch_x_chunk(const CUtensorMap* tm, int win, int chunk) {
    const int wh = win >> 6, ww = win & 63;
    asm volatile("cp.async.bulk.prefetch.tensor.4d.L2.global.tile [%0, {%1, %2, %3, %4}];"
                 ::"l"(tm), "r"(0), "r"(ww * 8), "r"(wh * 8), "r"(chunk) : "memory");
}

__device__ __forceinline__ void prefetch_for_ticket(const CUtensorMap* tmp, int t) {
    const int base = kNWG * (int)gridDim.x;
    auto lead = [&](int tt) {
        int down = max(((kNWin - base - tt) * PF_DOWN) >> 8, PF_MIN);
        return min(min((tt * PF_UP) >> 8, PF_LEAD), down);
    };
    const int hi = base + t + lead(t);
    int lo = max(base + t - 1 + lead(t - 1), base + t) + 1;
#pragma unroll 1
    for (; lo <= hi && lo < kNWin; lo++) prefetch_x(tmp, lo);
}

template <bool kFewSMs>
__global__ void __launch_bounds__(kThreads, 1)
swin_attn_kernel(const __nv_bfloat16* __restrict__ wqkv, const __nv_bfloat16* __restrict__ wo, __nv_bfloat16* __restrict__ out, Scratch* sc, uint32_t* tickets,
                 const __grid_constant__ CUtensorMap tmx, const __grid_constant__ CUtensorMap tmp, const __grid_constant__ CUtensorMap tmc) {
    extern __shared__ uint8_t smem_raw[];
    constexpr uint32_t sbase = kSmemBase;
    const uint32_t t_start = clock_now();
    asm volatile("{\n.reg .pred p, q;\n.reg .b32 i, j;\n.reg .b64 a, b;\nmad.lo.u32 i, %2, 14, %3;\nsetp.lt.u32 p, %3, 14;\nsetp.lt.and.u32 p, i, 1728, p;\n"
                 "mad.wide.u32 a, i, 128, %0;\n@p prefetch.global.L2 [a];\n"
                 "mad.lo.u32 j, %2, 5, %3;\nsetp.lt.u32 q, %3, 5;\nsetp.lt.and.u32 q, j, 576, q;\n"
                 "mad.wide.u32 b, j, 128, %1;\n@q prefetch.global.L2 [b];\n}\n" ::"l"(wqkv), "l"(wo), "r"(blockIdx.x), "r"(threadIdx.x) : "memory");
    if (smem_u32(smem_raw) != kSmemBase) __trap();
    const int tid = threadIdx.x, lane = tid & 31;
    const uint32_t warpu = __reduce_or_sync(0xffffffffu, (uint32_t)tid >> 5), wgu = warpu >> 2;
    const int warp = (int)warpu, wg = (int)wgu;
    const int G = gridDim.x;
    const uint32_t bar_full = sbase + kOffBar + 8 * wg;
    const uint32_t bar_w0 = sbase + kOffBar + 32, bar_w1 = bar_w0 + 8;
    int win = wg * G + blockIdx.x;

    if (warp > kWarmW) {
        if (warp == 10) {
            asm volatile("bar.sync 15, 64;" ::: "memory");
            asm volatile("bar.arrive 0, %0;" ::"n"(kThreads) : "memory");
            if (lane == 0) {
                asm volatile("prefetch.tensormap [%0];" ::"l"(&tmc) : "memory");
                asm volatile("prefetch.tensormap [%0];" ::"l"(&tmp) : "memory");
                asm volatile("prefetch.tensormap [%0];" ::"l"(&tmx) : "memory");
                const uint32_t due = (uint32_t)(blockIdx.x * TRK_S) / (uint32_t)G;
#pragma unroll 1
                for (int c = 0; c < 3; c++) {
                    while (clock_now() - t_start < TRK_T0 + (due + c * TRK_S) / 3) {}
                    if (c < 2) tma_load_x_chunk(sbase + kOffX + c * 8192, &tmc, bar_w0 + 16 * c, blockIdx.x, c);
                    else prefetch_x_chunk(&tmc, blockIdx.x, c);
                }
#pragma unroll 1
                for (int i = 1; i < kNWG; i++) {
                    while (clock_now() - t_start < TRK_T0 + due + i * TRK_S) {}
                    prefetch_x(&tmp, i * G + blockIdx.x);
                }
            }
            __syncwarp();
        } else if (warp == 11) {
            if (lane == 0) {
#pragma unroll
                for (int w = 0; w < kNWG; w++) mbar_init(sbase + kOffBar + 8 * w, 1);
                mbar_init(sbase + kOffBar + 24, 1);
                mbar_init(bar_w0, 1);
                mbar_init(bar_w1, 1);
                mbar_init(sbase + kOffBar + 48, 1);
                mbar_init(sbase + kOffBar + 56, 1);
                asm volatile("st.shared.v4.u32 [%0], {%1, %1, %1, %1};" ::"r"(sbase + kOffBar + 64), "r"(0) : "memory");
                asm volatile("st.shared.v2.u32 [%0], {%1, %1};" ::"r"(sbase + kOffBar + 80), "r"(0) : "memory");
                asm volatile("fence.mbarrier_init.release.cluster;" ::: "memory");
                asm volatile("mbarrier.arrive.shared::cta.b64 _, [%0];" ::"r"(sbase + kOffBar) : "memory");
            }
            __syncwarp();
            asm volatile("bar.arrive 15, 64;" ::: "memory");
            asm volatile("bar.arrive 0, %0;" ::"n"(kThreads) : "memory");
            if (elect_one()) {
                const char* img = reinterpret_cast<const char*>(sc->wfold);
#pragma unroll
                for (int c = 0; c < 3; c++) mbar_expect_tx(c == 0 ? bar_w0 : sbase + kOffBar + 40 + 8 * c, 24576 + 8192);
                mbar_expect_tx(sbase + kOffBar + 8, kXBytes);
                while (clock_now() - t_start < REQ_T) {}
#pragma unroll
                for (int c = 0; c < 3; c++) {
                    const uint32_t bar = c == 0 ? bar_w0 : sbase + kOffBar + 40 + 8 * c;
                    if (c == 2) tma_load_x_chunk(sbase + kOffX + c * 8192, &tmc, bar, blockIdx.x, c);
                    bulk_load(sbase + kOffWm + c * 24576, img + c * 24576, 24576, bar);
                }
                mbar_wait(bar_w0, 0);
                tma_load_x(sbase + kOffX + kXBytes, &tmx, sbase + kOffBar + 8, G + blockIdx.x);
            }
            __syncwarp();
        } else {
            asm volatile("bar.sync 0, %0;" ::"n"(kThreads) : "memory");
            if (warp == 9) {
                if (elect_one()) {
                    while (clock_now() - t_start < REQ_TV) {}
                    mbar_wait(sbase + kOffBar + 48, 0);
                    asm volatile("fence.proxy.async.shared::cta;" ::: "memory");
                    load_image(sbase + kOffWv, reinterpret_cast<const char*>(sc->wfold) + kWBytes, bar_w1);
                    mbar_expect_tx(sbase + kOffBar + 16, kXBytes);
                    tma_load_x(sbase + kOffX + 2 * kXBytes, &tmx, sbase + kOffBar + 16, 2 * G + blockIdx.x);
                }
                __syncwarp();
            }
        }
    } else {
        if constexpr (kFewSMs) {
#pragma unroll 1
            for (int j = blockIdx.x; j < kJobs; j += G) {
                fold_job(sc, wqkv, wo, j, warp, lane);
                asm volatile("bar.sync 14, %0;" ::"n"(32 * kWarmW + 32) : "memory");
            }
        } else {
            if (blockIdx.x < kJobs) fold_job(sc, wqkv, wo, blockIdx.x, warp, lane);
        }
        asm volatile("bar.sync 0, %0;" ::"n"(kThreads) : "memory");
    }
    if (wg == kNWG - 1) asm volatile("bar.sync 7, 128;" ::: "memory");
    if (wg == 1) {
        mbar_wait(bar_w0, 0);
        bool bad = chunk_incomplete(sbase + kOffWm);
        mbar_wait(sbase + kOffBar + 48, 0);
        bad |= chunk_incomplete(sbase + kOffWm + 24576);
        mbar_wait(sbase + kOffBar + 56, 0);
        bad |= chunk_incomplete(sbase + kOffWm + 2 * 24576);
        asm volatile("bar.arrive 8, 256;" ::: "memory");
        if (bar_or(11, 256, bad)) {
            repair_image(sbase + kOffWm, sc->wfold, sbase + kOffBar + 24, 0);
            asm volatile("bar.arrive 11, 256;" ::: "memory");
        }
        if (tid == 128) count_image(sc);
    } else if (wg == 2) {
        mbar_wait(bar_w1, 0);
        const bool bad = chunk_incomplete(sbase + kOffWv) | chunk_incomplete(sbase + kOffWv + 24576) | chunk_incomplete(sbase + kOffWv + 2 * 24576);
        if (bar_or(3, 128, bad)) {
            repair_image(sbase + kOffWv, reinterpret_cast<const char*>(sc->wfold) + kWBytes, bar_w1, 1);
        }
        if (tid == 256) count_image(sc);
    }

    constexpr uint32_t dWm = ((sbase + kOffWm) >> 4) | (1u << 16);
    constexpr uint32_t dWv = ((sbase + kOffWv) >> 4) | (1u << 16);
    const float cs = 0.07216878364870322f * 1.4426950408889634f;
    mbar_wait(bar_w0, 0);
    mbar_wait(bar_full, 0);

    uint4 hv[12];
    uint8_t* hptr;
    uint32_t phase = 0;
    float acc[96];
    uint32_t ticket = 0;
    {
        const uint32_t dX = desc_x(wg_uniform());
        if (wg != 0) ring_wait();
        wg_fence();
        Gemm1<0, 3>::run(acc, dX, dWm);
        mbar_wait(sbase + kOffBar + 48, 0);
        wg_fence();
        Gemm1<4, 7>::run(acc, dX, dWm);
        mbar_wait(sbase + kOffBar + 56, 0);
        wg_fence();
        Gemm1<8, 11>::run(acc, dX, dWm);
        wg_commit();
        if (wg != 0) asm volatile("bar.arrive 8, 256;" ::: "memory");
        ticket = draw_ticket(tickets);
        wg_wait0();
        if (wg == 0 && bar_or(11, 256, false)) {
            asm volatile("bar.sync 11, 256;" ::: "memory");
            wg_fence();
            Gemm1<0, 11>::run(acc, dX, dWm);
            wg_commit();
            wg_wait0();
        }
        __syncwarp();
    }

    while (true) {
        uint32_t fa[48];
        const uint32_t dX = desc_x(wg_uniform());
        fence_regs(acc);
#pragma unroll
        for (int i = 0; i < 48; i++) fa[i] = pack_bf16(acc[2 * i], acc[2 * i + 1]);

        float s[32];
        fence_regs(fa);
        wg_fence();
        ring_wait();
        Gemm2<11>::run(s, fa, dX);
        wg_commit();
        if constexpr (PASS2 == 11) ring_pass();
        if (((tid_now() >> 5) & 3) == 0) {
            if ((tid_now() & 31) == 0) {
                uint32_t nxt = kNWG * nctaid_now() + ticket;
                if (nxt >= kNWin) {
                    uint32_t p0, p1, p2, p3;
                    asm volatile("ld.shared.v4.u32 {%0, %1, %2, %3}, [%4];" : "=r"(p0), "=r"(p1), "=r"(p2), "=r"(p3) : "r"(sbase + kOffBar + 64) : "memory");
                    if ((p0 >= kNWin) + (p1 >= kNWin) + (p2 >= kNWin) == kNWG - 1) nxt = kLastOfCta;
                }
                asm volatile("st.shared.u32 [%0], %1;" ::"r"(sbase + kOffBar + 64 + 4 * (tid_now() >> 7)), "r"(nxt) : "memory");
            }
            __syncwarp();
            asm volatile("bar.arrive %0, 128;" ::"r"((tid_now() >> 7) + 4) : "memory");
        }
        wg_wait0();
        fence_regs(s);
        fence_regs(fa);

        uint32_t pa[16];
        {
            float a0[8], a1[8];
#pragma unroll
            for (int j = 0; j < 8; j++) { a0[j] = fmaxf(s[4 * j], s[4 * j + 1]); a1[j] = fmaxf(s[4 * j + 2], s[4 * j + 3]); }
#pragma unroll
            for (int d = 4; d > 0; d >>= 1)
#pragma unroll
                for (int j = 0; j < d; j++) { a0[j] = fmaxf(a0[j], a0[j + d]); a1[j] = fmaxf(a1[j], a1[j + d]); }
            float m0 = a0[0], m1 = a1[0];
            m0 = fmaxf(m0, __shfl_xor_sync(0xffffffffu, m0, 1));
            m1 = fmaxf(m1, __shfl_xor_sync(0xffffffffu, m1, 1));
            m0 = fmaxf(m0, __shfl_xor_sync(0xffffffffu, m0, 2));
            m1 = fmaxf(m1, __shfl_xor_sync(0xffffffffu, m1, 2));
            m0 *= cs; m1 *= cs;
            float l0 = 0.f, l1 = 0.f;
#pragma unroll
            for (int j = 0; j < 8; j++) {
                s[4 * j]     = ex2(fmaf(s[4 * j], cs, -m0));
                s[4 * j + 1] = ex2(fmaf(s[4 * j + 1], cs, -m0));
                s[4 * j + 2] = ex2(fmaf(s[4 * j + 2], cs, -m1));
                s[4 * j + 3] = ex2(fmaf(s[4 * j + 3], cs, -m1));
                l0 += s[4 * j] + s[4 * j + 1];
                l1 += s[4 * j + 2] + s[4 * j + 3];
            }
            l0 += __shfl_xor_sync(0xffffffffu, l0, 1);
            l1 += __shfl_xor_sync(0xffffffffu, l1, 1);
            l0 += __shfl_xor_sync(0xffffffffu, l0, 2);
            l1 += __shfl_xor_sync(0xffffffffu, l1, 2);
            const float r0 = rcp(l0), r1 = rcp(l1);
#pragma unroll
            for (int j = 0; j < 8; j++) {
                pa[2 * j]     = pack_bf16(s[4 * j] * r0, s[4 * j + 1] * r0);
                pa[2 * j + 1] = pack_bf16(s[4 * j + 2] * r1, s[4 * j + 3] * r1);
            }
        }

        const uint32_t dXt = desc_xt(wg_uniform());
        if (((tid_now() >> 5) & 3) != 0) asm volatile("bar.sync %0, 128;" ::"r"((tid_now() >> 7) + 4) : "memory");
        uint32_t pub;
        asm volatile("ld.shared.u32 %0, [%1];" : "=r"(pub) : "r"(sbase + kOffBar + 64 + 4 * (tid_now() >> 7)) : "memory");
        const int nxt = (int)__reduce_or_sync(0xffffffffu, pub);
        store_p_if(pa, nxt == (int)kLastOfCta);
        if (nxt == (int)kLastOfCta) {
            last_window(out, win);
            asm volatile("exit;");
            __builtin_unreachable();
        }
        fence_regs(pa);
        wg_fence();
        ring_wait();
        Gemm3<3>::run(acc, pa, dXt);
        wg_commit();
        if constexpr (PASS3 == 3) ring_pass();
        wg_wait0();
        fence_regs(acc);
        fence_regs(pa);

        if (((tid_now() >> 5) & 3) == 0) {
            asm volatile("bar.sync %0, 128;" ::"r"((tid_now() >> 7) + 1) : "memory");
            if (elect_one()) {
                const uint32_t wgl = tid_now() >> 7;
                const uint32_t bar = sbase + kOffBar + 8 * wgl;
                if (nxt < kNWin) {
                    mbar_expect_tx(bar, kXBytes);
                    tma_load_x(sbase + kOffX + wgl * kXBytes, &tmx, bar, nxt);
                    prefetch_for_ticket(&tmp, nxt - kNWG * (int)gridDim.x);
                }
            }
            __syncwarp();
        } else {
            asm volatile("bar.arrive %0, 128;" ::"r"((tid_now() >> 7) + 1) : "memory");
        }
#pragma unroll
        for (int i = 0; i < 48; i++) fa[i] = pack_bf16(acc[2 * i], acc[2 * i + 1]);

        asm volatile("st.volatile.shared.v4.b32 [%4], {%0, %1, %2, %3};"
                     :: "r"(fa[44]), "r"(fa[45]), "r"(fa[46]), "r"(fa[47]), "r"(sbase + kOffStash + tid_now() * 16) : "memory");
        fence_regs(fa);
        wg_fence();
        ring_wait();
        Gemm4<0, 1>::run(acc, fa, dWv);
        wg_commit();
        Gemm4<2, 10>::run(acc, fa, dWv);
        wg_commit();
        wg_wait1();
        uint32_t fl[4];
        asm volatile("ld.volatile.shared.v4.b32 {%0, %1, %2, %3}, [%4];"
                     : "=r"(fl[0]), "=r"(fl[1]), "=r"(fl[2]), "=r"(fl[3]) : "r"(sbase + kOffStash + tid_now() * 16) : "memory");
        wg_fence();
        wg192_rs<false, 0, koff(11, 24576)>(acc, fl, dWv);
        wg_commit();
        if (nxt >= kNWin) count_finished();
        ring_pass();
        hptr = out_address(out, win);
        win = nxt;
        const uint32_t dX1 = desc_x(wg_uniform());
        phase ^= 1;
        if (win < kNWin) mbar_wait(sbase + kOffBar + 8 * (tid_now() >> 7), phase);
        asm volatile("" : "+l"(hptr) :: "memory");
        wg_wait0();
        fence_regs(acc);
        fence_regs(fa);
        fence_regs(fl);

#pragma unroll
        for (int a = 0; a < 6; a++) {
            hv[2 * a].x     = pack_bf16(acc[16 * a + 0], acc[16 * a + 1]);
            hv[2 * a].y     = pack_bf16(acc[16 * a + 4], acc[16 * a + 5]);
            hv[2 * a].z     = pack_bf16(acc[16 * a + 8], acc[16 * a + 9]);
            hv[2 * a].w     = pack_bf16(acc[16 * a + 12], acc[16 * a + 13]);
            hv[2 * a + 1].x = pack_bf16(acc[16 * a + 2], acc[16 * a + 3]);
            hv[2 * a + 1].y = pack_bf16(acc[16 * a + 6], acc[16 * a + 7]);
            hv[2 * a + 1].z = pack_bf16(acc[16 * a + 10], acc[16 * a + 11]);
            hv[2 * a + 1].w = pack_bf16(acc[16 * a + 14], acc[16 * a + 15]);
        }
        if constexpr (slot_begin(0) > 0) {
            __syncwarp();
            store_slot<-1>(hv, hptr);
            __syncwarp();
        }
        if (win >= kNWin) break;
        wg_fence();
        ring_wait();
        Gemm1St<11>::run(acc, dX1, dWm, hv, hptr);
        ticket = draw_ticket(tickets);
        store_paced<slot_begin(12)>(hv, hptr, clock_now());
        wg_wait0();
    }
    {
        const uint32_t me = tid_now() >> 7, nx = me == kNWG - 1 ? 0 : me + 1;
        uint32_t nd, last;
        bool stored = false, first = false;
        while (true) {
            ring_wait();
            asm volatile("ld.volatile.shared.v2.u32 {%0, %1}, [%2];" : "=r"(nd), "=r"(last) : "r"(sbase + kOffBar + 80) : "memory");
            const bool all = nd == kNWG;
            if (!all || nx != last) ring_pass();
            if (!stored) { store_tail<slot_begin(0)>(hv, hptr, clock_now()); stored = true; first = nd == 1; }
            if (all) break;
        }
        if (first) clear_images(sc);
    }
}

typedef CUresult (*EncodeTiledFn)(CUtensorMap*, CUtensorMapDataType, cuuint32_t, void*, const cuuint64_t*,
                                  const cuuint64_t*, const cuuint32_t*, const cuuint32_t*, CUtensorMapInterleave,
                                  CUtensorMapSwizzle, CUtensorMapL2promotion, CUtensorMapFloatOOBfill);

}

extern "C" void kernel_launch(void* const* d_in, const int* in_sizes, int n_in, void* d_out, int out_size) {
    (void)in_sizes; (void)n_in; (void)out_size;
    const __nv_bfloat16* x    = (const __nv_bfloat16*)d_in[0];
    const __nv_bfloat16* wqkv = (const __nv_bfloat16*)d_in[1];
    const __nv_bfloat16* wo   = (const __nv_bfloat16*)d_in[2];

    static EncodeTiledFn encode = nullptr;
    static int num_sms = 0;
    static void* scratch = nullptr;
    if (!encode) {
        void* fn = nullptr;
        cudaDriverEntryPointQueryResult qr;
        cudaGetDriverEntryPoint("cuTensorMapEncodeTiled", &fn, cudaEnableDefault, &qr);
        encode = (EncodeTiledFn)fn;
        int dev = 0;
        cudaGetDevice(&dev);
        cudaDeviceGetAttribute(&num_sms, cudaDevAttrMultiProcessorCount, dev);
        cudaGetSymbolAddress(&scratch, g_scratch);
        cudaFuncSetAttribute(swin_attn_kernel<false>, cudaFuncAttributeMaxDynamicSharedMemorySize, kSmemBytes);
        cudaFuncSetAttribute(swin_attn_kernel<true>, cudaFuncAttributeMaxDynamicSharedMemorySize, kSmemBytes);
    }
    CUtensorMap tmx;
    const cuuint64_t gdim[4] = {64, (cuuint64_t)kHW, (cuuint64_t)kHW, 3};
    const cuuint64_t gstr[3] = {(cuuint64_t)kC * 2, (cuuint64_t)kHW * kC * 2, 128};
    const cuuint32_t box[4] = {64, 8, 8, 3};
    const cuuint32_t estr[4] = {1, 1, 1, 1};
    encode(&tmx, CU_TENSOR_MAP_DATA_TYPE_BFLOAT16, 4, (void*)x, gdim, gstr, box, estr, CU_TENSOR_MAP_INTERLEAVE_NONE,
           CU_TENSOR_MAP_SWIZZLE_128B, CU_TENSOR_MAP_L2_PROMOTION_NONE, CU_TENSOR_MAP_FLOAT_OOB_FILL_NONE);

    CUtensorMap tmp;
    const cuuint64_t pdim[3] = {(cuuint64_t)kC, (cuuint64_t)kHW, (cuuint64_t)kHW};
    const cuuint64_t pstr[2] = {(cuuint64_t)kC * 2, (cuuint64_t)kHW * kC * 2};
    const cuuint32_t pbox[3] = {(cuuint32_t)kC, 8, 8};
    encode(&tmp, CU_TENSOR_MAP_DATA_TYPE_BFLOAT16, 3, (void*)x, pdim, pstr, pbox, estr, CU_TENSOR_MAP_INTERLEAVE_NONE,
           CU_TENSOR_MAP_SWIZZLE_NONE, CU_TENSOR_MAP_L2_PROMOTION_NONE, CU_TENSOR_MAP_FLOAT_OOB_FILL_NONE);
    CUtensorMap tmc;
    const cuuint32_t boxc[4] = {64, 8, 8, 1};
    encode(&tmc, CU_TENSOR_MAP_DATA_TYPE_BFLOAT16, 4, (void*)x, gdim, gstr, boxc, estr, CU_TENSOR_MAP_INTERLEAVE_NONE,
           CU_TENSOR_MAP_SWIZZLE_128B, CU_TENSOR_MAP_L2_PROMOTION_NONE, CU_TENSOR_MAP_FLOAT_OOB_FILL_NONE);
    if (num_sms >= kJobs)
        swin_attn_kernel<false><<<num_sms, kThreads, kSmemBytes, cudaStreamPerThread>>>(wqkv, wo, (__nv_bfloat16*)d_out, (Scratch*)scratch, ((Scratch*)scratch)->ticket, tmx, tmp, tmc);
    else
        swin_attn_kernel<true><<<num_sms, kThreads, kSmemBytes, cudaStreamPerThread>>>(wqkv, wo, (__nv_bfloat16*)d_out, (Scratch*)scratch, ((Scratch*)scratch)->ticket, tmx, tmp, tmc);
}
```

```cpp
#include <cuda_runtime.h>
#include <cuda_bf16.h>
#include <cuda.h>
#include <stdint.h>

namespace {

constexpr int kC      = 192;
constexpr int kHW     = 512;
#define MAXWIN 4096
constexpr int kNWin   = MAXWIN;
constexpr int kXBytes = 64 * kC * 2;
constexpr int kWBytes = kC * kC * 2;
constexpr int kNWG    = 3;
constexpr int kThreads = kNWG * 128;
constexpr int kJobsM  = 72;
constexpr int kJobs   = 120;
constexpr int kWarmW  = 4;
#define PF_LEAD 400
#define PF_UP 170
#define PF_DOWN 34
#define PF_MIN 135
#define TRK_T0 400
#define TRK_S 1800
#define G11_DELAY 100
#define REQ_T 2650
#define REQ_TV 4000

constexpr int kOffWm  = 0;
constexpr int kOffWv  = kWBytes;
constexpr int kOffX   = 2 * kWBytes;
constexpr int kOffBar = kOffX + kNWG * kXBytes;
constexpr int kOffStash = kOffBar + 128;
constexpr int kOffProf = kOffStash + kThreads * 16;
constexpr int kSmemBytes = kOffProf;
constexpr uint32_t kSmemBase = 1024;

struct Scratch {
    uint4 wfold[2 * kWBytes / 16];
    uint32_t ticket[32];
    uint32_t cnt[32];
};
__device__ __align__(128) Scratch g_scratch;

__device__ __forceinline__ uint32_t smem_u32(const void* p) { return (uint32_t)__cvta_generic_to_shared(p); }

__device__ __forceinline__ void mbar_init(uint32_t bar, uint32_t count) {
    asm volatile("mbarrier.init.shared::cta.b64 [%0], %1;" ::"r"(bar), "r"(count) : "memory");
}
__device__ __forceinline__ void mbar_expect_tx(uint32_t bar, uint32_t bytes) {
    asm volatile("mbarrier.arrive.expect_tx.shared::cta.b64 _, [%0], %1;" ::"r"(bar), "r"(bytes) : "memory");
}
__device__ __forceinline__ void mbar_wait(uint32_t bar, uint32_t parity) {
    uint32_t ok;
    uint32_t spins = 0;
    do {
        asm volatile("{\n.reg .pred p;\n"
                     "mbarrier.try_wait.parity.shared::cta.b64 p, [%1], %2;\n"
                     "selp.b32 %0, 1, 0, p;\n}\n"
                     : "=r"(ok) : "r"(bar), "r"(parity) : "memory");
        if (++spins > (1u << 26)) __trap();
    } while (!ok);
}
__device__ __forceinline__ uint32_t tid_now() {
    uint32_t t;
    asm volatile("mov.u32 %0, %%tid.x;" : "=r"(t));
    return t;
}
__device__ __forceinline__ uint32_t nctaid_now() {
    uint32_t t;
    asm volatile("mov.u32 %0, %%nctaid.x;" : "=r"(t));
    return t;
}
__device__ __forceinline__ bool elect_one() {
    uint32_t pred;
    asm volatile("{\n.reg .pred p;\nelect.sync _|p, 0xffffffff;\nselp.b32 %0, 1, 0, p;\n}\n" : "=r"(pred));
    return pred != 0;
}
#define PASS1 11
#define PASS2 5
#define PASS3 3
__device__ __forceinline__ void ring_wait() {
    asm volatile("bar.sync %0, 256;" ::"r"((tid_now() >> 7) + 8) : "memory");
}
__device__ __forceinline__ void ring_pass() {
    const uint32_t w = tid_now() >> 7;
    asm volatile("bar.arrive %0, 256;" ::"r"(w == kNWG - 1 ? 8u : w + 9u) : "memory");
}
constexpr uint32_t kLastOfCta = 0x40000000u;
__device__ __forceinline__ uint32_t wg_uniform() { return __reduce_or_sync(0xffffffffu, tid_now() >> 7); }
__device__ __forceinline__ uint32_t desc_x(uint32_t w) { return (((kSmemBase + kOffX) >> 4) | (1u << 16)) + w * (kXBytes >> 4); }
__device__ __forceinline__ uint32_t desc_xt(uint32_t w) { return (((kSmemBase + kOffX) >> 4) | ((8192u >> 4) << 16)) + w * (kXBytes >> 4); }
__device__ __forceinline__ void tma_load_x(uint32_t dst, const CUtensorMap* tm, uint32_t bar, int win) {
    const int wh = win >> 6, ww = win & 63;
    asm volatile("cp.async.bulk.tensor.4d.shared::cluster.global.mbarrier::complete_tx::bytes"
                 " [%0], [%1, {%3, %4, %5, %6}], [%2];"
                 ::"r"(dst), "l"(tm), "r"(bar), "r"(0), "r"(ww * 8), "r"(wh * 8), "r"(0) : "memory");
}
__device__ __forceinline__ void tma_load_x_chunk(uint32_t dst, const CUtensorMap* tm, uint32_t bar, int win, int chunk) {
    const int wh = win >> 6, ww = win & 63;
    asm volatile("cp.async.bulk.tensor.4d.shared::cluster.global.mbarrier::complete_tx::bytes"
                 " [%0], [%1, {%3, %4, %5, %6}], [%2];"
                 ::"r"(dst), "l"(tm), "r"(bar), "r"(0), "r"(ww * 8), "r"(wh * 8), "r"(chunk) : "memory");
}
__device__ __forceinline__ void bulk_load(uint32_t dst, const void* src, uint32_t bytes, uint32_t bar) {
    asm volatile("cp.async.bulk.shared::cluster.global.mbarrier::complete_tx::bytes [%0], [%1], %2, [%3];"
                 ::"r"(dst), "l"(src), "r"(bytes), "r"(bar) : "memory");
}

__device__ __forceinline__ void stg128(void* p, uint4 v) {
    asm volatile("st.global.v4.b32 [%0], {%1, %2, %3, %4};" ::"l"(p), "r"(v.x), "r"(v.y), "r"(v.z), "r"(v.w) : "memory");
}
__device__ __forceinline__ void wg_fence()  { asm volatile("wgmma.fence.sync.aligned;" ::: "memory"); }
__device__ __forceinline__ void wg_commit() { asm volatile("wgmma.commit_group.sync.aligned;" ::: "memory"); }
__device__ __forceinline__ void wg_wait0()  { asm volatile("wgmma.wait_group.sync.aligned 0;" ::: "memory"); }
__device__ __forceinline__ void wg_wait1()  { asm volatile("wgmma.wait_group.sync.aligned 1;" ::: "memory"); }
__device__ __forceinline__ void wg_wait2()  { asm volatile("wgmma.wait_group.sync.aligned 2;" ::: "memory"); }

template <int N> __device__ __forceinline__ void fence_regs(float (&d)[N]) {
#pragma unroll
    for (int i = 0; i < N; i++) asm volatile("" : "+f"(d[i])::"memory");
}
template <int N> __device__ __forceinline__ void fence_regs(uint32_t (&d)[N]) {
#pragma unroll
    for (int i = 0; i < N; i++) asm volatile("" : "+r"(d[i])::"memory");
}

#define ACC8(c, d, i) c(d[i]), c(d[i + 1]), c(d[i + 2]), c(d[i + 3]), c(d[i + 4]), c(d[i + 5]), c(d[i + 6]), c(d[i + 7])
#define ACC32(c, d) ACC8(c, d, 0), ACC8(c, d, 8), ACC8(c, d, 16), ACC8(c, d, 24)
#define ACC96(c, d) ACC32(c, d), ACC8(c, d, 32), ACC8(c, d, 40), ACC8(c, d, 48), ACC8(c, d, 56), \
                    ACC8(c, d, 64), ACC8(c, d, 72), ACC8(c, d, 80), ACC8(c, d, 88)
#define C_IO(x) "+f"(x)
#define C_O(x) "=f"(x)
#define REGS32 "{%0, %1, %2, %3, %4, %5, %6, %7, %8, %9, %10, %11, %12, %13, %14, %15, " \
               "%16, %17, %18, %19, %20, %21, %22, %23, %24, %25, %26, %27, %28, %29, %30, %31}"
#define REGS96 "{%0, %1, %2, %3, %4, %5, %6, %7, %8, %9, %10, %11, %12, %13, %14, %15, " \
               "%16, %17, %18, %19, %20, %21, %22, %23, %24, %25, %26, %27, %28, %29, %30, %31, " \
               "%32, %33, %34, %35, %36, %37, %38, %39, %40, %41, %42, %43, %44, %45, %46, %47, " \
               "%48, %49, %50, %51, %52, %53, %54, %55, %56, %57, %58, %59, %60, %61, %62, %63, " \
               "%64, %65, %66, %67, %68, %69, %70, %71, %72, %73, %74, %75, %76, %77, %78, %79, " \
               "%80, %81, %82, %83, %84, %85, %86, %87, %88, %89, %90, %91, %92, %93, %94, %95}"

#define DESC_HI "0x40000040"
#define MK_DESC(name, lo, off) "add.u32 t, " lo ", " off ";\nmov.b64 " name ", {t, " DESC_HI "};\n"

template <bool First, int OA, int OB> __device__ __forceinline__ void wg192_ss(float (&d)[96], uint32_t la, uint32_t lb) {
    if constexpr (First)
        asm volatile("{\n.reg .pred p;\n.reg .b32 t;\n.reg .b64 da, db;\nsetp.ne.b32 p, 0, 0;\n"
                     MK_DESC("da", "%96", "%98") MK_DESC("db", "%97", "%99")
                     "wgmma.mma_async.sync.aligned.m64n192k16.f32.bf16.bf16 " REGS96 ", da, db, p, 1, 1, 0, 0;\n}\n"
                     : ACC96(C_O, d) : "r"(la), "r"(lb), "n"(OA), "n"(OB));
    else
        asm volatile("{\n.reg .pred p;\n.reg .b32 t;\n.reg .b64 da, db;\nsetp.ne.b32 p, 1, 0;\n"
                     MK_DESC("da", "%96", "%98") MK_DESC("db", "%97", "%99")
                     "wgmma.mma_async.sync.aligned.m64n192k16.f32.bf16.bf16 " REGS96 ", da, db, p, 1, 1, 0, 0;\n}\n"
                     : ACC96(C_IO, d) : "r"(la), "r"(lb), "n"(OA), "n"(OB));
}
template <bool First, int TB, int OB> __device__ __forceinline__ void wg192_rs(float (&d)[96], const uint32_t* a, uint32_t lb) {
    if constexpr (First)
        asm volatile("{\n.reg .pred p;\n.reg .b32 t;\n.reg .b64 db;\nsetp.ne.b32 p, 0, 0;\n"
                     MK_DESC("db", "%100", "%102")
                     "wgmma.mma_async.sync.aligned.m64n192k16.f32.bf16.bf16 " REGS96 ", {%96, %97, %98, %99}, db, p, 1, 1, %101;\n}\n"
                     : ACC96(C_O, d) : "r"(a[0]), "r"(a[1]), "r"(a[2]), "r"(a[3]), "r"(lb), "n"(TB), "n"(OB));
    else
        asm volatile("{\n.reg .pred p;\n.reg .b32 t;\n.reg .b64 db;\nsetp.ne.b32 p, 1, 0;\n"
                     MK_DESC("db", "%100", "%102")
                     "wgmma.mma_async.sync.aligned.m64n192k16.f32.bf16.bf16 " REGS96 ", {%96, %97, %98, %99}, db, p, 1, 1, %101;\n}\n"
                     : ACC96(C_IO, d) : "r"(a[0]), "r"(a[1]), "r"(a[2]), "r"(a[3]), "r"(lb), "n"(TB), "n"(OB));
}
template <bool First, int OB> __device__ __forceinline__ void wg64_rs(float (&d)[32], const uint32_t* a, uint32_t lb) {
    if constexpr (First)
        asm volatile("{\n.reg .pred p;\n.reg .b32 t;\n.reg .b64 db;\nsetp.ne.b32 p, 0, 0;\n"
                     MK_DESC("db", "%36", "%37")
                     "wgmma.mma_async.sync.aligned.m64n64k16.f32.bf16.bf16 " REGS32 ", {%32, %33, %34, %35}, db, p, 1, 1, 0;\n}\n"
                     : ACC32(C_O, d) : "r"(a[0]), "r"(a[1]), "r"(a[2]), "r"(a[3]), "r"(lb), "n"(OB));
    else
        asm volatile("{\n.reg .pred p;\n.reg .b32 t;\n.reg .b64 db;\nsetp.ne.b32 p, 1, 0;\n"
                     MK_DESC("db", "%36", "%37")
                     "wgmma.mma_async.sync.aligned.m64n64k16.f32.bf16.bf16 " REGS32 ", {%32, %33, %34, %35}, db, p, 1, 1, 0;\n}\n"
                     : ACC32(C_IO, d) : "r"(a[0]), "r"(a[1]), "r"(a[2]), "r"(a[3]), "r"(lb), "n"(OB));
}
template <bool First, int OA, int OB> __device__ __forceinline__ void wg64_ss(float (&d)[32], uint32_t la, uint32_t lb) {
    if constexpr (First)
        asm volatile("{\n.reg .pred p;\n.reg .b32 t;\n.reg .b64 da, db;\nsetp.ne.b32 p, 0, 0;\n"
                     MK_DESC("da", "%32", "%34") MK_DESC("db", "%33", "%35")
                     "wgmma.mma_async.sync.aligned.m64n64k16.f32.bf16.bf16 " REGS32 ", da, db, p, 1, 1, 0, 1;\n}\n"
                     : ACC32(C_O, d) : "r"(la), "r"(lb), "n"(OA), "n"(OB));
    else
        asm volatile("{\n.reg .pred p;\n.reg .b32 t;\n.reg .b64 da, db;\nsetp.ne.b32 p, 1, 0;\n"
                     MK_DESC("da", "%32", "%34") MK_DESC("db", "%33", "%35")
                     "wgmma.mma_async.sync.aligned.m64n64k16.f32.bf16.bf16 " REGS32 ", da, db, p, 1, 1, 0, 1;\n}\n"
                     : ACC32(C_IO, d) : "r"(la), "r"(lb), "n"(OA), "n"(OB));
}
__host__ __device__ constexpr int koff(int kk, int chunk) { return ((kk >> 2) * chunk + (kk & 3) * 32) >> 4; }

#define ST_SLOTS 0x2000000000001ull
__host__ __device__ constexpr int slot_begin(int i) {
    int b = 0;
    for (int k = -1; k < i; k++) b += (int)((ST_SLOTS >> (4 * (11 - k))) & 15);
    return b;
}
#define PACE_DT 160
#define SPIN_NS 50
template <int J> __device__ __forceinline__ void store_one(const uint4 (&h)[12], uint8_t* hptr) {
    constexpr int r = J / 6, a = J % 6;
    stg128(hptr + r * (kHW * kC * 2) + a * 64, h[2 * a + r]);
}
template <int J, int E> __device__ __forceinline__ void store_range(uint4 (&h)[12], uint8_t* hptr) {
    if constexpr (J < E) {
        store_one<J>(h, hptr);
        store_range<J + 1, E>(h, hptr);
    }
}
template <int I> __device__ __forceinline__ void store_slot(uint4 (&h)[12], uint8_t* hptr) {
    store_range<slot_begin(I), slot_begin(I + 1)>(h, hptr);
}
__device__ __forceinline__ uint32_t clock_now() {
    uint32_t t;
    asm volatile("mov.u32 %0, %%clock;" : "=r"(t));
    return t;
}
template <int J> __device__ __forceinline__ void store_paced(uint4 (&h)[12], uint8_t* hptr, uint32_t t0) {
    if constexpr (J < 12) {
        while (clock_now() - t0 < (uint32_t)((J - slot_begin(12) + 1) * PACE_DT)) asm volatile("nanosleep.u32 %0;" ::"n"(SPIN_NS));
        store_one<J>(h, hptr);
        store_paced<J + 1>(h, hptr, t0);
    }
}
#define TAIL_DT 70
#define TAIL_PASS 6
template <int J, int E> __device__ __forceinline__ void store_tail(uint4 (&h)[12], uint8_t* hptr, uint32_t t0) {
    if constexpr (J < E) {
        if constexpr (J > slot_begin(0)) { while (clock_now() - t0 < (uint32_t)((J - slot_begin(0)) * TAIL_DT)) {} }
        store_one<J>(h, hptr);
        store_tail<J + 1, E>(h, hptr, t0);
    }
}
template <int K> struct Gemm1St {
    static __device__ __forceinline__ void run(float (&d)[96], uint32_t lx, uint32_t lw, uint4 (&h)[12], uint8_t* hptr) {
        if constexpr (K > 0) Gemm1St<K - 1>::run(d, lx, lw, h, hptr);
        wg192_ss<K == 0, koff(K, 8192), koff(K, 24576)>(d, lx, lw);
        if constexpr (K == 11) wg_commit();
        if constexpr (K == PASS1) ring_pass();
        if constexpr (slot_begin(K + 1) > slot_begin(K)) {
            __syncwarp();
            store_slot<K>(h, hptr);
            __syncwarp();
        }
    }
};
template <int K0, int K> struct Gemm1 {
    static __device__ __forceinline__ void run(float (&d)[96], uint32_t lx, uint32_t lw) {
        if constexpr (K > K0) Gemm1<K0, K - 1>::run(d, lx, lw);
        wg192_ss<K == 0, koff(K, 8192), koff(K, 24576)>(d, lx, lw);
    }
};
__device__ __forceinline__ uint32_t draw_ticket(uint32_t* counter) {
    uint32_t ticket = 0;
    asm volatile("{\n.reg .pred p;\nsetp.eq.u32 p, %2, 0;\n@p atom.relaxed.gpu.global.inc.u32 %0, [%1], %3;\n}\n"
                 : "+r"(ticket) : "l"(counter), "r"(tid_now() & 127), "n"(kNWin - 1) : "memory");
    return ticket;
}
template <int KK> struct Gemm2 { static __device__ __forceinline__ void run(float (&d)[32], const uint32_t* a, uint32_t lx) {
    Gemm2<KK - 1>::run(d, a, lx); wg64_rs<KK == 0, koff(KK, 8192)>(d, a + 4 * KK, lx);
    if constexpr (KK == PASS2 && KK < 11) ring_pass(); } };
template <> struct Gemm2<-1> { static __device__ __forceinline__ void run(float (&)[32], const uint32_t*, uint32_t) {} };
template <int KK> struct Gemm3 { static __device__ __forceinline__ void run(float (&d)[96], const uint32_t* a, uint32_t lxt) {
    Gemm3<KK - 1>::run(d, a, lxt); wg192_rs<KK == 0, 1, KK * (2048 >> 4)>(d, a + 4 * KK, lxt);
    if constexpr (KK == PASS3 && KK < 3) ring_pass(); } };
template <> struct Gemm3<-1> { static __device__ __forceinline__ void run(float (&)[96], const uint32_t*, uint32_t) {} };
template <int K0, int KK> struct Gemm4 { static __device__ __forceinline__ void run(float (&d)[96], const uint32_t* a, uint32_t lw) {
    if constexpr (KK > K0) Gemm4<K0, KK - 1>::run(d, a, lw);
    wg192_rs<KK == 0, 0, koff(KK, 24576)>(d, a + 4 * KK, lw); } };

template <int J, int KK> struct Gemm3s { static __device__ __forceinline__ void run(float (&d)[32], uint32_t lp, uint32_t lxt) {
    if constexpr (KK > 0) Gemm3s<J, KK - 1>::run(d, lp, lxt);
    wg64_ss<KK == 0, KK * 2, (J * 8192 + KK * 2048) / 16>(d, lp, lxt); } };
template <int J, int K0, int KK> struct Gemm4s { static __device__ __forceinline__ void run(float (&d)[32], const uint32_t* a, uint32_t lw) {
    if constexpr (KK > K0) Gemm4s<J, K0, KK - 1>::run(d, a, lw);
    wg64_rs<KK == 0, koff(KK, 24576) + J * (8192 / 16)>(d, a + 4 * KK, lw); } };

__device__ __forceinline__ uint32_t pack_bf16(float lo, float hi) {
    uint32_t r;
    asm("cvt.rn.bf16x2.f32 %0, %1, %2;" : "=r"(r) : "f"(hi), "f"(lo));
    return r;
}
__device__ __forceinline__ float ex2(float x) {
    float r;
    asm("ex2.approx.ftz.f32 %0, %1;" : "=f"(r) : "f"(x));
    return r;
}
__device__ __forceinline__ float rcp(float x) {
    float r;
    asm("rcp.approx.ftz.f32 %0, %1;" : "=f"(r) : "f"(x));
    return r;
}

__device__ __forceinline__ void pack_slice(uint32_t* a, float (&d)[32]) {
    fence_regs(d);
#pragma unroll
    for (int i = 0; i < 16; i++) a[i] = pack_bf16(d[2 * i], d[2 * i + 1]);
#pragma unroll
    for (int i = 0; i < 16; i++) asm volatile("" : "+r"(a[i])::"memory");
}
template <int J> __device__ __forceinline__ void store_slice(float (&d)[32], uint8_t* hptr) {
    fence_regs(d);
#pragma unroll
    for (int r = 0; r < 2; r++) {
        uint4 h[2];
#pragma unroll
        for (int a = 0; a < 2; a++) {
            const int o = 16 * a + 2 * r;
            h[a] = make_uint4(pack_bf16(d[o], d[o + 1]), pack_bf16(d[o + 4], d[o + 5]), pack_bf16(d[o + 8], d[o + 9]), pack_bf16(d[o + 12], d[o + 13]));
        }
        stg128(hptr + r * (kHW * kC * 2) + J * 128, h[0]);
        stg128(hptr + r * (kHW * kC * 2) + J * 128 + 64, h[1]);
    }
    __syncwarp();
}
__device__ __forceinline__ uint8_t* out_address(__nv_bfloat16* out, int win) {
    const uint32_t ln = tid_now() & 31;
    return reinterpret_cast<uint8_t*>(out) + (uint32_t)((win >> 6) * 8 * kHW + (win & 63) * 8 + 2 * ((tid_now() >> 5) & 3) * kHW + (ln >> 2)) * (uint32_t)(kC * 2) + (ln & 3) * 16;
}
__device__ __forceinline__ void count_finished() {
    if (((tid_now() >> 5) & 3) == 0) {
        if (elect_one()) {
            uint32_t nd;
            asm volatile("ld.shared.u32 %0, [%1];" : "=r"(nd) : "r"(kSmemBase + kOffBar + 80) : "memory");
            asm volatile("st.shared.v2.u32 [%0], {%1, %2};" ::"r"(kSmemBase + kOffBar + 80), "r"(nd + 1), "r"(tid_now() >> 7) : "memory");
        }
        __syncwarp();
    }
}
__device__ __forceinline__ void store_p_if(const uint32_t (&pa)[16], bool cond) {
    const uint32_t t = tid_now(), w = t >> 7, row = ((t >> 1) & 48) + (t & 15);
    const uint32_t adr = kSmemBase + kOffX + (w == kNWG - 1 ? 0 : w + 1) * kXBytes + row * 128 + ((((t >> 4) & 1) ^ (t & 7)) << 4);
#pragma unroll
    for (int i = 0; i < 4; i++)
        asm volatile("{\n.reg .pred p;\nsetp.ne.u32 p, %5, 0;\n@p stmatrix.sync.aligned.m8n8.x4.shared.b16 [%4], {%0, %1, %2, %3};\n}\n"
                     :: "r"(pa[4 * i]), "r"(pa[4 * i + 1]), "r"(pa[4 * i + 2]), "r"(pa[4 * i + 3]), "r"(adr ^ (i << 5)), "r"((uint32_t)cond) : "memory");
}
__device__ __forceinline__ void last_window(__nv_bfloat16* out, int win) {
    constexpr uint32_t dWv = ((kSmemBase + kOffWv) >> 4) | (1u << 16);
    asm volatile("fence.proxy.async.shared::cta;" ::: "memory");
    const uint32_t w = wg_uniform();
    const uint32_t dXt = desc_xt(w);
    const uint32_t dP = desc_x(w == kNWG - 1 ? 0 : w + 1);
    float u0[32], u1[32], u2[32];
    uint32_t fa[48];
    uint8_t* hptr = out_address(out, win);
    asm volatile("" : "+l"(hptr) :: "memory");
    ring_wait();
    wg_fence();
    Gemm3s<0, 3>::run(u0, dP, dXt); wg_commit();
    Gemm3s<1, 3>::run(u1, dP, dXt); wg_commit();
    Gemm3s<2, 3>::run(u2, dP, dXt); wg_commit();
    count_finished();
    ring_pass();
    wg_wait2();
    pack_slice(fa, u0);
    wg_wait1();
    pack_slice(fa + 16, u1);
    wg_fence();
    Gemm4s<0, 0, 7>::run(u0, fa, dWv); wg_commit();
    wg_wait1();
    pack_slice(fa + 32, u2);
    wg_fence();
    Gemm4s<0, 8, 11>::run(u0, fa, dWv); wg_commit();
    Gemm4s<1, 0, 5>::run(u1, fa, dWv); wg_commit();
    wg_wait1();
    store_slice<0>(u0, hptr);
    wg_fence();
    Gemm4s<1, 6, 11>::run(u1, fa, dWv); wg_commit();
    Gemm4s<2, 0, 5>::run(u2, fa, dWv); wg_commit();
    wg_wait1();
    store_slice<1>(u1, hptr);
    wg_fence();
    Gemm4s<2, 6, 11>::run(u2, fa, dWv); wg_commit();
    wg_wait0();
    fence_regs(fa);
    store_slice<2>(u2, hptr);
}

__device__ __forceinline__ int fold_offset(int n, int k0, int q) {
    const int u = ((k0 & 63) >> 3) + (q >> 1);
    return (k0 >> 6) * 24576 + (q & 1) * 8 + n * 128 + ((u ^ (n & 7)) << 4);
}
__device__ __forceinline__ void mma16816x2(float (&c)[4], float (&d)[4], const uint32_t (&a)[4], const uint32_t (&b)[4]) {
    asm volatile("mma.sync.aligned.m16n8k16.row.col.f32.bf16.bf16.f32 {%0,%1,%2,%3}, {%8,%9,%10,%11}, {%12,%13}, {%0,%1,%2,%3};\n"
                 "mma.sync.aligned.m16n8k16.row.col.f32.bf16.bf16.f32 {%4,%5,%6,%7}, {%8,%9,%10,%11}, {%14,%15}, {%4,%5,%6,%7};"
                 : "+f"(c[0]), "+f"(c[1]), "+f"(c[2]), "+f"(c[3]), "+f"(d[0]), "+f"(d[1]), "+f"(d[2]), "+f"(d[3])
                 : "r"(a[0]), "r"(a[1]), "r"(a[2]), "r"(a[3]), "r"(b[0]), "r"(b[1]), "r"(b[2]), "r"(b[3]));
}
__device__ __forceinline__ void cp_async16(uint32_t dst, const void* src) {
    asm volatile("cp.async.cg.shared.global [%0], [%1], 16;" ::"r"(dst), "l"(src) : "memory");
}
template <bool kTrans> __device__ __forceinline__ void ldsm4(uint32_t (&r)[4], uint32_t addr) {
    if constexpr (kTrans)
        asm volatile("ldmatrix.sync.aligned.m8n8.x4.trans.shared.b16 {%0, %1, %2, %3}, [%4];" : "=r"(r[0]), "=r"(r[1]), "=r"(r[2]), "=r"(r[3]) : "r"(addr) : "memory");
    else
        asm volatile("ldmatrix.sync.aligned.m8n8.x4.shared.b16 {%0, %1, %2, %3}, [%4];" : "=r"(r[0]), "=r"(r[1]), "=r"(r[2]), "=r"(r[3]) : "r"(addr) : "memory");
}
__device__ __forceinline__ uint32_t nonzero(uint32_t w) { return w ? w : 0x80000000u; }
__device__ __forceinline__ void fold_job(Scratch* sc, const __nv_bfloat16* __restrict__ wqkv, const __nv_bfloat16* __restrict__ wo,
                                         int job, int warp, int lane) {
    const bool vo = job >= kJobsM;
    const int nw = vo ? 3 : 2, tile0 = vo ? 3 * (job - kJobsM) : 2 * job;
    const int n0 = (tile0 / 12) * 16, k0 = (tile0 % 12 + max(warp, 1) - 1) * 16;
    const uint32_t stage = kSmemBase + kOffWv;
    if (warp <= nw) {
        if (vo && warp == 0) {
            const char* src = reinterpret_cast<const char*>(wo + (lane >> 1) * kC + n0 + (lane & 1) * 8);
            const uint32_t dst = stage + ((lane ^ ((lane >> 3) & 1)) << 4);
#pragma unroll
            for (int i = 0; i < 12; i++) cp_async16(dst + i * 512, src + i * 16 * kC * 2);
        } else {
            const int row0 = warp == 0 ? n0 : k0, col0 = warp == 0 ? kC : vo ? 2 * kC : 0;
            const char* src = reinterpret_cast<const char*>(wqkv + (row0 + (lane >> 3)) * (3 * kC) + col0 + (lane & 7) * 8);
            const uint32_t dst = stage + warp * 6144 + (lane >> 3) * 384 + (((lane & 7) ^ (lane >> 3)) << 4);
#pragma unroll
            for (int i = 0; i < 12; i++) cp_async16((dst ^ (((i / 3) & 1) << 6)) + (i / 3) * 1536 + (i % 3) * 128, src + (i / 3) * 4 * 3 * kC * 2 + (i % 3) * 128);
        }
        asm volatile("cp.async.wait_all;" ::: "memory");
        asm volatile("bar.sync 13, %0;" ::"r"(32 * nw + 32) : "memory");
    }
    if (warp == 0 || (warp > nw && warp != kWarmW)) return;
    const int g = lane >> 2, q = lane & 3, mi = lane >> 3, r8 = lane & 7;
    uint32_t A[12][4], B[12][4];
    {
        const int row = 4 * (r8 >> 1) + (r8 & 1) + 2 * (mi >> 1);
        const uint32_t base = stage + warp * 6144 + row * 384 + (((mi & 1) ^ (row & 7)) << 4);
#pragma unroll
        for (int ks = 0; ks < 12; ks++) ldsm4<false>(B[ks], (base ^ ((ks & 3) << 5)) + (ks >> 2) * 128);
    }
    if (vo) {
        const int c = r8 + 8 * (mi >> 1);
        const uint32_t base = stage + (((2 * c + (mi & 1)) ^ ((c >> 2) & 1)) << 4);
#pragma unroll
        for (int ks = 0; ks < 12; ks++) ldsm4<true>(A[ks], base + ks * 512);
    } else {
        const uint32_t base = stage + (r8 + 8 * (mi & 1)) * 384 + (((mi >> 1) ^ r8) << 4);
#pragma unroll
        for (int ks = 0; ks < 12; ks++) ldsm4<false>(A[ks], (base ^ ((ks & 3) << 5)) + (ks >> 2) * 128);
    }
    float c0[4] = {0.f, 0.f, 0.f, 0.f}, c1[4] = {0.f, 0.f, 0.f, 0.f}, c2[4] = {0.f, 0.f, 0.f, 0.f}, c3[4] = {0.f, 0.f, 0.f, 0.f};
#pragma unroll
    for (int ks = 0; ks < 12; ks += 2) {
        mma16816x2(c0, c1, A[ks], B[ks]);
        mma16816x2(c2, c3, A[ks + 1], B[ks + 1]);
    }
#pragma unroll
    for (int i = 0; i < 4; i++) { c0[i] += c2[i]; c1[i] += c3[i]; }
    const int ch = n0 + g;
    const int n = vo ? 32 * (ch >> 5) + 8 * ((ch >> 1) & 3) + 2 * ((ch >> 3) & 3) + (ch & 1) : ch;
    char* img = reinterpret_cast<char*>(sc->wfold) + (vo ? kWBytes : 0);
    asm volatile("{\n.reg .pred p;\nsetp.ne.u32 p, %6, %7;\n@p st.global.v2.u32 [%0], {%2, %3};\n@p st.global.v2.u32 [%1], {%4, %5};\n}\n"
                 ::"l"(img + fold_offset(n, k0, q)), "l"(img + fold_offset(n + (vo ? 2 : 8), k0, q)),
                   "r"(nonzero(pack_bf16(c0[0], c0[1]))), "r"(nonzero(pack_bf16(c1[0], c1[1]))), "r"(nonzero(pack_bf16(c0[2], c0[3]))), "r"(nonzero(pack_bf16(c1[2], c1[3]))),
                   "r"(warp), "n"(kWarmW) : "memory");
}

__device__ __forceinline__ bool bar_or(uint32_t id, uint32_t n, bool pred) {
    uint32_t r;
    asm volatile("{\n.reg .pred p, q;\nsetp.ne.u32 q, %3, 0;\nbar.red.or.pred p, %1, %2, q;\nselp.u32 %0, 1, 0, p;\n}\n"
                 : "=r"(r) : "r"(id), "r"(n), "r"((uint32_t)pred) : "memory");
    return r != 0;
}
__device__ __forceinline__ bool chunk_incomplete(uint32_t base) {
    const uint32_t t = tid_now(), r = (t >> 2) & 7;
    const uint32_t adr = base + (((t >> 5) & 3) * 48 + r) * 128 + (t & 3) * 32 + r * 4;
    uint32_t m = ~0u;
#pragma unroll
    for (int j = 0; j < 6; j++) {
        uint32_t v;
        asm volatile("ld.shared.u32 %0, [%1];" : "=r"(v) : "r"(adr + j * 1024) : "memory");
        m = min(m, v);
    }
    return m == 0;
}
__device__ __forceinline__ void load_image(uint32_t dst, const void* src, uint32_t bar) {
    mbar_expect_tx(bar, kWBytes);
#pragma unroll
    for (int c = 0; c < 3; c++) bulk_load(dst + c * 24576, reinterpret_cast<const char*>(src) + c * 24576, 24576, bar);
}
__device__ __forceinline__ void repair_image(uint32_t dst, const void* src, uint32_t bar, uint32_t par) {
    uint32_t tries = 0;
    bool bad;
    do {
        if (((tid_now() >> 5) & 3) == 0) {
            if (elect_one()) {
                asm volatile("fence.proxy.async;" ::: "memory");
                load_image(dst, src, bar);
            }
            __syncwarp();
        }
        mbar_wait(bar, par);
        par ^= 1;
        bad = chunk_incomplete(dst) | chunk_incomplete(dst + 24576) | chunk_incomplete(dst + 2 * 24576);
        if (++tries > (1u << 16)) __trap();
    } while (bar_or((tid_now() >> 7) + 1, 128, bad));
}
__device__ __forceinline__ void count_image(Scratch* sc) {
    asm volatile("red.relaxed.gpu.global.inc.u32 [%0], %1;" ::"l"(sc->cnt), "r"(3 * nctaid_now() - 1) : "memory");
}
__device__ __forceinline__ uint32_t ld_acquire(const uint32_t* p) {
    uint32_t v;
    asm volatile("ld.acquire.gpu.global.u32 %0, [%1];" : "=r"(v) : "l"(p) : "memory");
    return v;
}
__device__ __noinline__ void clear_images(Scratch* sc) {
    const uint32_t g = gridDim.x, t = threadIdx.x & 127;
    if (t == 0) {
        uint32_t spins = 0;
        while (ld_acquire(sc->cnt) < 2 * g) { if (++spins > (1u << 24)) __trap(); }
    }
    asm volatile("bar.sync %0, 128;" ::"r"((threadIdx.x >> 7) + 1) : "memory");
    for (uint32_t i = blockIdx.x * 64 + t; t < 64 && i < 2 * kWBytes / 16; i += g * 64) sc->wfold[i] = make_uint4(0, 0, 0, 0);
    if (t == 0) count_image(sc);
}
__device__ __forceinline__ void prefetch_x(const CUtensorMap* tm, int win) {
    const int wh = win >> 6, ww = win & 63;
    asm volatile("cp.async.bulk.prefetch.tensor.3d.L2.global.tile [%0, {%1, %2, %3}];"
                 ::"l"(tm), "r"(0), "r"(ww * 8), "r"(wh * 8) : "memory");
}
__device__ __forceinline__ void prefetch_x_chunk(const CUtensorMap* tm, int win, int chunk) {
    const int wh = win >> 6, ww = win & 63;
    asm volatile("cp.async.bulk.prefetch.tensor.4d.L2.global.tile [%0, {%1, %2, %3, %4}];"
                 ::"l"(tm), "r"(0), "r"(ww * 8), "r"(wh * 8), "r"(chunk) : "memory");
}

__device__ __forceinline__ void prefetch_for_ticket(const CUtensorMap* tmp, int t) {
    const int base = kNWG * (int)gridDim.x;
    auto lead = [&](int tt) {
        int down = max(((kNWin - base - tt) * PF_DOWN) >> 8, PF_MIN);
        return min(min((tt * PF_UP) >> 8, PF_LEAD), down);
    };
    const int hi = base + t + lead(t);
    int lo = max(base + t - 1 + lead(t - 1), base + t) + 1;
#pragma unroll 1
    for (; lo <= hi && lo < kNWin; lo++) prefetch_x(tmp, lo);
}

template <bool kFewSMs>
__global__ void __launch_bounds__(kThreads, 1)
swin_attn_kernel(const __nv_bfloat16* __restrict__ wqkv, const __nv_bfloat16* __restrict__ wo, __nv_bfloat16* __restrict__ out, Scratch* sc, uint32_t* tickets,
                 const __grid_constant__ CUtensorMap tmx, const __grid_constant__ CUtensorMap tmp, const __grid_constant__ CUtensorMap tmc) {
    extern __shared__ uint8_t smem_raw[];
    constexpr uint32_t sbase = kSmemBase;
    const uint32_t t_start = clock_now();
    asm volatile("{\n.reg .pred p, q;\n.reg .b32 i, j;\n.reg .b64 a, b;\nmad.lo.u32 i, %2, 14, %3;\nsetp.lt.u32 p, %3, 14;\nsetp.lt.and.u32 p, i, 1728, p;\n"
                 "mad.wide.u32 a, i, 128, %0;\n@p prefetch.global.L2 [a];\n"
                 "mad.lo.u32 j, %2, 5, %3;\nsetp.lt.u32 q, %3, 5;\nsetp.lt.and.u32 q, j, 576, q;\n"
                 "mad.wide.u32 b, j, 128, %1;\n@q prefetch.global.L2 [b];\n}\n" ::"l"(wqkv), "l"(wo), "r"(blockIdx.x), "r"(threadIdx.x) : "memory");
    if (smem_u32(smem_raw) != kSmemBase) __trap();
    const int tid = threadIdx.x, lane = tid & 31;
    const uint32_t warpu = __reduce_or_sync(0xffffffffu, (uint32_t)tid >> 5), wgu = warpu >> 2;
    const int warp = (int)warpu, wg = (int)wgu;
    const int G = gridDim.x;
    const uint32_t bar_full = sbase + kOffBar + 8 * wg;
    const uint32_t bar_w0 = sbase + kOffBar + 32, bar_w1 = bar_w0 + 8;
    int win = wg * G + blockIdx.x;

    if (warp > kWarmW) {
        if (warp == 10) {
            asm volatile("bar.sync 15, 64;" ::: "memory");
            asm volatile("bar.arrive 0, %0;" ::"n"(kThreads) : "memory");
            if (lane == 0) {
                asm volatile("prefetch.tensormap [%0];" ::"l"(&tmc) : "memory");
                asm volatile("prefetch.tensormap [%0];" ::"l"(&tmp) : "memory");
                asm volatile("prefetch.tensormap [%0];" ::"l"(&tmx) : "memory");
                const uint32_t due = (uint32_t)(blockIdx.x * TRK_S) / (uint32_t)G;
#pragma unroll 1
                for (int c = 0; c < 6; c++) {
                    while (clock_now() - t_start < TRK_T0 + (due + c * TRK_S) / 3) {}
                    if (c < 2) tma_load_x_chunk(sbase + kOffX + c * 8192, &tmc, bar_w0 + 16 * c, blockIdx.x, c);
                    else prefetch_x_chunk(&tmc, (c / 3) * G + blockIdx.x, c % 3);
                }
                while (clock_now() - t_start < TRK_T0 + due + 2 * TRK_S) {}
                prefetch_x(&tmp, 2 * G + blockIdx.x);
            }
            __syncwarp();
        } else if (warp == 11) {
            if (lane == 0) {
#pragma unroll
                for (int w = 0; w < kNWG; w++) mbar_init(sbase + kOffBar + 8 * w, 1);
                mbar_init(sbase + kOffBar + 24, 1);
                mbar_init(sbase + kOffBar + 88, 1);
                mbar_init(sbase + kOffBar + 96, 1);
                mbar_init(bar_w0, 1);
                mbar_init(bar_w1, 1);
                mbar_init(sbase + kOffBar + 48, 1);
                mbar_init(sbase + kOffBar + 56, 1);
                asm volatile("st.shared.v4.u32 [%0], {%1, %1, %1, %1};" ::"r"(sbase + kOffBar + 64), "r"(0) : "memory");
                asm volatile("st.shared.v2.u32 [%0], {%1, %1};" ::"r"(sbase + kOffBar + 80), "r"(0) : "memory");
                asm volatile("fence.mbarrier_init.release.cluster;" ::: "memory");
                asm volatile("mbarrier.arrive.shared::cta.b64 _, [%0];" ::"r"(sbase + kOffBar) : "memory");
            }
            __syncwarp();
            asm volatile("bar.arrive 15, 64;" ::: "memory");
            asm volatile("bar.arrive 0, %0;" ::"n"(kThreads) : "memory");
            if (elect_one()) {
                const char* img = reinterpret_cast<const char*>(sc->wfold);
#pragma unroll
                for (int c = 0; c < 3; c++) mbar_expect_tx(c == 0 ? bar_w0 : sbase + kOffBar + 40 + 8 * c, 24576 + 8192);
#pragma unroll
                for (int c = 0; c < 3; c++) mbar_expect_tx(sbase + kOffBar + (c == 0 ? 8 : 80 + 8 * c), 8192);
                while (clock_now() - t_start < REQ_T) {}
#pragma unroll
                for (int c = 0; c < 3; c++) {
                    const uint32_t bar = c == 0 ? bar_w0 : sbase + kOffBar + 40 + 8 * c;
                    if (c == 2) tma_load_x_chunk(sbase + kOffX + c * 8192, &tmc, bar, blockIdx.x, c);
                    bulk_load(sbase + kOffWm + c * 24576, img + c * 24576, 24576, bar);
                }
                mbar_wait(bar_w0, 0);
#pragma unroll
                for (int c = 0; c < 3; c++)
                    tma_load_x_chunk(sbase + kOffX + kXBytes + c * 8192, &tmc, sbase + kOffBar + (c == 0 ? 8 : 80 + 8 * c), G + blockIdx.x, c);
            }
            __syncwarp();
        } else {
            asm volatile("bar.sync 0, %0;" ::"n"(kThreads) : "memory");
            if (warp == 9) {
                if (elect_one()) {
                    while (clock_now() - t_start < REQ_TV) {}
                    mbar_wait(sbase + kOffBar + 48, 0);
                    asm volatile("fence.proxy.async.shared::cta;" ::: "memory");
                    load_image(sbase + kOffWv, reinterpret_cast<const char*>(sc->wfold) + kWBytes, bar_w1);
                    mbar_expect_tx(sbase + kOffBar + 16, kXBytes);
                    tma_load_x(sbase + kOffX + 2 * kXBytes, &tmx, sbase + kOffBar + 16, 2 * G + blockIdx.x);
                }
                __syncwarp();
            }
        }
    } else {
        if constexpr (kFewSMs) {
#pragma unroll 1
            for (int j = blockIdx.x; j < kJobs; j += G) {
                fold_job(sc, wqkv, wo, j, warp, lane);
                asm volatile("bar.sync 14, %0;" ::"n"(32 * kWarmW + 32) : "memory");
            }
        } else {
            if (blockIdx.x < kJobs) fold_job(sc, wqkv, wo, blockIdx.x, warp, lane);
        }
        asm volatile("bar.sync 0, %0;" ::"n"(kThreads) : "memory");
    }
    if (wg == kNWG - 1) asm volatile("bar.sync 7, 128;" ::: "memory");
    if (wg == 1) {
        mbar_wait(bar_w0, 0);
        bool bad = chunk_incomplete(sbase + kOffWm);
        mbar_wait(sbase + kOffBar + 48, 0);
        bad |= chunk_incomplete(sbase + kOffWm + 24576);
        mbar_wait(sbase + kOffBar + 56, 0);
        bad |= chunk_incomplete(sbase + kOffWm + 2 * 24576);
        asm volatile("bar.arrive 8, 256;" ::: "memory");
        if (bar_or(11, 256, bad)) {
            repair_image(sbase + kOffWm, sc->wfold, sbase + kOffBar + 24, 0);
            asm volatile("bar.arrive 11, 256;" ::: "memory");
        }
        if (tid == 128) count_image(sc);
    } else if (wg == 2) {
        mbar_wait(bar_w1, 0);
        const bool bad = chunk_incomplete(sbase + kOffWv) | chunk_incomplete(sbase + kOffWv + 24576) | chunk_incomplete(sbase + kOffWv + 2 * 24576);
        if (bar_or(3, 128, bad)) {
            repair_image(sbase + kOffWv, reinterpret_cast<const char*>(sc->wfold) + kWBytes, bar_w1, 1);
        }
        if (tid == 256) count_image(sc);
    }

    constexpr uint32_t dWm = ((sbase + kOffWm) >> 4) | (1u << 16);
    constexpr uint32_t dWv = ((sbase + kOffWv) >> 4) | (1u << 16);
    const float cs = 0.07216878364870322f * 1.4426950408889634f;
    mbar_wait(bar_w0, 0);
    mbar_wait(bar_full, 0);

    uint4 hv[12];
    uint8_t* hptr;
    uint32_t phase = 0;
    float acc[96];
    uint32_t ticket = 0;
    {
        const uint32_t dX = desc_x(wg_uniform());
        if (wg != 0) ring_wait();
        if (wg == 1) {
            __syncwarp();
            const uint32_t t1 = clock_now();
            while (clock_now() - t1 < G11_DELAY) {}
        }
        wg_fence();
        Gemm1<0, 3>::run(acc, dX, dWm);
        const uint32_t bar_c1 = sbase + kOffBar + (wg == 1 ? 88 : 48);
        mbar_wait(bar_c1, 0);
        wg_fence();
        Gemm1<4, 7>::run(acc, dX, dWm);
        mbar_wait(bar_c1 + 8, 0);
        wg_fence();
        Gemm1<8, 11>::run(acc, dX, dWm);
        wg_commit();
        if (wg != 0) asm volatile("bar.arrive 8, 256;" ::: "memory");
        ticket = draw_ticket(tickets);
        const bool redo = wg == 0 && bar_or(11, 256, false);
        wg_wait0();
        if (redo) {
            asm volatile("bar.sync 11, 256;" ::: "memory");
            wg_fence();
            Gemm1<0, 11>::run(acc, dX, dWm);
            wg_commit();
            wg_wait0();
        }
        __syncwarp();
    }

    while (true) {
        uint32_t fa[48];
        const uint32_t dX = desc_x(wg_uniform());
        fence_regs(acc);
#pragma unroll
        for (int i = 0; i < 48; i++) fa[i] = pack_bf16(acc[2 * i], acc[2 * i + 1]);

        float s[32];
        fence_regs(fa);
        wg_fence();
        ring_wait();
        Gemm2<11>::run(s, fa, dX);
        wg_commit();
        if constexpr (PASS2 == 11) ring_pass();
        if (((tid_now() >> 5) & 3) == 0) {
            if ((tid_now() & 31) == 0) {
                uint32_t nxt = kNWG * nctaid_now() + ticket;
                if (nxt >= kNWin) {
                    uint32_t p0, p1, p2, p3;
                    asm volatile("ld.shared.v4.u32 {%0, %1, %2, %3}, [%4];" : "=r"(p0), "=r"(p1), "=r"(p2), "=r"(p3) : "r"(sbase + kOffBar + 64) : "memory");
                    if ((p0 >= kNWin) + (p1 >= kNWin) + (p2 >= kNWin) == kNWG - 1) nxt = kLastOfCta;
                }
                asm volatile("st.shared.u32 [%0], %1;" ::"r"(sbase + kOffBar + 64 + 4 * (tid_now() >> 7)), "r"(nxt) : "memory");
            }
            __syncwarp();
            asm volatile("bar.arrive %0, 128;" ::"r"((tid_now() >> 7) + 4) : "memory");
        }
        wg_wait0();
        fence_regs(s);
        fence_regs(fa);

        uint32_t pa[16];
        {
            float a0[8], a1[8];
#pragma unroll
            for (int j = 0; j < 8; j++) { a0[j] = fmaxf(s[4 * j], s[4 * j + 1]); a1[j] = fmaxf(s[4 * j + 2], s[4 * j + 3]); }
#pragma unroll
            for (int d = 4; d > 0; d >>= 1)
#pragma unroll
                for (int j = 0; j < d; j++) { a0[j] = fmaxf(a0[j], a0[j + d]); a1[j] = fmaxf(a1[j], a1[j + d]); }
            float m0 = a0[0], m1 = a1[0];
            m0 = fmaxf(m0, __shfl_xor_sync(0xffffffffu, m0, 1));
            m1 = fmaxf(m1, __shfl_xor_sync(0xffffffffu, m1, 1));
            m0 = fmaxf(m0, __shfl_xor_sync(0xffffffffu, m0, 2));
            m1 = fmaxf(m1, __shfl_xor_sync(0xffffffffu, m1, 2));
            m0 *= cs; m1 *= cs;
            float l0 = 0.f, l1 = 0.f;
#pragma unroll
            for (int j = 0; j < 8; j++) {
                s[4 * j]     = ex2(fmaf(s[4 * j], cs, -m0));
                s[4 * j + 1] = ex2(fmaf(s[4 * j + 1], cs, -m0));
                s[4 * j + 2] = ex2(fmaf(s[4 * j + 2], cs, -m1));
                s[4 * j + 3] = ex2(fmaf(s[4 * j + 3], cs, -m1));
                l0 += s[4 * j] + s[4 * j + 1];
                l1 += s[4 * j + 2] + s[4 * j + 3];
            }
            l0 += __shfl_xor_sync(0xffffffffu, l0, 1);
            l1 += __shfl_xor_sync(0xffffffffu, l1, 1);
            l0 += __shfl_xor_sync(0xffffffffu, l0, 2);
            l1 += __shfl_xor_sync(0xffffffffu, l1, 2);
            const float r0 = rcp(l0), r1 = rcp(l1);
#pragma unroll
            for (int j = 0; j < 8; j++) {
                pa[2 * j]     = pack_bf16(s[4 * j] * r0, s[4 * j + 1] * r0);
                pa[2 * j + 1] = pack_bf16(s[4 * j + 2] * r1, s[4 * j + 3] * r1);
            }
        }

        const uint32_t dXt = desc_xt(wg_uniform());
        if (((tid_now() >> 5) & 3) != 0) asm volatile("bar.sync %0, 128;" ::"r"((tid_now() >> 7) + 4) : "memory");
        uint32_t pub;
        asm volatile("ld.shared.u32 %0, [%1];" : "=r"(pub) : "r"(sbase + kOffBar + 64 + 4 * (tid_now() >> 7)) : "memory");
        const int nxt = (int)__reduce_or_sync(0xffffffffu, pub);
        store_p_if(pa, nxt == (int)kLastOfCta);
        if (nxt == (int)kLastOfCta) {
            last_window(out, win);
            asm volatile("exit;");
            __builtin_unreachable();
        }
        fence_regs(pa);
        wg_fence();
        ring_wait();
        Gemm3<3>::run(acc, pa, dXt);
        wg_commit();
        if constexpr (PASS3 == 3) ring_pass();
        wg_wait0();
        fence_regs(acc);
        fence_regs(pa);

        if (((tid_now() >> 5) & 3) == 0) {
            asm volatile("bar.sync %0, 128;" ::"r"((tid_now() >> 7) + 1) : "memory");
            if (elect_one()) {
                const uint32_t wgl = tid_now() >> 7;
                const uint32_t bar = sbase + kOffBar + 8 * wgl;
                if (nxt < kNWin) {
                    mbar_expect_tx(bar, kXBytes);
                    tma_load_x(sbase + kOffX + wgl * kXBytes, &tmx, bar, nxt);
                    uint32_t again;
                    asm volatile("ld.volatile.shared.u32 %0, [%1];" : "=r"(again) : "r"(sbase + kOffBar + 64 + 4 * wgl) : "memory");
                    prefetch_for_ticket(&tmp, (int)again - kNWG * (int)gridDim.x);
                }
            }
            __syncwarp();
        } else {
            asm volatile("bar.arrive %0, 128;" ::"r"((tid_now() >> 7) + 1) : "memory");
        }
#pragma unroll
        for (int i = 0; i < 48; i++) fa[i] = pack_bf16(acc[2 * i], acc[2 * i + 1]);

        asm volatile("st.volatile.shared.v4.b32 [%4], {%0, %1, %2, %3};"
                     :: "r"(fa[44]), "r"(fa[45]), "r"(fa[46]), "r"(fa[47]), "r"(sbase + kOffStash + tid_now() * 16) : "memory");
        fence_regs(fa);
        wg_fence();
        ring_wait();
        Gemm4<0, 1>::run(acc, fa, dWv);
        wg_commit();
        Gemm4<2, 10>::run(acc, fa, dWv);
        wg_commit();
        wg_wait1();
        uint32_t fl[4];
        asm volatile("ld.volatile.shared.v4.b32 {%0, %1, %2, %3}, [%4];"
                     : "=r"(fl[0]), "=r"(fl[1]), "=r"(fl[2]), "=r"(fl[3]) : "r"(sbase + kOffStash + tid_now() * 16) : "memory");
        wg_fence();
        wg192_rs<false, 0, koff(11, 24576)>(acc, fl, dWv);
        wg_commit();
        if (nxt >= kNWin) count_finished();
        ring_pass();
        hptr = out_address(out, win);
        win = nxt;
        const uint32_t dX1 = desc_x(wg_uniform());
        phase ^= 1;
        if (win < kNWin) mbar_wait(sbase + kOffBar + 8 * (tid_now() >> 7), phase);
        asm volatile("" : "+l"(hptr) :: "memory");
        wg_wait0();
        fence_regs(acc);
        fence_regs(fa);
        fence_regs(fl);

#pragma unroll
        for (int a = 0; a < 6; a++) {
            hv[2 * a].x     = pack_bf16(acc[16 * a + 0], acc[16 * a + 1]);
            hv[2 * a].y     = pack_bf16(acc[16 * a + 4], acc[16 * a + 5]);
            hv[2 * a].z     = pack_bf16(acc[16 * a + 8], acc[16 * a + 9]);
            hv[2 * a].w     = pack_bf16(acc[16 * a + 12], acc[16 * a + 13]);
            hv[2 * a + 1].x = pack_bf16(acc[16 * a + 2], acc[16 * a + 3]);
            hv[2 * a + 1].y = pack_bf16(acc[16 * a + 6], acc[16 * a + 7]);
            hv[2 * a + 1].z = pack_bf16(acc[16 * a + 10], acc[16 * a + 11]);
            hv[2 * a + 1].w = pack_bf16(acc[16 * a + 14], acc[16 * a + 15]);
        }
        if constexpr (slot_begin(0) > 0) {
            __syncwarp();
            store_slot<-1>(hv, hptr);
            __syncwarp();
        }
        if (win >= kNWin) break;
        wg_fence();
        ring_wait();
        Gemm1St<11>::run(acc, dX1, dWm, hv, hptr);
        ticket = draw_ticket(tickets);
        store_paced<slot_begin(12)>(hv, hptr, clock_now());
        wg_wait0();
    }
    {
        const uint32_t me = tid_now() >> 7, nx = me == kNWG - 1 ? 0 : me + 1;
        uint32_t nd, last;
        asm volatile("bar.sync %0, 128;" ::"r"(me + 1) : "memory");
        asm volatile("ld.volatile.shared.u32 %0, [%1];" : "=r"(nd) : "r"(sbase + kOffBar + 80) : "memory");
        const bool first = nd == 1;
        const uint32_t t0 = clock_now();
        store_tail<slot_begin(0), TAIL_PASS>(hv, hptr, t0);
        if (first) { ring_wait(); ring_pass(); }
        store_tail<TAIL_PASS, 12>(hv, hptr, t0);
        do {
            ring_wait();
            asm volatile("ld.volatile.shared.v2.u32 {%0, %1}, [%2];" : "=r"(nd), "=r"(last) : "r"(sbase + kOffBar + 80) : "memory");
            if (nd != kNWG || nx != last) ring_pass();
        } while (nd != kNWG);
        if (first) clear_images(sc);
    }
}

typedef CUresult (*EncodeTiledFn)(CUtensorMap*, CUtensorMapDataType, cuuint32_t, void*, const cuuint64_t*,
                                  const cuuint64_t*, const cuuint32_t*, const cuuint32_t*, CUtensorMapInterleave,
                                  CUtensorMapSwizzle, CUtensorMapL2promotion, CUtensorMapFloatOOBfill);

}

extern "C" void kernel_launch(void* const* d_in, const int* in_sizes, int n_in, void* d_out, int out_size) {
    (void)in_sizes; (void)n_in; (void)out_size;
    const __nv_bfloat16* x    = (const __nv_bfloat16*)d_in[0];
    const __nv_bfloat16* wqkv = (const __nv_bfloat16*)d_in[1];
    const __nv_bfloat16* wo   = (const __nv_bfloat16*)d_in[2];

    static EncodeTiledFn encode = nullptr;
    static int num_sms = 0;
    static void* scratch = nullptr;
    if (!encode) {
        void* fn = nullptr;
        cudaDriverEntryPointQueryResult qr;
        cudaGetDriverEntryPoint("cuTensorMapEncodeTiled", &fn, cudaEnableDefault, &qr);
        encode = (EncodeTiledFn)fn;
        int dev = 0;
        cudaGetDevice(&dev);
        cudaDeviceGetAttribute(&num_sms, cudaDevAttrMultiProcessorCount, dev);
        cudaGetSymbolAddress(&scratch, g_scratch);
        cudaFuncSetAttribute(swin_attn_kernel<false>, cudaFuncAttributeMaxDynamicSharedMemorySize, kSmemBytes);
        cudaFuncSetAttribute(swin_attn_kernel<true>, cudaFuncAttributeMaxDynamicSharedMemorySize, kSmemBytes);
    }
    CUtensorMap tmx;
    const cuuint64_t gdim[4] = {64, (cuuint64_t)kHW, (cuuint64_t)kHW, 3};
    const cuuint64_t gstr[3] = {(cuuint64_t)kC * 2, (cuuint64_t)kHW * kC * 2, 128};
    const cuuint32_t box[4] = {64, 8, 8, 3};
    const cuuint32_t estr[4] = {1, 1, 1, 1};
    encode(&tmx, CU_TENSOR_MAP_DATA_TYPE_BFLOAT16, 4, (void*)x, gdim, gstr, box, estr, CU_TENSOR_MAP_INTERLEAVE_NONE,
           CU_TENSOR_MAP_SWIZZLE_128B, CU_TENSOR_MAP_L2_PROMOTION_NONE, CU_TENSOR_MAP_FLOAT_OOB_FILL_NONE);

    CUtensorMap tmp;
    const cuuint64_t pdim[3] = {(cuuint64_t)kC, (cuuint64_t)kHW, (cuuint64_t)kHW};
    const cuuint64_t pstr[2] = {(cuuint64_t)kC * 2, (cuuint64_t)kHW * kC * 2};
    const cuuint32_t pbox[3] = {(cuuint32_t)kC, 8, 8};
    encode(&tmp, CU_TENSOR_MAP_DATA_TYPE_BFLOAT16, 3, (void*)x, pdim, pstr, pbox, estr, CU_TENSOR_MAP_INTERLEAVE_NONE,
           CU_TENSOR_MAP_SWIZZLE_NONE, CU_TENSOR_MAP_L2_PROMOTION_NONE, CU_TENSOR_MAP_FLOAT_OOB_FILL_NONE);
    CUtensorMap tmc;
    const cuuint32_t boxc[4] = {64, 8, 8, 1};
    encode(&tmc, CU_TENSOR_MAP_DATA_TYPE_BFLOAT16, 4, (void*)x, gdim, gstr, boxc, estr, CU_TENSOR_MAP_INTERLEAVE_NONE,
           CU_TENSOR_MAP_SWIZZLE_128B, CU_TENSOR_MAP_L2_PROMOTION_NONE, CU_TENSOR_MAP_FLOAT_OOB_FILL_NONE);
    if (num_sms >= kJobs)
        swin_attn_kernel<false><<<num_sms, kThreads, kSmemBytes, cudaStreamPerThread>>>(wqkv, wo, (__nv_bfloat16*)d_out, (Scratch*)scratch, ((Scratch*)scratch)->ticket, tmx, tmp, tmc);
    else
        swin_attn_kernel<true><<<num_sms, kThreads, kSmemBytes, cudaStreamPerThread>>>(wqkv, wo, (__nv_bfloat16*)d_out, (Scratch*)scratch, ((Scratch*)scratch)->ticket, tmx, tmp, tmc);
}
```

```cpp
#include <cuda_runtime.h>
#include <cuda_bf16.h>
#include <cuda.h>
#include <stdint.h>

namespace {

constexpr int kC      = 192;
constexpr int kHW     = 512;
#define MAXWIN 4096
constexpr int kNWin   = MAXWIN;
constexpr int kXBytes = 64 * kC * 2;
constexpr int kWBytes = kC * kC * 2;
constexpr int kNWG    = 3;
constexpr int kThreads = kNWG * 128;
constexpr int kJobsM  = 72;
constexpr int kJobs   = 120;
constexpr int kWarmW  = 4;
#define PF_LEAD 400
#define PF_UP 170
#define PF_DOWN 34
#define PF_MIN 135
#define TRK_T0 400
#define TRK_S 1800
#define G11_DELAY 100
#define REQ_T 2650
#define REQ_TV 4000

constexpr int kOffWm  = 0;
constexpr int kOffWv  = kWBytes;
constexpr int kOffX   = 2 * kWBytes;
constexpr int kOffStage = kOffX + kNWG * kXBytes;
constexpr int kOffBar = kOffStage + 8192;
constexpr int kOffStash = kOffBar + 128;
constexpr int kOffProf = kOffStash + 128 * 16;
constexpr int kSmemBytes = kOffProf;
constexpr uint32_t kSmemBase = 1024;

struct Scratch {
    uint4 wfold[2 * kWBytes / 16];
    uint32_t ticket[32];
    uint32_t cnt[32];
};
__device__ __align__(128) Scratch g_scratch;

__device__ __forceinline__ uint32_t smem_u32(const void* p) { return (uint32_t)__cvta_generic_to_shared(p); }

__device__ __forceinline__ void mbar_init(uint32_t bar, uint32_t count) {
    asm volatile("mbarrier.init.shared::cta.b64 [%0], %1;" ::"r"(bar), "r"(count) : "memory");
}
__device__ __forceinline__ void mbar_expect_tx(uint32_t bar, uint32_t bytes) {
    asm volatile("mbarrier.arrive.expect_tx.shared::cta.b64 _, [%0], %1;" ::"r"(bar), "r"(bytes) : "memory");
}
__device__ __forceinline__ void mbar_wait(uint32_t bar, uint32_t parity) {
    uint32_t ok;
    uint32_t spins = 0;
    do {
        asm volatile("{\n.reg .pred p;\n"
                     "mbarrier.try_wait.parity.shared::cta.b64 p, [%1], %2;\n"
                     "selp.b32 %0, 1, 0, p;\n}\n"
                     : "=r"(ok) : "r"(bar), "r"(parity) : "memory");
        if (++spins > (1u << 26)) __trap();
    } while (!ok);
}
__device__ __forceinline__ uint32_t tid_now() {
    uint32_t t;
    asm volatile("mov.u32 %0, %%tid.x;" : "=r"(t));
    return t;
}
__device__ __forceinline__ uint32_t nctaid_now() {
    uint32_t t;
    asm volatile("mov.u32 %0, %%nctaid.x;" : "=r"(t));
    return t;
}
__device__ __forceinline__ bool elect_one() {
    uint32_t pred;
    asm volatile("{\n.reg .pred p;\nelect.sync _|p, 0xffffffff;\nselp.b32 %0, 1, 0, p;\n}\n" : "=r"(pred));
    return pred != 0;
}
#define PASS2 5
#define PASS3 3
__device__ __forceinline__ void ring_wait() {
    asm volatile("bar.sync %0, 256;" ::"r"((tid_now() >> 7) + 8) : "memory");
}
__device__ __forceinline__ void ring_pass() {
    const uint32_t w = tid_now() >> 7;
    asm volatile("bar.arrive %0, 256;" ::"r"(w == kNWG - 1 ? 8u : w + 9u) : "memory");
}
constexpr uint32_t kLastOfCta = 0x40000000u;
__device__ __forceinline__ uint32_t wg_uniform() { return __reduce_or_sync(0xffffffffu, tid_now() >> 7); }
__device__ __forceinline__ uint32_t desc_x(uint32_t w) { return (((kSmemBase + kOffX) >> 4) | (1u << 16)) + w * (kXBytes >> 4); }
__device__ __forceinline__ uint32_t desc_xt(uint32_t w) { return (((kSmemBase + kOffX) >> 4) | ((8192u >> 4) << 16)) + w * (kXBytes >> 4); }
__device__ __forceinline__ void tma_load_x(uint32_t dst, const CUtensorMap* tm, uint32_t bar, int win) {
    const int wh = win >> 6, ww = win & 63;
    asm volatile("cp.async.bulk.tensor.4d.shared::cluster.global.mbarrier::complete_tx::bytes"
                 " [%0], [%1, {%3, %4, %5, %6}], [%2];"
                 ::"r"(dst), "l"(tm), "r"(bar), "r"(0), "r"(ww * 8), "r"(wh * 8), "r"(0) : "memory");
}
__device__ __forceinline__ void tma_load_x_chunk(uint32_t dst, const CUtensorMap* tm, uint32_t bar, int win, int chunk) {
    const int wh = win >> 6, ww = win & 63;
    asm volatile("cp.async.bulk.tensor.4d.shared::cluster.global.mbarrier::complete_tx::bytes"
                 " [%0], [%1, {%3, %4, %5, %6}], [%2];"
                 ::"r"(dst), "l"(tm), "r"(bar), "r"(0), "r"(ww * 8), "r"(wh * 8), "r"(chunk) : "memory");
}
__device__ __forceinline__ void bulk_load(uint32_t dst, const void* src, uint32_t bytes, uint32_t bar) {
    asm volatile("cp.async.bulk.shared::cluster.global.mbarrier::complete_tx::bytes [%0], [%1], %2, [%3];"
                 ::"r"(dst), "l"(src), "r"(bytes), "r"(bar) : "memory");
}

__device__ __forceinline__ void wg_fence()  { asm volatile("wgmma.fence.sync.aligned;" ::: "memory"); }
__device__ __forceinline__ void wg_commit() { asm volatile("wgmma.commit_group.sync.aligned;" ::: "memory"); }
__device__ __forceinline__ void wg_wait0()  { asm volatile("wgmma.wait_group.sync.aligned 0;" ::: "memory"); }
__device__ __forceinline__ void wg_wait1()  { asm volatile("wgmma.wait_group.sync.aligned 1;" ::: "memory"); }
__device__ __forceinline__ void wg_wait2()  { asm volatile("wgmma.wait_group.sync.aligned 2;" ::: "memory"); }

template <int N> __device__ __forceinline__ void fence_regs(float (&d)[N]) {
#pragma unroll
    for (int i = 0; i < N; i++) asm volatile("" : "+f"(d[i])::"memory");
}
template <int N> __device__ __forceinline__ void fence_regs(uint32_t (&d)[N]) {
#pragma unroll
    for (int i = 0; i < N; i++) asm volatile("" : "+r"(d[i])::"memory");
}

#define ACC8(c, d, i) c(d[i]), c(d[i + 1]), c(d[i + 2]), c(d[i + 3]), c(d[i + 4]), c(d[i + 5]), c(d[i + 6]), c(d[i + 7])
#define ACC32(c, d) ACC8(c, d, 0), ACC8(c, d, 8), ACC8(c, d, 16), ACC8(c, d, 24)
#define ACC96(c, d) ACC32(c, d), ACC8(c, d, 32), ACC8(c, d, 40), ACC8(c, d, 48), ACC8(c, d, 56), \
                    ACC8(c, d, 64), ACC8(c, d, 72), ACC8(c, d, 80), ACC8(c, d, 88)
#define C_IO(x) "+f"(x)
#define C_O(x) "=f"(x)
#define REGS32 "{%0, %1, %2, %3, %4, %5, %6, %7, %8, %9, %10, %11, %12, %13, %14, %15, " \
               "%16, %17, %18, %19, %20, %21, %22, %23, %24, %25, %26, %27, %28, %29, %30, %31}"
#define REGS96 "{%0, %1, %2, %3, %4, %5, %6, %7, %8, %9, %10, %11, %12, %13, %14, %15, " \
               "%16, %17, %18, %19, %20, %21, %22, %23, %24, %25, %26, %27, %28, %29, %30, %31, " \
               "%32, %33, %34, %35, %36, %37, %38, %39, %40, %41, %42, %43, %44, %45, %46, %47, " \
               "%48, %49, %50, %51, %52, %53, %54, %55, %56, %57, %58, %59, %60, %61, %62, %63, " \
               "%64, %65, %66, %67, %68, %69, %70, %71, %72, %73, %74, %75, %76, %77, %78, %79, " \
               "%80, %81, %82, %83, %84, %85, %86, %87, %88, %89, %90, %91, %92, %93, %94, %95}"

#define DESC_HI "0x40000040"
#define MK_DESC(name, lo, off) "add.u32 t, " lo ", " off ";\nmov.b64 " name ", {t, " DESC_HI "};\n"

template <bool First, int OA, int OB> __device__ __forceinline__ void wg192_ss(float (&d)[96], uint32_t la, uint32_t lb) {
    if constexpr (First)
        asm volatile("{\n.reg .pred p;\n.reg .b32 t;\n.reg .b64 da, db;\nsetp.ne.b32 p, 0, 0;\n"
                     MK_DESC("da", "%96", "%98") MK_DESC("db", "%97", "%99")
                     "wgmma.mma_async.sync.aligned.m64n192k16.f32.bf16.bf16 " REGS96 ", da, db, p, 1, 1, 0, 0;\n}\n"
                     : ACC96(C_O, d) : "r"(la), "r"(lb), "n"(OA), "n"(OB));
    else
        asm volatile("{\n.reg .pred p;\n.reg .b32 t;\n.reg .b64 da, db;\nsetp.ne.b32 p, 1, 0;\n"
                     MK_DESC("da", "%96", "%98") MK_DESC("db", "%97", "%99")
                     "wgmma.mma_async.sync.aligned.m64n192k16.f32.bf16.bf16 " REGS96 ", da, db, p, 1, 1, 0, 0;\n}\n"
                     : ACC96(C_IO, d) : "r"(la), "r"(lb), "n"(OA), "n"(OB));
}
template <bool First, int TB, int OB> __device__ __forceinline__ void wg192_rs(float (&d)[96], const uint32_t* a, uint32_t lb) {
    if constexpr (First)
        asm volatile("{\n.reg .pred p;\n.reg .b32 t;\n.reg .b64 db;\nsetp.ne.b32 p, 0, 0;\n"
                     MK_DESC("db", "%100", "%102")
                     "wgmma.mma_async.sync.aligned.m64n192k16.f32.bf16.bf16 " REGS96 ", {%96, %97, %98, %99}, db, p, 1, 1, %101;\n}\n"
                     : ACC96(C_O, d) : "r"(a[0]), "r"(a[1]), "r"(a[2]), "r"(a[3]), "r"(lb), "n"(TB), "n"(OB));
    else
        asm volatile("{\n.reg .pred p;\n.reg .b32 t;\n.reg .b64 db;\nsetp.ne.b32 p, 1, 0;\n"
                     MK_DESC("db", "%100", "%102")
                     "wgmma.mma_async.sync.aligned.m64n192k16.f32.bf16.bf16 " REGS96 ", {%96, %97, %98, %99}, db, p, 1, 1, %101;\n}\n"
                     : ACC96(C_IO, d) : "r"(a[0]), "r"(a[1]), "r"(a[2]), "r"(a[3]), "r"(lb), "n"(TB), "n"(OB));
}
template <bool First, int OB> __device__ __forceinline__ void wg64_rs(float (&d)[32], const uint32_t* a, uint32_t lb) {
    if constexpr (First)
        asm volatile("{\n.reg .pred p;\n.reg .b32 t;\n.reg .b64 db;\nsetp.ne.b32 p, 0, 0;\n"
                     MK_DESC("db", "%36", "%37")
                     "wgmma.mma_async.sync.aligned.m64n64k16.f32.bf16.bf16 " REGS32 ", {%32, %33, %34, %35}, db, p, 1, 1, 0;\n}\n"
                     : ACC32(C_O, d) : "r"(a[0]), "r"(a[1]), "r"(a[2]), "r"(a[3]), "r"(lb), "n"(OB));
    else
        asm volatile("{\n.reg .pred p;\n.reg .b32 t;\n.reg .b64 db;\nsetp.ne.b32 p, 1, 0;\n"
                     MK_DESC("db", "%36", "%37")
                     "wgmma.mma_async.sync.aligned.m64n64k16.f32.bf16.bf16 " REGS32 ", {%32, %33, %34, %35}, db, p, 1, 1, 0;\n}\n"
                     : ACC32(C_IO, d) : "r"(a[0]), "r"(a[1]), "r"(a[2]), "r"(a[3]), "r"(lb), "n"(OB));
}
template <bool First, int OA, int OB> __device__ __forceinline__ void wg64_ss(float (&d)[32], uint32_t la, uint32_t lb) {
    if constexpr (First)
        asm volatile("{\n.reg .pred p;\n.reg .b32 t;\n.reg .b64 da, db;\nsetp.ne.b32 p, 0, 0;\n"
                     MK_DESC("da", "%32", "%34") MK_DESC("db", "%33", "%35")
                     "wgmma.mma_async.sync.aligned.m64n64k16.f32.bf16.bf16 " REGS32 ", da, db, p, 1, 1, 0, 1;\n}\n"
                     : ACC32(C_O, d) : "r"(la), "r"(lb), "n"(OA), "n"(OB));
    else
        asm volatile("{\n.reg .pred p;\n.reg .b32 t;\n.reg .b64 da, db;\nsetp.ne.b32 p, 1, 0;\n"
                     MK_DESC("da", "%32", "%34") MK_DESC("db", "%33", "%35")
                     "wgmma.mma_async.sync.aligned.m64n64k16.f32.bf16.bf16 " REGS32 ", da, db, p, 1, 1, 0, 1;\n}\n"
                     : ACC32(C_IO, d) : "r"(la), "r"(lb), "n"(OA), "n"(OB));
}
__host__ __device__ constexpr int koff(int kk, int chunk) { return ((kk >> 2) * chunk + (kk & 3) * 32) >> 4; }

__device__ __forceinline__ uint32_t clock_now() {
    uint32_t t;
    asm volatile("mov.u32 %0, %%clock;" : "=r"(t));
    return t;
}
__device__ __forceinline__ void stage_put(const uint4* h, uint32_t buf) {
    const uint32_t t = tid_now();
    const uint32_t adr = buf + (t & 7) * 128 + ((((t >> 3) & 3) ^ (t & 7)) << 4);
#pragma unroll
    for (int i = 0; i < 4; i++)
        asm volatile("stmatrix.sync.aligned.m8n8.x4.shared.b16 [%4], {%0, %1, %2, %3};"
                     :: "r"(h[i].x), "r"(h[i].y), "r"(h[i].z), "r"(h[i].w), "r"((adr ^ ((i >> 1) << 6)) + (i & 1) * 1024) : "memory");
}
template <int N> __device__ __forceinline__ void stage_send(const CUtensorMap* tm, uint32_t pos, int k, uint32_t buf) {
    asm volatile("fence.proxy.async.shared::cta;" ::: "memory");
    __syncwarp();
    if (elect_one()) {
#pragma unroll
        for (int i = 0; i < N; i++)
            asm volatile("cp.async.bulk.tensor.4d.global.shared::cta.bulk_group [%0, {%2, %3, %4, %5}], [%1];"
                         ::"l"(tm), "r"(buf + i * 8192), "r"(0), "r"(pos & 0xffff), "r"(pos >> 16), "r"(k + i) : "memory");
        asm volatile("cp.async.bulk.commit_group;" ::: "memory");
    }
    __syncwarp();
}
__device__ __forceinline__ void stage_wait() {
    asm volatile("cp.async.bulk.wait_group.read 0;" ::: "memory");
    __syncwarp();
}
__device__ __forceinline__ uint32_t out_pos(int win) {
    return ((win & 63) * 8) | (((win >> 6) * 8 + 2 * ((tid_now() >> 5) & 3)) << 16);
}
__device__ __forceinline__ uint32_t stage_buf() { return kSmemBase + kOffStage + ((tid_now() >> 5) & 3) * 2048; }
__device__ __forceinline__ uint32_t tile_buf() { return kSmemBase + kOffX + (tid_now() >> 7) * kXBytes + ((tid_now() >> 5) & 3) * 2048; }
__device__ __forceinline__ void stage_window(uint4 (&h)[12], const CUtensorMap* tm, uint32_t pos, [[maybe_unused]] int win) {
#pragma unroll
    for (int k = 0; k < 3; k++) {
        if (k > 0) stage_wait();
        stage_put(h + 4 * k, stage_buf());
        stage_send<1>(tm, pos, k, stage_buf());
    }
}
template <int K0, int K> struct Gemm1 {
    static __device__ __forceinline__ void run(float (&d)[96], uint32_t lx, uint32_t lw) {
        if constexpr (K > K0) Gemm1<K0, K - 1>::run(d, lx, lw);
        wg192_ss<K == 0, koff(K, 8192), koff(K, 24576)>(d, lx, lw);
    }
};
__device__ __forceinline__ uint32_t draw_ticket(uint32_t* counter) {
    uint32_t ticket = 0;
    asm volatile("{\n.reg .pred p;\nsetp.eq.u32 p, %2, 0;\n@p atom.relaxed.gpu.global.inc.u32 %0, [%1], %3;\n}\n"
                 : "+r"(ticket) : "l"(counter), "r"(tid_now() & 127), "n"(kNWin - 1) : "memory");
    return ticket;
}
template <int KK> struct Gemm2 { static __device__ __forceinline__ void run(float (&d)[32], const uint32_t* a, uint32_t lx) {
    Gemm2<KK - 1>::run(d, a, lx); wg64_rs<KK == 0, koff(KK, 8192)>(d, a + 4 * KK, lx);
    if constexpr (KK == PASS2 && KK < 11) ring_pass(); } };
template <> struct Gemm2<-1> { static __device__ __forceinline__ void run(float (&)[32], const uint32_t*, uint32_t) {} };
template <int KK> struct Gemm3 { static __device__ __forceinline__ void run(float (&d)[96], const uint32_t* a, uint32_t lxt) {
    Gemm3<KK - 1>::run(d, a, lxt); wg192_rs<KK == 0, 1, KK * (2048 >> 4)>(d, a + 4 * KK, lxt);
    if constexpr (KK == PASS3 && KK < 3) ring_pass(); } };
template <> struct Gemm3<-1> { static __device__ __forceinline__ void run(float (&)[96], const uint32_t*, uint32_t) {} };
template <int K0, int KK> struct Gemm4 { static __device__ __forceinline__ void run(float (&d)[96], const uint32_t* a, uint32_t lw) {
    if constexpr (KK > K0) Gemm4<K0, KK - 1>::run(d, a, lw);
    wg192_rs<KK == 0, 0, koff(KK, 24576)>(d, a + 4 * KK, lw); } };

template <int J, int KK> struct Gemm3s { static __device__ __forceinline__ void run(float (&d)[32], uint32_t lp, uint32_t lxt) {
    if constexpr (KK > 0) Gemm3s<J, KK - 1>::run(d, lp, lxt);
    wg64_ss<KK == 0, KK * 2, (J * 8192 + KK * 2048) / 16>(d, lp, lxt); } };
template <int J, int K0, int KK> struct Gemm4s { static __device__ __forceinline__ void run(float (&d)[32], const uint32_t* a, uint32_t lw) {
    if constexpr (KK > K0) Gemm4s<J, K0, KK - 1>::run(d, a, lw);
    wg64_rs<KK == 0, koff(KK, 24576) + J * (8192 / 16)>(d, a + 4 * KK, lw); } };

__device__ __forceinline__ uint32_t pack_bf16(float lo, float hi) {
    uint32_t r;
    asm("cvt.rn.bf16x2.f32 %0, %1, %2;" : "=r"(r) : "f"(hi), "f"(lo));
    return r;
}
__device__ __forceinline__ float ex2(float x) {
    float r;
    asm("ex2.approx.ftz.f32 %0, %1;" : "=f"(r) : "f"(x));
    return r;
}
__device__ __forceinline__ float rcp(float x) {
    float r;
    asm("rcp.approx.ftz.f32 %0, %1;" : "=f"(r) : "f"(x));
    return r;
}

__device__ __forceinline__ void pack_slice(uint32_t* a, float (&d)[32]) {
    fence_regs(d);
#pragma unroll
    for (int i = 0; i < 16; i++) a[i] = pack_bf16(d[2 * i], d[2 * i + 1]);
#pragma unroll
    for (int i = 0; i < 16; i++) asm volatile("" : "+r"(a[i])::"memory");
}
__device__ __forceinline__ void put_slice(float (&d)[32], uint32_t buf) {
    fence_regs(d);
    uint4 h[4];
#pragma unroll
    for (int i = 0; i < 4; i++) {
        const int o = 16 * (i >> 1) + 2 * (i & 1);
        h[i] = make_uint4(pack_bf16(d[o], d[o + 1]), pack_bf16(d[o + 4], d[o + 5]), pack_bf16(d[o + 8], d[o + 9]), pack_bf16(d[o + 12], d[o + 13]));
    }
    stage_put(h, buf);
    __syncwarp();
}
__device__ __forceinline__ void count_finished() {
    if (((tid_now() >> 5) & 3) == 0) {
        if (elect_one()) {
            uint32_t nd;
            asm volatile("ld.shared.u32 %0, [%1];" : "=r"(nd) : "r"(kSmemBase + kOffBar + 80) : "memory");
            asm volatile("st.shared.v2.u32 [%0], {%1, %2};" ::"r"(kSmemBase + kOffBar + 80), "r"(nd + 1), "r"(tid_now() >> 7) : "memory");
        }
        __syncwarp();
    }
}
__device__ __forceinline__ void store_p_if(const uint32_t (&pa)[16], bool cond) {
    const uint32_t t = tid_now(), row = ((t >> 1) & 48) + (t & 15);
    const uint32_t adr = kSmemBase + kOffStage + row * 128 + ((((t >> 4) & 1) ^ (t & 7)) << 4);
#pragma unroll
    for (int i = 0; i < 4; i++)
        asm volatile("{\n.reg .pred p;\nsetp.ne.u32 p, %5, 0;\n@p stmatrix.sync.aligned.m8n8.x4.shared.b16 [%4], {%0, %1, %2, %3};\n}\n"
                     :: "r"(pa[4 * i]), "r"(pa[4 * i + 1]), "r"(pa[4 * i + 2]), "r"(pa[4 * i + 3]), "r"(adr ^ (i << 5)), "r"((uint32_t)cond) : "memory");
}
__device__ __forceinline__ void last_window(int win) {
    constexpr uint32_t dWv = ((kSmemBase + kOffWv) >> 4) | (1u << 16);
    asm volatile("fence.proxy.async.shared::cta;" ::: "memory");
    const uint32_t w = wg_uniform();
    const uint32_t dXt = desc_xt(w);
    constexpr uint32_t dP = ((kSmemBase + kOffStage) >> 4) | (1u << 16);
    float u0[32], u1[32], u2[32];
    uint32_t fa[48];
    uint32_t buf = tile_buf();
    asm volatile("st.shared.u32 [%0], %1;" ::"r"(kSmemBase + kOffBar + 104), "r"(win) : "memory");
    asm volatile("" : "+r"(buf) :: "memory");
    ring_wait();
    wg_fence();
    Gemm3s<0, 3>::run(u0, dP, dXt); wg_commit();
    Gemm3s<1, 3>::run(u1, dP, dXt); wg_commit();
    Gemm3s<2, 3>::run(u2, dP, dXt); wg_commit();
    count_finished();
    ring_pass();
    wg_wait2();
    pack_slice(fa, u0);
    __syncwarp();
    wg_wait1();
    pack_slice(fa + 16, u1);
    wg_fence();
    Gemm4s<0, 0, 7>::run(u0, fa, dWv); wg_commit();
    wg_wait1();
    pack_slice(fa + 32, u2);
    wg_fence();
    Gemm4s<0, 8, 11>::run(u0, fa, dWv); wg_commit();
    Gemm4s<1, 0, 5>::run(u1, fa, dWv); wg_commit();
    wg_wait1();
    asm volatile("bar.sync %0, 128;" ::"r"(w + 1) : "memory");
    put_slice(u0, buf);
    asm volatile("bar.arrive 12, 256;" ::: "memory");
    wg_fence();
    Gemm4s<1, 6, 11>::run(u1, fa, dWv); wg_commit();
    Gemm4s<2, 0, 5>::run(u2, fa, dWv); wg_commit();
    wg_wait1();
    put_slice(u1, buf + 8192);
    asm volatile("bar.arrive 13, 256;" ::: "memory");
    wg_fence();
    Gemm4s<2, 6, 11>::run(u2, fa, dWv); wg_commit();
    wg_wait0();
    fence_regs(fa);
    put_slice(u2, buf + 2 * 8192);
    asm volatile("bar.arrive 14, 256;" ::: "memory");
}

__device__ __forceinline__ int fold_offset(int n, int k0, int q) {
    const int u = ((k0 & 63) >> 3) + (q >> 1);
    return (k0 >> 6) * 24576 + (q & 1) * 8 + n * 128 + ((u ^ (n & 7)) << 4);
}
__device__ __forceinline__ void mma16816x2(float (&c)[4], float (&d)[4], const uint32_t (&a)[4], const uint32_t (&b)[4]) {
    asm volatile("mma.sync.aligned.m16n8k16.row.col.f32.bf16.bf16.f32 {%0,%1,%2,%3}, {%8,%9,%10,%11}, {%12,%13}, {%0,%1,%2,%3};\n"
                 "mma.sync.aligned.m16n8k16.row.col.f32.bf16.bf16.f32 {%4,%5,%6,%7}, {%8,%9,%10,%11}, {%14,%15}, {%4,%5,%6,%7};"
                 : "+f"(c[0]), "+f"(c[1]), "+f"(c[2]), "+f"(c[3]), "+f"(d[0]), "+f"(d[1]), "+f"(d[2]), "+f"(d[3])
                 : "r"(a[0]), "r"(a[1]), "r"(a[2]), "r"(a[3]), "r"(b[0]), "r"(b[1]), "r"(b[2]), "r"(b[3]));
}
__device__ __forceinline__ void cp_async16(uint32_t dst, const void* src) {
    asm volatile("cp.async.cg.shared.global [%0], [%1], 16;" ::"r"(dst), "l"(src) : "memory");
}
template <bool kTrans> __device__ __forceinline__ void ldsm4(uint32_t (&r)[4], uint32_t addr) {
    if constexpr (kTrans)
        asm volatile("ldmatrix.sync.aligned.m8n8.x4.trans.shared.b16 {%0, %1, %2, %3}, [%4];" : "=r"(r[0]), "=r"(r[1]), "=r"(r[2]), "=r"(r[3]) : "r"(addr) : "memory");
    else
        asm volatile("ldmatrix.sync.aligned.m8n8.x4.shared.b16 {%0, %1, %2, %3}, [%4];" : "=r"(r[0]), "=r"(r[1]), "=r"(r[2]), "=r"(r[3]) : "r"(addr) : "memory");
}
__device__ __forceinline__ uint32_t nonzero(uint32_t w) { return w ? w : 0x80000000u; }
__device__ __forceinline__ void fold_job(Scratch* sc, const __nv_bfloat16* __restrict__ wqkv, const __nv_bfloat16* __restrict__ wo,
                                         int job, int warp, int lane) {
    const bool vo = job >= kJobsM;
    const int nw = vo ? 3 : 2, tile0 = vo ? 3 * (job - kJobsM) : 2 * job;
    const int n0 = (tile0 / 12) * 16, k0 = (tile0 % 12 + max(warp, 1) - 1) * 16;
    const uint32_t stage = kSmemBase + kOffWv;
    if (warp <= nw) {
        if (vo && warp == 0) {
            const char* src = reinterpret_cast<const char*>(wo + (lane >> 1) * kC + n0 + (lane & 1) * 8);
            const uint32_t dst = stage + ((lane ^ ((lane >> 3) & 1)) << 4);
#pragma unroll
            for (int i = 0; i < 12; i++) cp_async16(dst + i * 512, src + i * 16 * kC * 2);
        } else {
            const int row0 = warp == 0 ? n0 : k0, col0 = warp == 0 ? kC : vo ? 2 * kC : 0;
            const char* src = reinterpret_cast<const char*>(wqkv + (row0 + (lane >> 3)) * (3 * kC) + col0 + (lane & 7) * 8);
            const uint32_t dst = stage + warp * 6144 + (lane >> 3) * 384 + (((lane & 7) ^ (lane >> 3)) << 4);
#pragma unroll
            for (int i = 0; i < 12; i++) cp_async16((dst ^ (((i / 3) & 1) << 6)) + (i / 3) * 1536 + (i % 3) * 128, src + (i / 3) * 4 * 3 * kC * 2 + (i % 3) * 128);
        }
        asm volatile("cp.async.wait_all;" ::: "memory");
        asm volatile("bar.sync 13, %0;" ::"r"(32 * nw + 32) : "memory");
    }
    if (warp == 0 || (warp > nw && warp != kWarmW)) return;
    const int g = lane >> 2, q = lane & 3, mi = lane >> 3, r8 = lane & 7;
    uint32_t A[12][4], B[12][4];
    {
        const int row = 4 * (r8 >> 1) + (r8 & 1) + 2 * (mi >> 1);
        const uint32_t base = stage + warp * 6144 + row * 384 + (((mi & 1) ^ (row & 7)) << 4);
#pragma unroll
        for (int ks = 0; ks < 12; ks++) ldsm4<false>(B[ks], (base ^ ((ks & 3) << 5)) + (ks >> 2) * 128);
    }
    if (vo) {
        const int c = r8 + 8 * (mi >> 1);
        const uint32_t base = stage + (((2 * c + (mi & 1)) ^ ((c >> 2) & 1)) << 4);
#pragma unroll
        for (int ks = 0; ks < 12; ks++) ldsm4<true>(A[ks], base + ks * 512);
    } else {
        const uint32_t base = stage + (r8 + 8 * (mi & 1)) * 384 + (((mi >> 1) ^ r8) << 4);
#pragma unroll
        for (int ks = 0; ks < 12; ks++) ldsm4<false>(A[ks], (base ^ ((ks & 3) << 5)) + (ks >> 2) * 128);
    }
    float c0[4] = {0.f, 0.f, 0.f, 0.f}, c1[4] = {0.f, 0.f, 0.f, 0.f}, c2[4] = {0.f, 0.f, 0.f, 0.f}, c3[4] = {0.f, 0.f, 0.f, 0.f};
#pragma unroll
    for (int ks = 0; ks < 12; ks += 2) {
        mma16816x2(c0, c1, A[ks], B[ks]);
        mma16816x2(c2, c3, A[ks + 1], B[ks + 1]);
    }
#pragma unroll
    for (int i = 0; i < 4; i++) { c0[i] += c2[i]; c1[i] += c3[i]; }
    const int n = n0 + g;
    char* img = reinterpret_cast<char*>(sc->wfold) + (vo ? kWBytes : 0);
    asm volatile("{\n.reg .pred p;\nsetp.ne.u32 p, %6, %7;\n@p st.global.v2.u32 [%0], {%2, %3};\n@p st.global.v2.u32 [%1], {%4, %5};\n}\n"
                 ::"l"(img + fold_offset(n, k0, q)), "l"(img + fold_offset(n + 8, k0, q)),
                   "r"(nonzero(pack_bf16(c0[0], c0[1]))), "r"(nonzero(pack_bf16(c1[0], c1[1]))), "r"(nonzero(pack_bf16(c0[2], c0[3]))), "r"(nonzero(pack_bf16(c1[2], c1[3]))),
                   "r"(warp), "n"(kWarmW) : "memory");
}

__device__ __forceinline__ bool bar_or(uint32_t id, uint32_t n, bool pred) {
    uint32_t r;
    asm volatile("{\n.reg .pred p, q;\nsetp.ne.u32 q, %3, 0;\nbar.red.or.pred p, %1, %2, q;\nselp.u32 %0, 1, 0, p;\n}\n"
                 : "=r"(r) : "r"(id), "r"(n), "r"((uint32_t)pred) : "memory");
    return r != 0;
}
__device__ __forceinline__ bool chunk_incomplete(uint32_t base) {
    const uint32_t t = tid_now(), r = (t >> 2) & 7;
    const uint32_t adr = base + (((t >> 5) & 3) * 48 + r) * 128 + (t & 3) * 32 + r * 4;
    uint32_t m = ~0u;
#pragma unroll
    for (int j = 0; j < 6; j++) {
        uint32_t v;
        asm volatile("ld.shared.u32 %0, [%1];" : "=r"(v) : "r"(adr + j * 1024) : "memory");
        m = min(m, v);
    }
    return m == 0;
}
__device__ __forceinline__ void load_image(uint32_t dst, const void* src, uint32_t bar) {
    mbar_expect_tx(bar, kWBytes);
#pragma unroll
    for (int c = 0; c < 3; c++) bulk_load(dst + c * 24576, reinterpret_cast<const char*>(src) + c * 24576, 24576, bar);
}
__device__ __forceinline__ void repair_image(uint32_t dst, const void* src, uint32_t bar, uint32_t par) {
    uint32_t tries = 0;
    bool bad;
    do {
        if (((tid_now() >> 5) & 3) == 0) {
            if (elect_one()) {
                asm volatile("fence.proxy.async;" ::: "memory");
                load_image(dst, src, bar);
            }
            __syncwarp();
        }
        mbar_wait(bar, par);
        par ^= 1;
        bad = chunk_incomplete(dst) | chunk_incomplete(dst + 24576) | chunk_incomplete(dst + 2 * 24576);
        if (++tries > (1u << 16)) __trap();
    } while (bar_or((tid_now() >> 7) + 1, 128, bad));
}
__device__ __forceinline__ void count_image(Scratch* sc) {
    asm volatile("red.relaxed.gpu.global.inc.u32 [%0], %1;" ::"l"(sc->cnt), "r"(3 * nctaid_now() - 1) : "memory");
}
__device__ __forceinline__ uint32_t ld_acquire(const uint32_t* p) {
    uint32_t v;
    asm volatile("ld.acquire.gpu.global.u32 %0, [%1];" : "=r"(v) : "l"(p) : "memory");
    return v;
}
__device__ __noinline__ void clear_images(Scratch* sc) {
    const uint32_t g = gridDim.x, t = threadIdx.x & 127;
    if (t == 0) {
        uint32_t spins = 0;
        while (ld_acquire(sc->cnt) < 2 * g) { if (++spins > (1u << 24)) __trap(); }
    }
    asm volatile("bar.sync %0, 128;" ::"r"((threadIdx.x >> 7) + 1) : "memory");
    for (uint32_t i = blockIdx.x * 64 + t; t < 64 && i < 2 * kWBytes / 16; i += g * 64) sc->wfold[i] = make_uint4(0, 0, 0, 0);
    if (t == 0) count_image(sc);
}
__device__ __forceinline__ void prefetch_x(const CUtensorMap* tm, int win) {
    const int wh = win >> 6, ww = win & 63;
    asm volatile("cp.async.bulk.prefetch.tensor.3d.L2.global.tile [%0, {%1, %2, %3}];"
                 ::"l"(tm), "r"(0), "r"(ww * 8), "r"(wh * 8) : "memory");
}
__device__ __forceinline__ void prefetch_x_chunk(const CUtensorMap* tm, int win, int chunk) {
    const int wh = win >> 6, ww = win & 63;
    asm volatile("cp.async.bulk.prefetch.tensor.4d.L2.global.tile [%0, {%1, %2, %3, %4}];"
                 ::"l"(tm), "r"(0), "r"(ww * 8), "r"(wh * 8), "r"(chunk) : "memory");
}

__device__ __forceinline__ void prefetch_for_ticket(const CUtensorMap* tmp, int t) {
    const int base = kNWG * (int)gridDim.x;
    auto lead = [&](int tt) {
        int down = max(((kNWin - base - tt) * PF_DOWN) >> 8, PF_MIN);
        return min(min((tt * PF_UP) >> 8, PF_LEAD), down);
    };
    const int hi = base + t + lead(t);
    int lo = max(base + t - 1 + lead(t - 1), base + t) + 1;
#pragma unroll 1
    for (; lo <= hi && lo < kNWin; lo++) prefetch_x(tmp, lo);
}

template <bool kFewSMs>
__global__ void __launch_bounds__(kThreads, 1)
swin_attn_kernel(const __nv_bfloat16* __restrict__ wqkv, const __nv_bfloat16* __restrict__ wo, Scratch* sc, uint32_t* tickets,
                 const __grid_constant__ CUtensorMap tmx, const __grid_constant__ CUtensorMap tmp, const __grid_constant__ CUtensorMap tmc,
                 const __grid_constant__ CUtensorMap tmo) {
    extern __shared__ uint8_t smem_raw[];
    constexpr uint32_t sbase = kSmemBase;
    const uint32_t t_start = clock_now();
    asm volatile("{\n.reg .pred p, q;\n.reg .b32 i, j;\n.reg .b64 a, b;\nmad.lo.u32 i, %2, 14, %3;\nsetp.lt.u32 p, %3, 14;\nsetp.lt.and.u32 p, i, 1728, p;\n"
                 "mad.wide.u32 a, i, 128, %0;\n@p prefetch.global.L2 [a];\n"
                 "mad.lo.u32 j, %2, 5, %3;\nsetp.lt.u32 q, %3, 5;\nsetp.lt.and.u32 q, j, 576, q;\n"
                 "mad.wide.u32 b, j, 128, %1;\n@q prefetch.global.L2 [b];\n}\n" ::"l"(wqkv), "l"(wo), "r"(blockIdx.x), "r"(threadIdx.x) : "memory");
    if (smem_u32(smem_raw) != kSmemBase) __trap();
    const int tid = threadIdx.x, lane = tid & 31;
    const uint32_t warpu = __reduce_or_sync(0xffffffffu, (uint32_t)tid >> 5), wgu = warpu >> 2;
    const int warp = (int)warpu, wg = (int)wgu;
    const int G = gridDim.x;
    const uint32_t bar_full = sbase + kOffBar + 8 * wg;
    const uint32_t bar_w0 = sbase + kOffBar + 32, bar_w1 = bar_w0 + 8;
    int win = wg * G + blockIdx.x;

    if (warp > kWarmW) {
        if (warp == 10) {
            asm volatile("bar.sync 15, 64;" ::: "memory");
            asm volatile("bar.arrive 0, %0;" ::"n"(kThreads) : "memory");
            if (lane == 0) {
                asm volatile("prefetch.tensormap [%0];" ::"l"(&tmc) : "memory");
                asm volatile("prefetch.tensormap [%0];" ::"l"(&tmp) : "memory");
                asm volatile("prefetch.tensormap [%0];" ::"l"(&tmx) : "memory");
                const uint32_t due = (uint32_t)(blockIdx.x * TRK_S) / (uint32_t)G;
#pragma unroll 1
                for (int c = 0; c < 6; c++) {
                    while (clock_now() - t_start < TRK_T0 + (due + c * TRK_S) / 3) {}
                    if (c < 2) tma_load_x_chunk(sbase + kOffX + c * 8192, &tmc, bar_w0 + 16 * c, blockIdx.x, c);
                    else prefetch_x_chunk(&tmc, (c / 3) * G + blockIdx.x, c % 3);
                }
                while (clock_now() - t_start < TRK_T0 + due + 2 * TRK_S) {}
                prefetch_x(&tmp, 2 * G + blockIdx.x);
            }
            __syncwarp();
        } else if (warp == 11) {
            if (lane == 0) {
#pragma unroll
                for (int w = 0; w < kNWG; w++) mbar_init(sbase + kOffBar + 8 * w, 1);
                mbar_init(sbase + kOffBar + 24, 1);
                mbar_init(sbase + kOffBar + 88, 1);
                mbar_init(sbase + kOffBar + 96, 1);
                mbar_init(bar_w0, 1);
                mbar_init(bar_w1, 1);
                mbar_init(sbase + kOffBar + 48, 1);
                mbar_init(sbase + kOffBar + 56, 1);
                asm volatile("st.shared.v4.u32 [%0], {%1, %1, %1, %1};" ::"r"(sbase + kOffBar + 64), "r"(0) : "memory");
                asm volatile("st.shared.v2.u32 [%0], {%1, %1};" ::"r"(sbase + kOffBar + 80), "r"(0) : "memory");
                asm volatile("fence.mbarrier_init.release.cluster;" ::: "memory");
                asm volatile("mbarrier.arrive.shared::cta.b64 _, [%0];" ::"r"(sbase + kOffBar) : "memory");
            }
            __syncwarp();
            asm volatile("bar.arrive 15, 64;" ::: "memory");
            asm volatile("bar.arrive 0, %0;" ::"n"(kThreads) : "memory");
            if (elect_one()) {
                const char* img = reinterpret_cast<const char*>(sc->wfold);
#pragma unroll
                for (int c = 0; c < 3; c++) mbar_expect_tx(c == 0 ? bar_w0 : sbase + kOffBar + 40 + 8 * c, 24576 + 8192);
#pragma unroll
                for (int c = 0; c < 3; c++) mbar_expect_tx(sbase + kOffBar + (c == 0 ? 8 : 80 + 8 * c), 8192);
                while (clock_now() - t_start < REQ_T) {}
#pragma unroll
                for (int c = 0; c < 3; c++) {
                    const uint32_t bar = c == 0 ? bar_w0 : sbase + kOffBar + 40 + 8 * c;
                    if (c == 2) tma_load_x_chunk(sbase + kOffX + c * 8192, &tmc, bar, blockIdx.x, c);
                    bulk_load(sbase + kOffWm + c * 24576, img + c * 24576, 24576, bar);
                }
                mbar_wait(bar_w0, 0);
#pragma unroll
                for (int c = 0; c < 3; c++)
                    tma_load_x_chunk(sbase + kOffX + kXBytes + c * 8192, &tmc, sbase + kOffBar + (c == 0 ? 8 : 80 + 8 * c), G + blockIdx.x, c);
            }
            __syncwarp();
        } else {
            asm volatile("bar.sync 0, %0;" ::"n"(kThreads) : "memory");
            if (warp == 9) {
                if (elect_one()) {
                    while (clock_now() - t_start < REQ_TV) {}
                    mbar_wait(sbase + kOffBar + 48, 0);
                    asm volatile("fence.proxy.async.shared::cta;" ::: "memory");
                    load_image(sbase + kOffWv, reinterpret_cast<const char*>(sc->wfold) + kWBytes, bar_w1);
                    mbar_expect_tx(sbase + kOffBar + 16, kXBytes);
                    tma_load_x(sbase + kOffX + 2 * kXBytes, &tmx, sbase + kOffBar + 16, 2 * G + blockIdx.x);
                }
                __syncwarp();
            }
        }
    } else {
        if constexpr (kFewSMs) {
#pragma unroll 1
            for (int j = blockIdx.x; j < kJobs; j += G) {
                fold_job(sc, wqkv, wo, j, warp, lane);
                asm volatile("bar.sync 14, %0;" ::"n"(32 * kWarmW + 32) : "memory");
            }
        } else {
            if (blockIdx.x < kJobs) fold_job(sc, wqkv, wo, blockIdx.x, warp, lane);
        }
        asm volatile("bar.sync 0, %0;" ::"n"(kThreads) : "memory");
    }
    if (wg == kNWG - 1) asm volatile("bar.sync 7, 128;" ::: "memory");
    if (wg == 1) {
        mbar_wait(bar_w0, 0);
        bool bad = chunk_incomplete(sbase + kOffWm);
        mbar_wait(sbase + kOffBar + 48, 0);
        bad |= chunk_incomplete(sbase + kOffWm + 24576);
        mbar_wait(sbase + kOffBar + 56, 0);
        bad |= chunk_incomplete(sbase + kOffWm + 2 * 24576);
        asm volatile("bar.arrive 8, 256;" ::: "memory");
        if (bar_or(11, 256, bad)) {
            repair_image(sbase + kOffWm, sc->wfold, sbase + kOffBar + 24, 0);
            asm volatile("bar.arrive 11, 256;" ::: "memory");
        }
        if (tid == 128) count_image(sc);
    } else if (wg == 2) {
        mbar_wait(bar_w1, 0);
        const bool bad = chunk_incomplete(sbase + kOffWv) | chunk_incomplete(sbase + kOffWv + 24576) | chunk_incomplete(sbase + kOffWv + 2 * 24576);
        if (bar_or(3, 128, bad)) {
            repair_image(sbase + kOffWv, reinterpret_cast<const char*>(sc->wfold) + kWBytes, bar_w1, 1);
        }
        if (tid == 256) count_image(sc);
    }

    constexpr uint32_t dWm = ((sbase + kOffWm) >> 4) | (1u << 16);
    constexpr uint32_t dWv = ((sbase + kOffWv) >> 4) | (1u << 16);
    const float cs = 0.07216878364870322f * 1.4426950408889634f;
    mbar_wait(bar_w0, 0);
    mbar_wait(bar_full, 0);

    uint4 hv[12];
    uint32_t pos;
    uint32_t phase = 0;
    float acc[96];
    uint32_t ticket = 0;
    {
        const uint32_t dX = desc_x(wg_uniform());
        if (wg != 0) ring_wait();
        if (wg == 1) {
            __syncwarp();
            const uint32_t t1 = clock_now();
            while (clock_now() - t1 < G11_DELAY) {}
        }
        wg_fence();
        Gemm1<0, 3>::run(acc, dX, dWm);
        const uint32_t bar_c1 = sbase + kOffBar + (wg == 1 ? 88 : 48);
        mbar_wait(bar_c1, 0);
        wg_fence();
        Gemm1<4, 7>::run(acc, dX, dWm);
        mbar_wait(bar_c1 + 8, 0);
        wg_fence();
        Gemm1<8, 11>::run(acc, dX, dWm);
        wg_commit();
        if (wg != 0) asm volatile("bar.arrive 8, 256;" ::: "memory");
        ticket = draw_ticket(tickets);
        const bool redo = wg == 0 && bar_or(11, 256, false);
        wg_wait0();
        if (redo) {
            asm volatile("bar.sync 11, 256;" ::: "memory");
            wg_fence();
            Gemm1<0, 11>::run(acc, dX, dWm);
            wg_commit();
            wg_wait0();
        }
        __syncwarp();
    }

    while (true) {
        uint32_t fa[48];
        const uint32_t dX = desc_x(wg_uniform());
        fence_regs(acc);
#pragma unroll
        for (int i = 0; i < 48; i++) fa[i] = pack_bf16(acc[2 * i], acc[2 * i + 1]);

        float s[32];
        fence_regs(fa);
        wg_fence();
        ring_wait();
        Gemm2<11>::run(s, fa, dX);
        wg_commit();
        if constexpr (PASS2 == 11) ring_pass();
        if (((tid_now() >> 5) & 3) == 0) {
            if ((tid_now() & 31) == 0) {
                uint32_t nxt = kNWG * nctaid_now() + ticket;
                if (nxt >= kNWin) {
                    uint32_t p0, p1, p2, p3;
                    asm volatile("ld.shared.v4.u32 {%0, %1, %2, %3}, [%4];" : "=r"(p0), "=r"(p1), "=r"(p2), "=r"(p3) : "r"(sbase + kOffBar + 64) : "memory");
                    if ((p0 >= kNWin) + (p1 >= kNWin) + (p2 >= kNWin) == kNWG - 1) nxt = kLastOfCta;
                }
                asm volatile("st.shared.u32 [%0], %1;" ::"r"(sbase + kOffBar + 64 + 4 * (tid_now() >> 7)), "r"(nxt) : "memory");
            }
            __syncwarp();
            asm volatile("bar.arrive %0, 128;" ::"r"((tid_now() >> 7) + 4) : "memory");
        }
        asm volatile("cp.async.bulk.wait_group.read 0;" ::: "memory");
        asm volatile("bar.arrive 15, 256;" ::: "memory");
        wg_wait0();
        fence_regs(s);
        fence_regs(fa);

        uint32_t pa[16];
        {
            float a0[8], a1[8];
#pragma unroll
            for (int j = 0; j < 8; j++) { a0[j] = fmaxf(s[4 * j], s[4 * j + 1]); a1[j] = fmaxf(s[4 * j + 2], s[4 * j + 3]); }
#pragma unroll
            for (int d = 4; d > 0; d >>= 1)
#pragma unroll
                for (int j = 0; j < d; j++) { a0[j] = fmaxf(a0[j], a0[j + d]); a1[j] = fmaxf(a1[j], a1[j + d]); }
            float m0 = a0[0], m1 = a1[0];
            m0 = fmaxf(m0, __shfl_xor_sync(0xffffffffu, m0, 1));
            m1 = fmaxf(m1, __shfl_xor_sync(0xffffffffu, m1, 1));
            m0 = fmaxf(m0, __shfl_xor_sync(0xffffffffu, m0, 2));
            m1 = fmaxf(m1, __shfl_xor_sync(0xffffffffu, m1, 2));
            m0 *= cs; m1 *= cs;
            float l0 = 0.f, l1 = 0.f;
#pragma unroll
            for (int j = 0; j < 8; j++) {
                s[4 * j]     = ex2(fmaf(s[4 * j], cs, -m0));
                s[4 * j + 1] = ex2(fmaf(s[4 * j + 1], cs, -m0));
                s[4 * j + 2] = ex2(fmaf(s[4 * j + 2], cs, -m1));
                s[4 * j + 3] = ex2(fmaf(s[4 * j + 3], cs, -m1));
                l0 += s[4 * j] + s[4 * j + 1];
                l1 += s[4 * j + 2] + s[4 * j + 3];
            }
            l0 += __shfl_xor_sync(0xffffffffu, l0, 1);
            l1 += __shfl_xor_sync(0xffffffffu, l1, 1);
            l0 += __shfl_xor_sync(0xffffffffu, l0, 2);
            l1 += __shfl_xor_sync(0xffffffffu, l1, 2);
            const float r0 = rcp(l0), r1 = rcp(l1);
#pragma unroll
            for (int j = 0; j < 8; j++) {
                pa[2 * j]     = pack_bf16(s[4 * j] * r0, s[4 * j + 1] * r0);
                pa[2 * j + 1] = pack_bf16(s[4 * j + 2] * r1, s[4 * j + 3] * r1);
            }
        }

        const uint32_t dXt = desc_xt(wg_uniform());
        if (((tid_now() >> 5) & 3) != 0) asm volatile("bar.sync %0, 128;" ::"r"((tid_now() >> 7) + 4) : "memory");
        uint32_t pub;
        asm volatile("ld.shared.u32 %0, [%1];" : "=r"(pub) : "r"(sbase + kOffBar + 64 + 4 * (tid_now() >> 7)) : "memory");
        const int nxt = (int)__reduce_or_sync(0xffffffffu, pub);
        store_p_if(pa, nxt == (int)kLastOfCta);
        if (nxt == (int)kLastOfCta) {
            last_window(win);
            asm volatile("exit;");
            __builtin_unreachable();
        }
        fence_regs(pa);
        wg_fence();
        ring_wait();
        Gemm3<3>::run(acc, pa, dXt);
        wg_commit();
        if constexpr (PASS3 == 3) ring_pass();
        wg_wait0();
        fence_regs(acc);
        fence_regs(pa);

        if (((tid_now() >> 5) & 3) == 0) {
            asm volatile("bar.sync %0, 128;" ::"r"((tid_now() >> 7) + 1) : "memory");
            if (elect_one()) {
                const uint32_t wgl = tid_now() >> 7;
                const uint32_t bar = sbase + kOffBar + 8 * wgl;
                if (nxt < kNWin) {
                    mbar_expect_tx(bar, kXBytes);
                    tma_load_x(sbase + kOffX + wgl * kXBytes, &tmx, bar, nxt);
                    uint32_t again;
                    asm volatile("ld.volatile.shared.u32 %0, [%1];" : "=r"(again) : "r"(sbase + kOffBar + 64 + 4 * wgl) : "memory");
                    prefetch_for_ticket(&tmp, (int)again - kNWG * (int)gridDim.x);
                }
            }
            __syncwarp();
        } else {
            asm volatile("bar.arrive %0, 128;" ::"r"((tid_now() >> 7) + 1) : "memory");
        }
#pragma unroll
        for (int i = 0; i < 48; i++) fa[i] = pack_bf16(acc[2 * i], acc[2 * i + 1]);

        asm volatile("st.volatile.shared.v4.b32 [%4], {%0, %1, %2, %3};"
                     :: "r"(fa[44]), "r"(fa[45]), "r"(fa[46]), "r"(fa[47]), "r"(sbase + kOffStash + (tid_now() & 127) * 16) : "memory");
        fence_regs(fa);
        wg_fence();
        ring_wait();
        Gemm4<0, 1>::run(acc, fa, dWv);
        wg_commit();
        Gemm4<2, 10>::run(acc, fa, dWv);
        wg_commit();
        wg_wait1();
        uint32_t fl[4];
        asm volatile("ld.volatile.shared.v4.b32 {%0, %1, %2, %3}, [%4];"
                     : "=r"(fl[0]), "=r"(fl[1]), "=r"(fl[2]), "=r"(fl[3]) : "r"(sbase + kOffStash + (tid_now() & 127) * 16) : "memory");
        wg_fence();
        wg192_rs<false, 0, koff(11, 24576)>(acc, fl, dWv);
        wg_commit();
        if (nxt >= kNWin) count_finished();
        ring_pass();
        pos = out_pos(win);
        win = nxt;
        const uint32_t dX1 = desc_x(wg_uniform());
        phase ^= 1;
        if (win < kNWin) mbar_wait(sbase + kOffBar + 8 * (tid_now() >> 7), phase);
        asm volatile("" : "+r"(pos) :: "memory");
        wg_wait0();
        fence_regs(acc);
        fence_regs(fa);
        fence_regs(fl);

#pragma unroll
        for (int a = 0; a < 6; a++) {
            hv[2 * a].x     = pack_bf16(acc[16 * a + 0], acc[16 * a + 1]);
            hv[2 * a].y     = pack_bf16(acc[16 * a + 4], acc[16 * a + 5]);
            hv[2 * a].z     = pack_bf16(acc[16 * a + 8], acc[16 * a + 9]);
            hv[2 * a].w     = pack_bf16(acc[16 * a + 12], acc[16 * a + 13]);
            hv[2 * a + 1].x = pack_bf16(acc[16 * a + 2], acc[16 * a + 3]);
            hv[2 * a + 1].y = pack_bf16(acc[16 * a + 6], acc[16 * a + 7]);
            hv[2 * a + 1].z = pack_bf16(acc[16 * a + 10], acc[16 * a + 11]);
            hv[2 * a + 1].w = pack_bf16(acc[16 * a + 14], acc[16 * a + 15]);
        }
        if (win >= kNWin) break;
        wg_fence();
        ring_wait();
        Gemm1<0, 11>::run(acc, dX1, dWm);
        wg_commit();
        ring_pass();
        ticket = draw_ticket(tickets);
        asm volatile("bar.sync 15, 256;" ::: "memory");
        stage_window(hv, &tmo, pos, win);
        wg_wait0();
    }
    {
        const uint32_t me = tid_now() >> 7, nx = me == kNWG - 1 ? 0 : me + 1;
        uint32_t nd, last;
        asm volatile("bar.sync %0, 128;" ::"r"(me + 1) : "memory");
        asm volatile("ld.volatile.shared.u32 %0, [%1];" : "=r"(nd) : "r"(sbase + kOffBar + 80) : "memory");
        const bool first = nd == 1;
#pragma unroll
        for (int k = 0; k < 3; k++) stage_put(hv + 4 * k, tile_buf() + k * 8192);
        if (first) { ring_wait(); ring_pass(); }
        stage_send<3>(&tmo, pos, 0, tile_buf());
        do {
            ring_wait();
            asm volatile("ld.volatile.shared.v2.u32 {%0, %1}, [%2];" : "=r"(nd), "=r"(last) : "r"(sbase + kOffBar + 80) : "memory");
            if (nd != kNWG || nx != last) ring_pass();
        } while (nd != kNWG);
        if (first) {
            asm volatile("bar.sync 15, 256;" ::: "memory");
        } else {
            const uint32_t buf = sbase + kOffX + last * kXBytes + ((tid_now() >> 5) & 3) * 2048;
            asm volatile("bar.sync 12, 256;" ::: "memory");
            uint32_t lw;
            asm volatile("ld.volatile.shared.u32 %0, [%1];" : "=r"(lw) : "r"(sbase + kOffBar + 104) : "memory");
            pos = out_pos(lw);
            stage_send<1>(&tmo, pos, 0, buf);
            asm volatile("bar.sync 13, 256;" ::: "memory");
            stage_send<1>(&tmo, pos, 1, buf + 8192);
            asm volatile("bar.sync 14, 256;" ::: "memory");
            stage_send<1>(&tmo, pos, 2, buf + 2 * 8192);
        }
        stage_wait();
        if (first) clear_images(sc);
    }
}

typedef CUresult (*EncodeTiledFn)(CUtensorMap*, CUtensorMapDataType, cuuint32_t, void*, const cuuint64_t*,
                                  const cuuint64_t*, const cuuint32_t*, const cuuint32_t*, CUtensorMapInterleave,
                                  CUtensorMapSwizzle, CUtensorMapL2promotion, CUtensorMapFloatOOBfill);

}

extern "C" void kernel_launch(void* const* d_in, const int* in_sizes, int n_in, void* d_out, int out_size) {
    (void)in_sizes; (void)n_in; (void)out_size;
    const __nv_bfloat16* x    = (const __nv_bfloat16*)d_in[0];
    const __nv_bfloat16* wqkv = (const __nv_bfloat16*)d_in[1];
    const __nv_bfloat16* wo   = (const __nv_bfloat16*)d_in[2];

    static EncodeTiledFn encode = nullptr;
    static int num_sms = 0;
    static void* scratch = nullptr;
    if (!encode) {
        void* fn = nullptr;
        cudaDriverEntryPointQueryResult qr;
        cudaGetDriverEntryPoint("cuTensorMapEncodeTiled", &fn, cudaEnableDefault, &qr);
        encode = (EncodeTiledFn)fn;
        int dev = 0;
        cudaGetDevice(&dev);
        cudaDeviceGetAttribute(&num_sms, cudaDevAttrMultiProcessorCount, dev);
        cudaGetSymbolAddress(&scratch, g_scratch);
        cudaFuncSetAttribute(swin_attn_kernel<false>, cudaFuncAttributeMaxDynamicSharedMemorySize, kSmemBytes);
        cudaFuncSetAttribute(swin_attn_kernel<true>, cudaFuncAttributeMaxDynamicSharedMemorySize, kSmemBytes);
    }
    CUtensorMap tmx;
    const cuuint64_t gdim[4] = {64, (cuuint64_t)kHW, (cuuint64_t)kHW, 3};
    const cuuint64_t gstr[3] = {(cuuint64_t)kC * 2, (cuuint64_t)kHW * kC * 2, 128};
    const cuuint32_t box[4] = {64, 8, 8, 3};
    const cuuint32_t estr[4] = {1, 1, 1, 1};
    encode(&tmx, CU_TENSOR_MAP_DATA_TYPE_BFLOAT16, 4, (void*)x, gdim, gstr, box, estr, CU_TENSOR_MAP_INTERLEAVE_NONE,
           CU_TENSOR_MAP_SWIZZLE_128B, CU_TENSOR_MAP_L2_PROMOTION_NONE, CU_TENSOR_MAP_FLOAT_OOB_FILL_NONE);

    CUtensorMap tmp;
    const cuuint64_t pdim[3] = {(cuuint64_t)kC, (cuuint64_t)kHW, (cuuint64_t)kHW};
    const cuuint64_t pstr[2] = {(cuuint64_t)kC * 2, (cuuint64_t)kHW * kC * 2};
    const cuuint32_t pbox[3] = {(cuuint32_t)kC, 8, 8};
    encode(&tmp, CU_TENSOR_MAP_DATA_TYPE_BFLOAT16, 3, (void*)x, pdim, pstr, pbox, estr, CU_TENSOR_MAP_INTERLEAVE_NONE,
           CU_TENSOR_MAP_SWIZZLE_NONE, CU_TENSOR_MAP_L2_PROMOTION_NONE, CU_TENSOR_MAP_FLOAT_OOB_FILL_NONE);
    CUtensorMap tmc;
    const cuuint32_t boxc[4] = {64, 8, 8, 1};
    encode(&tmc, CU_TENSOR_MAP_DATA_TYPE_BFLOAT16, 4, (void*)x, gdim, gstr, boxc, estr, CU_TENSOR_MAP_INTERLEAVE_NONE,
           CU_TENSOR_MAP_SWIZZLE_128B, CU_TENSOR_MAP_L2_PROMOTION_NONE, CU_TENSOR_MAP_FLOAT_OOB_FILL_NONE);
    CUtensorMap tmo;
    const cuuint32_t boxo[4] = {64, 8, 2, 1};
    encode(&tmo, CU_TENSOR_MAP_DATA_TYPE_BFLOAT16, 4, d_out, gdim, gstr, boxo, estr, CU_TENSOR_MAP_INTERLEAVE_NONE,
           CU_TENSOR_MAP_SWIZZLE_128B, CU_TENSOR_MAP_L2_PROMOTION_NONE, CU_TENSOR_MAP_FLOAT_OOB_FILL_NONE);
    if (num_sms >= kJobs)
        swin_attn_kernel<false><<<num_sms, kThreads, kSmemBytes, cudaStreamPerThread>>>(wqkv, wo, (Scratch*)scratch, ((Scratch*)scratch)->ticket, tmx, tmp, tmc, tmo);
    else
        swin_attn_kernel<true><<<num_sms, kThreads, kSmemBytes, cudaStreamPerThread>>>(wqkv, wo, (Scratch*)scratch, ((Scratch*)scratch)->ticket, tmx, tmp, tmc, tmo);
}
```

```cpp
#include <cuda_runtime.h>
#include <cuda_bf16.h>
#include <cuda.h>
#include <stdint.h>

namespace {

constexpr int kC      = 192;
constexpr int kHW     = 512;
#define MAXWIN 4096
constexpr int kNWin   = MAXWIN;
constexpr int kXBytes = 64 * kC * 2;
constexpr int kWBytes = kC * kC * 2;
constexpr int kNWG    = 3;
constexpr int kThreads = kNWG * 128;
constexpr int kJobsM  = 72;
constexpr int kJobs   = 120;
constexpr int kWarmW  = 4;
#define PF_LEAD 400
#define PF_UP 114
#define PF_DOWN 34
#define PF_MIN 135
#define EF_LAST 1000
#define TRK_T0 400
#define TRK_S 1800
#define G11_DELAY 100
#define REQ_T 2650
#define REQ_TV 4000

constexpr int kOffWm  = 0;
constexpr int kOffWv  = kWBytes;
constexpr int kOffX   = 2 * kWBytes;
constexpr int kOffStage = kOffX + kNWG * kXBytes;
constexpr int kOffBar = kOffStage + 8192;
constexpr int kOffStash = kOffBar + 128;
constexpr int kOffProf = kOffStash + 128 * 16;
constexpr int kSmemBytes = kOffProf;
constexpr uint32_t kSmemBase = 1024;

struct Scratch {
    uint4 wfold[2 * kWBytes / 16];
    uint32_t ticket[32];
    uint32_t cnt[32];
};
__device__ __align__(128) Scratch g_scratch;

__device__ __forceinline__ uint32_t smem_u32(const void* p) { return (uint32_t)__cvta_generic_to_shared(p); }

__device__ __forceinline__ void mbar_init(uint32_t bar, uint32_t count) {
    asm volatile("mbarrier.init.shared::cta.b64 [%0], %1;" ::"r"(bar), "r"(count) : "memory");
}
__device__ __forceinline__ void mbar_expect_tx(uint32_t bar, uint32_t bytes) {
    asm volatile("mbarrier.arrive.expect_tx.shared::cta.b64 _, [%0], %1;" ::"r"(bar), "r"(bytes) : "memory");
}
__device__ __forceinline__ void mbar_wait(uint32_t bar, uint32_t parity) {
    uint32_t ok;
    uint32_t spins = 0;
    do {
        asm volatile("{\n.reg .pred p;\n"
                     "mbarrier.try_wait.parity.shared::cta.b64 p, [%1], %2;\n"
                     "selp.b32 %0, 1, 0, p;\n}\n"
                     : "=r"(ok) : "r"(bar), "r"(parity) : "memory");
        if (++spins > (1u << 26)) __trap();
    } while (!ok);
}
__device__ __forceinline__ uint32_t tid_now() {
    uint32_t t;
    asm volatile("mov.u32 %0, %%tid.x;" : "=r"(t));
    return t;
}
__device__ __forceinline__ uint32_t nctaid_now() {
    uint32_t t;
    asm volatile("mov.u32 %0, %%nctaid.x;" : "=r"(t));
    return t;
}
__device__ __forceinline__ bool elect_one() {
    uint32_t pred;
    asm volatile("{\n.reg .pred p;\nelect.sync _|p, 0xffffffff;\nselp.b32 %0, 1, 0, p;\n}\n" : "=r"(pred));
    return pred != 0;
}
#define PASS2 5
#define PASS3 3
__device__ __forceinline__ void ring_wait() {
    asm volatile("bar.sync %0, 256;" ::"r"((tid_now() >> 7) + 8) : "memory");
}
__device__ __forceinline__ void ring_pass() {
    const uint32_t w = tid_now() >> 7;
    asm volatile("bar.arrive %0, 256;" ::"r"(w == kNWG - 1 ? 8u : w + 9u) : "memory");
}
constexpr uint32_t kLastOfCta = 0x40000000u;
__device__ __forceinline__ uint32_t wg_uniform() { return __reduce_or_sync(0xffffffffu, tid_now() >> 7); }
__device__ __forceinline__ uint32_t desc_x(uint32_t w) { return (((kSmemBase + kOffX) >> 4) | (1u << 16)) + w * (kXBytes >> 4); }
__device__ __forceinline__ uint32_t desc_xt(uint32_t w) { return (((kSmemBase + kOffX) >> 4) | ((8192u >> 4) << 16)) + w * (kXBytes >> 4); }
__device__ __forceinline__ void tma_load_x(uint32_t dst, const CUtensorMap* tm, uint32_t bar, int win) {
    const int wh = win >> 6, ww = win & 63;
    asm volatile("cp.async.bulk.tensor.4d.shared::cluster.global.mbarrier::complete_tx::bytes"
                 " [%0], [%1, {%3, %4, %5, %6}], [%2];"
                 ::"r"(dst), "l"(tm), "r"(bar), "r"(0), "r"(ww * 8), "r"(wh * 8), "r"(0) : "memory");
}
__device__ __forceinline__ void tma_load_x_hint(uint32_t dst, const CUtensorMap* tm, uint32_t bar, int win, bool evict_first) {
    const int wh = win >> 6, ww = win & 63;
    uint64_t first, normal;
    asm("createpolicy.fractional.L2::evict_first.b64 %0, 1.0;" : "=l"(first));
    asm("createpolicy.fractional.L2::evict_normal.b64 %0, 1.0;" : "=l"(normal));
    asm volatile("cp.async.bulk.tensor.4d.shared::cluster.global.mbarrier::complete_tx::bytes.L2::cache_hint"
                 " [%0], [%1, {%3, %4, %5, %6}], [%2], %7;"
                 ::"r"(dst), "l"(tm), "r"(bar), "r"(0), "r"(ww * 8), "r"(wh * 8), "r"(0), "l"(evict_first ? first : normal) : "memory");
}
__device__ __forceinline__ void tma_load_x_chunk(uint32_t dst, const CUtensorMap* tm, uint32_t bar, int win, int chunk) {
    const int wh = win >> 6, ww = win & 63;
    asm volatile("cp.async.bulk.tensor.4d.shared::cluster.global.mbarrier::complete_tx::bytes"
                 " [%0], [%1, {%3, %4, %5, %6}], [%2];"
                 ::"r"(dst), "l"(tm), "r"(bar), "r"(0), "r"(ww * 8), "r"(wh * 8), "r"(chunk) : "memory");
}
__device__ __forceinline__ void bulk_load(uint32_t dst, const void* src, uint32_t bytes, uint32_t bar) {
    asm volatile("cp.async.bulk.shared::cluster.global.mbarrier::complete_tx::bytes [%0], [%1], %2, [%3];"
                 ::"r"(dst), "l"(src), "r"(bytes), "r"(bar) : "memory");
}

__device__ __forceinline__ void wg_fence()  { asm volatile("wgmma.fence.sync.aligned;" ::: "memory"); }
__device__ __forceinline__ void wg_commit() { asm volatile("wgmma.commit_group.sync.aligned;" ::: "memory"); }
__device__ __forceinline__ void wg_wait0()  { asm volatile("wgmma.wait_group.sync.aligned 0;" ::: "memory"); }
__device__ __forceinline__ void wg_wait1()  { asm volatile("wgmma.wait_group.sync.aligned 1;" ::: "memory"); }
__device__ __forceinline__ void wg_wait2()  { asm volatile("wgmma.wait_group.sync.aligned 2;" ::: "memory"); }

template <int N> __device__ __forceinline__ void fence_regs(float (&d)[N]) {
#pragma unroll
    for (int i = 0; i < N; i++) asm volatile("" : "+f"(d[i])::"memory");
}
template <int N> __device__ __forceinline__ void fence_regs(uint32_t (&d)[N]) {
#pragma unroll
    for (int i = 0; i < N; i++) asm volatile("" : "+r"(d[i])::"memory");
}

#define ACC8(c, d, i) c(d[i]), c(d[i + 1]), c(d[i + 2]), c(d[i + 3]), c(d[i + 4]), c(d[i + 5]), c(d[i + 6]), c(d[i + 7])
#define ACC32(c, d) ACC8(c, d, 0), ACC8(c, d, 8), ACC8(c, d, 16), ACC8(c, d, 24)
#define ACC96(c, d) ACC32(c, d), ACC8(c, d, 32), ACC8(c, d, 40), ACC8(c, d, 48), ACC8(c, d, 56), \
                    ACC8(c, d, 64), ACC8(c, d, 72), ACC8(c, d, 80), ACC8(c, d, 88)
#define C_IO(x) "+f"(x)
#define C_O(x) "=f"(x)
#define REGS32 "{%0, %1, %2, %3, %4, %5, %6, %7, %8, %9, %10, %11, %12, %13, %14, %15, " \
               "%16, %17, %18, %19, %20, %21, %22, %23, %24, %25, %26, %27, %28, %29, %30, %31}"
#define REGS96 "{%0, %1, %2, %3, %4, %5, %6, %7, %8, %9, %10, %11, %12, %13, %14, %15, " \
               "%16, %17, %18, %19, %20, %21, %22, %23, %24, %25, %26, %27, %28, %29, %30, %31, " \
               "%32, %33, %34, %35, %36, %37, %38, %39, %40, %41, %42, %43, %44, %45, %46, %47, " \
               "%48, %49, %50, %51, %52, %53, %54, %55, %56, %57, %58, %59, %60, %61, %62, %63, " \
               "%64, %65, %66, %67, %68, %69, %70, %71, %72, %73, %74, %75, %76, %77, %78, %79, " \
               "%80, %81, %82, %83, %84, %85, %86, %87, %88, %89, %90, %91, %92, %93, %94, %95}"

#define DESC_HI "0x40000040"
#define MK_DESC(name, lo, off) "add.u32 t, " lo ", " off ";\nmov.b64 " name ", {t, " DESC_HI "};\n"

template <bool First, int OA, int OB> __device__ __forceinline__ void wg192_ss(float (&d)[96], uint32_t la, uint32_t lb) {
    if constexpr (First)
        asm volatile("{\n.reg .pred p;\n.reg .b32 t;\n.reg .b64 da, db;\nsetp.ne.b32 p, 0, 0;\n"
                     MK_DESC("da", "%96", "%98") MK_DESC("db", "%97", "%99")
                     "wgmma.mma_async.sync.aligned.m64n192k16.f32.bf16.bf16 " REGS96 ", da, db, p, 1, 1, 0, 0;\n}\n"
                     : ACC96(C_O, d) : "r"(la), "r"(lb), "n"(OA), "n"(OB));
    else
        asm volatile("{\n.reg .pred p;\n.reg .b32 t;\n.reg .b64 da, db;\nsetp.ne.b32 p, 1, 0;\n"
                     MK_DESC("da", "%96", "%98") MK_DESC("db", "%97", "%99")
                     "wgmma.mma_async.sync.aligned.m64n192k16.f32.bf16.bf16 " REGS96 ", da, db, p, 1, 1, 0, 0;\n}\n"
                     : ACC96(C_IO, d) : "r"(la), "r"(lb), "n"(OA), "n"(OB));
}
template <bool First, int TB, int OB> __device__ __forceinline__ void wg192_rs(float (&d)[96], const uint32_t* a, uint32_t lb) {
    if constexpr (First)
        asm volatile("{\n.reg .pred p;\n.reg .b32 t;\n.reg .b64 db;\nsetp.ne.b32 p, 0, 0;\n"
                     MK_DESC("db", "%100", "%102")
                     "wgmma.mma_async.sync.aligned.m64n192k16.f32.bf16.bf16 " REGS96 ", {%96, %97, %98, %99}, db, p, 1, 1, %101;\n}\n"
                     : ACC96(C_O, d) : "r"(a[0]), "r"(a[1]), "r"(a[2]), "r"(a[3]), "r"(lb), "n"(TB), "n"(OB));
    else
        asm volatile("{\n.reg .pred p;\n.reg .b32 t;\n.reg .b64 db;\nsetp.ne.b32 p, 1, 0;\n"
                     MK_DESC("db", "%100", "%102")
                     "wgmma.mma_async.sync.aligned.m64n192k16.f32.bf16.bf16 " REGS96 ", {%96, %97, %98, %99}, db, p, 1, 1, %101;\n}\n"
                     : ACC96(C_IO, d) : "r"(a[0]), "r"(a[1]), "r"(a[2]), "r"(a[3]), "r"(lb), "n"(TB), "n"(OB));
}
template <bool First, int OB> __device__ __forceinline__ void wg64_rs(float (&d)[32], const uint32_t* a, uint32_t lb) {
    if constexpr (First)
        asm volatile("{\n.reg .pred p;\n.reg .b32 t;\n.reg .b64 db;\nsetp.ne.b32 p, 0, 0;\n"
                     MK_DESC("db", "%36", "%37")
                     "wgmma.mma_async.sync.aligned.m64n64k16.f32.bf16.bf16 " REGS32 ", {%32, %33, %34, %35}, db, p, 1, 1, 0;\n}\n"
                     : ACC32(C_O, d) : "r"(a[0]), "r"(a[1]), "r"(a[2]), "r"(a[3]), "r"(lb), "n"(OB));
    else
        asm volatile("{\n.reg .pred p;\n.reg .b32 t;\n.reg .b64 db;\nsetp.ne.b32 p, 1, 0;\n"
                     MK_DESC("db", "%36", "%37")
                     "wgmma.mma_async.sync.aligned.m64n64k16.f32.bf16.bf16 " REGS32 ", {%32, %33, %34, %35}, db, p, 1, 1, 0;\n}\n"
                     : ACC32(C_IO, d) : "r"(a[0]), "r"(a[1]), "r"(a[2]), "r"(a[3]), "r"(lb), "n"(OB));
}
template <bool First, int OA, int OB> __device__ __forceinline__ void wg64_ss(float (&d)[32], uint32_t la, uint32_t lb) {
    if constexpr (First)
        asm volatile("{\n.reg .pred p;\n.reg .b32 t;\n.reg .b64 da, db;\nsetp.ne.b32 p, 0, 0;\n"
                     MK_DESC("da", "%32", "%34") MK_DESC("db", "%33", "%35")
                     "wgmma.mma_async.sync.aligned.m64n64k16.f32.bf16.bf16 " REGS32 ", da, db, p, 1, 1, 0, 1;\n}\n"
                     : ACC32(C_O, d) : "r"(la), "r"(lb), "n"(OA), "n"(OB));
    else
        asm volatile("{\n.reg .pred p;\n.reg .b32 t;\n.reg .b64 da, db;\nsetp.ne.b32 p, 1, 0;\n"
                     MK_DESC("da", "%32", "%34") MK_DESC("db", "%33", "%35")
                     "wgmma.mma_async.sync.aligned.m64n64k16.f32.bf16.bf16 " REGS32 ", da, db, p, 1, 1, 0, 1;\n}\n"
                     : ACC32(C_IO, d) : "r"(la), "r"(lb), "n"(OA), "n"(OB));
}
__host__ __device__ constexpr int koff(int kk, int chunk) { return ((kk >> 2) * chunk + (kk & 3) * 32) >> 4; }

__device__ __forceinline__ uint32_t clock_now() {
    uint32_t t;
    asm volatile("mov.u32 %0, %%clock;" : "=r"(t));
    return t;
}
__device__ __forceinline__ void stage_put(const uint4* h, uint32_t buf) {
    const uint32_t t = tid_now();
    const uint32_t adr = buf + (t & 7) * 128 + ((((t >> 3) & 3) ^ (t & 7)) << 4);
#pragma unroll
    for (int i = 0; i < 4; i++)
        asm volatile("stmatrix.sync.aligned.m8n8.x4.shared.b16 [%4], {%0, %1, %2, %3};"
                     :: "r"(h[i].x), "r"(h[i].y), "r"(h[i].z), "r"(h[i].w), "r"((adr ^ ((i >> 1) << 6)) + (i & 1) * 1024) : "memory");
}
template <int N> __device__ __forceinline__ void stage_send(const CUtensorMap* tm, uint32_t pos, int k, uint32_t buf) {
    asm volatile("fence.proxy.async.shared::cta;" ::: "memory");
    __syncwarp();
    if (elect_one()) {
#pragma unroll
        for (int i = 0; i < N; i++)
            asm volatile("cp.async.bulk.tensor.4d.global.shared::cta.bulk_group [%0, {%2, %3, %4, %5}], [%1];"
                         ::"l"(tm), "r"(buf + i * 8192), "r"(0), "r"(pos & 0xffff), "r"(pos >> 16), "r"(k + i) : "memory");
        asm volatile("cp.async.bulk.commit_group;" ::: "memory");
    }
    __syncwarp();
}
__device__ __forceinline__ void stage_wait() {
    asm volatile("cp.async.bulk.wait_group.read 0;" ::: "memory");
    __syncwarp();
}
__device__ __forceinline__ uint32_t out_pos(int win) {
    return ((win & 63) * 8) | (((win >> 6) * 8 + 2 * ((tid_now() >> 5) & 3)) << 16);
}
__device__ __forceinline__ uint32_t stage_buf() { return kSmemBase + kOffStage + ((tid_now() >> 5) & 3) * 2048; }
__device__ __forceinline__ uint32_t tile_buf() { return kSmemBase + kOffX + (tid_now() >> 7) * kXBytes + ((tid_now() >> 5) & 3) * 2048; }
__device__ __forceinline__ void stage_window(uint4 (&h)[12], const CUtensorMap* tm, uint32_t pos, [[maybe_unused]] int win) {
#pragma unroll
    for (int k = 0; k < 3; k++) {
        if (k > 0) stage_wait();
        stage_put(h + 4 * k, stage_buf());
        stage_send<1>(tm, pos, k, stage_buf());
    }
}
template <int K0, int K> struct Gemm1 {
    static __device__ __forceinline__ void run(float (&d)[96], uint32_t lx, uint32_t lw) {
        if constexpr (K > K0) Gemm1<K0, K - 1>::run(d, lx, lw);
        wg192_ss<K == 0, koff(K, 8192), koff(K, 24576)>(d, lx, lw);
    }
};
__device__ __forceinline__ uint32_t draw_ticket(uint32_t* counter) {
    uint32_t ticket = 0;
    asm volatile("{\n.reg .pred p;\nsetp.eq.u32 p, %2, 0;\n@p atom.relaxed.gpu.global.inc.u32 %0, [%1], %3;\n}\n"
                 : "+r"(ticket) : "l"(counter), "r"(tid_now() & 127), "n"(kNWin - 1) : "memory");
    return ticket;
}
template <int KK> struct Gemm2 { static __device__ __forceinline__ void run(float (&d)[32], const uint32_t* a, uint32_t lx) {
    Gemm2<KK - 1>::run(d, a, lx); wg64_rs<KK == 0, koff(KK, 8192)>(d, a + 4 * KK, lx);
    if constexpr (KK == PASS2 && KK < 11) ring_pass(); } };
template <> struct Gemm2<-1> { static __device__ __forceinline__ void run(float (&)[32], const uint32_t*, uint32_t) {} };
template <int KK> struct Gemm3 { static __device__ __forceinline__ void run(float (&d)[96], const uint32_t* a, uint32_t lxt) {
    Gemm3<KK - 1>::run(d, a, lxt); wg192_rs<KK == 0, 1, KK * (2048 >> 4)>(d, a + 4 * KK, lxt);
    if constexpr (KK == PASS3 && KK < 3) ring_pass(); } };
template <> struct Gemm3<-1> { static __device__ __forceinline__ void run(float (&)[96], const uint32_t*, uint32_t) {} };
template <int K0, int KK> struct Gemm4 { static __device__ __forceinline__ void run(float (&d)[96], const uint32_t* a, uint32_t lw) {
    if constexpr (KK > K0) Gemm4<K0, KK - 1>::run(d, a, lw);
    wg192_rs<KK == 0, 0, koff(KK, 24576)>(d, a + 4 * KK, lw); } };

template <int J, int KK> struct Gemm3s { static __device__ __forceinline__ void run(float (&d)[32], uint32_t lp, uint32_t lxt) {
    if constexpr (KK > 0) Gemm3s<J, KK - 1>::run(d, lp, lxt);
    wg64_ss<KK == 0, KK * 2, (J * 8192 + KK * 2048) / 16>(d, lp, lxt); } };
template <int J, int K0, int KK> struct Gemm4s { static __device__ __forceinline__ void run(float (&d)[32], const uint32_t* a, uint32_t lw) {
    if constexpr (KK > K0) Gemm4s<J, K0, KK - 1>::run(d, a, lw);
    wg64_rs<KK == 0, koff(KK, 24576) + J * (8192 / 16)>(d, a + 4 * KK, lw); } };

__device__ __forceinline__ uint32_t pack_bf16(float lo, float hi) {
    uint32_t r;
    asm("cvt.rn.bf16x2.f32 %0, %1, %2;" : "=r"(r) : "f"(hi), "f"(lo));
    return r;
}
__device__ __forceinline__ float ex2(float x) {
    float r;
    asm("ex2.approx.ftz.f32 %0, %1;" : "=f"(r) : "f"(x));
    return r;
}
__device__ __forceinline__ float rcp(float x) {
    float r;
    asm("rcp.approx.ftz.f32 %0, %1;" : "=f"(r) : "f"(x));
    return r;
}

__device__ __forceinline__ void pack_slice(uint32_t* a, float (&d)[32]) {
    fence_regs(d);
#pragma unroll
    for (int i = 0; i < 16; i++) a[i] = pack_bf16(d[2 * i], d[2 * i + 1]);
#pragma unroll
    for (int i = 0; i < 16; i++) asm volatile("" : "+r"(a[i])::"memory");
}
__device__ __forceinline__ void put_slice(float (&d)[32], uint32_t buf) {
    fence_regs(d);
    uint4 h[4];
#pragma unroll
    for (int i = 0; i < 4; i++) {
        const int o = 16 * (i >> 1) + 2 * (i & 1);
        h[i] = make_uint4(pack_bf16(d[o], d[o + 1]), pack_bf16(d[o + 4], d[o + 5]), pack_bf16(d[o + 8], d[o + 9]), pack_bf16(d[o + 12], d[o + 13]));
    }
    stage_put(h, buf);
    __syncwarp();
}
__device__ __forceinline__ void count_finished() {
    if (((tid_now() >> 5) & 3) == 0) {
        if (elect_one()) {
            uint32_t nd;
            asm volatile("ld.shared.u32 %0, [%1];" : "=r"(nd) : "r"(kSmemBase + kOffBar + 80) : "memory");
            asm volatile("st.shared.v2.u32 [%0], {%1, %2};" ::"r"(kSmemBase + kOffBar + 80), "r"(nd + 1), "r"(tid_now() >> 7) : "memory");
        }
        __syncwarp();
    }
}
__device__ __forceinline__ void store_p_if(const uint32_t (&pa)[16], bool cond) {
    const uint32_t t = tid_now(), row = ((t >> 1) & 48) + (t & 15);
    const uint32_t adr = kSmemBase + kOffStage + row * 128 + ((((t >> 4) & 1) ^ (t & 7)) << 4);
#pragma unroll
    for (int i = 0; i < 4; i++)
        asm volatile("{\n.reg .pred p;\nsetp.ne.u32 p, %5, 0;\n@p stmatrix.sync.aligned.m8n8.x4.shared.b16 [%4], {%0, %1, %2, %3};\n}\n"
                     :: "r"(pa[4 * i]), "r"(pa[4 * i + 1]), "r"(pa[4 * i + 2]), "r"(pa[4 * i + 3]), "r"(adr ^ (i << 5)), "r"((uint32_t)cond) : "memory");
}
__device__ __forceinline__ void last_window(int win) {
    constexpr uint32_t dWv = ((kSmemBase + kOffWv) >> 4) | (1u << 16);
    asm volatile("fence.proxy.async.shared::cta;" ::: "memory");
    const uint32_t w = wg_uniform();
    const uint32_t dXt = desc_xt(w);
    constexpr uint32_t dP = ((kSmemBase + kOffStage) >> 4) | (1u << 16);
    float u0[32], u1[32], u2[32];
    uint32_t fa[48];
    uint32_t buf = tile_buf();
    asm volatile("st.shared.u32 [%0], %1;" ::"r"(kSmemBase + kOffBar + 104), "r"(win) : "memory");
    asm volatile("" : "+r"(buf) :: "memory");
    ring_wait();
    wg_fence();
    Gemm3s<0, 3>::run(u0, dP, dXt); wg_commit();
    Gemm3s<1, 3>::run(u1, dP, dXt); wg_commit();
    Gemm3s<2, 3>::run(u2, dP, dXt); wg_commit();
    count_finished();
    ring_pass();
    wg_wait2();
    pack_slice(fa, u0);
    __syncwarp();
    wg_wait1();
    pack_slice(fa + 16, u1);
    wg_fence();
    Gemm4s<0, 0, 7>::run(u0, fa, dWv); wg_commit();
    wg_wait1();
    pack_slice(fa + 32, u2);
    wg_fence();
    Gemm4s<0, 8, 11>::run(u0, fa, dWv); wg_commit();
    Gemm4s<1, 0, 5>::run(u1, fa, dWv); wg_commit();
    wg_wait1();
    asm volatile("bar.sync %0, 128;" ::"r"(w + 1) : "memory");
    put_slice(u0, buf);
    asm volatile("bar.arrive 12, 256;" ::: "memory");
    wg_fence();
    Gemm4s<1, 6, 11>::run(u1, fa, dWv); wg_commit();
    Gemm4s<2, 0, 5>::run(u2, fa, dWv); wg_commit();
    wg_wait1();
    put_slice(u1, buf + 8192);
    asm volatile("bar.arrive 13, 256;" ::: "memory");
    wg_fence();
    Gemm4s<2, 6, 11>::run(u2, fa, dWv); wg_commit();
    wg_wait0();
    fence_regs(fa);
    put_slice(u2, buf + 2 * 8192);
    asm volatile("bar.arrive 14, 256;" ::: "memory");
}

__device__ __forceinline__ int fold_offset(int n, int k0, int q) {
    const int u = ((k0 & 63) >> 3) + (q >> 1);
    return (k0 >> 6) * 24576 + (q & 1) * 8 + n * 128 + ((u ^ (n & 7)) << 4);
}
__device__ __forceinline__ void mma16816x2(float (&c)[4], float (&d)[4], const uint32_t (&a)[4], const uint32_t (&b)[4]) {
    asm volatile("mma.sync.aligned.m16n8k16.row.col.f32.bf16.bf16.f32 {%0,%1,%2,%3}, {%8,%9,%10,%11}, {%12,%13}, {%0,%1,%2,%3};\n"
                 "mma.sync.aligned.m16n8k16.row.col.f32.bf16.bf16.f32 {%4,%5,%6,%7}, {%8,%9,%10,%11}, {%14,%15}, {%4,%5,%6,%7};"
                 : "+f"(c[0]), "+f"(c[1]), "+f"(c[2]), "+f"(c[3]), "+f"(d[0]), "+f"(d[1]), "+f"(d[2]), "+f"(d[3])
                 : "r"(a[0]), "r"(a[1]), "r"(a[2]), "r"(a[3]), "r"(b[0]), "r"(b[1]), "r"(b[2]), "r"(b[3]));
}
__device__ __forceinline__ void cp_async16(uint32_t dst, const void* src) {
    asm volatile("cp.async.cg.shared.global [%0], [%1], 16;" ::"r"(dst), "l"(src) : "memory");
}
template <bool kTrans> __device__ __forceinline__ void ldsm4(uint32_t (&r)[4], uint32_t addr) {
    if constexpr (kTrans)
        asm volatile("ldmatrix.sync.aligned.m8n8.x4.trans.shared.b16 {%0, %1, %2, %3}, [%4];" : "=r"(r[0]), "=r"(r[1]), "=r"(r[2]), "=r"(r[3]) : "r"(addr) : "memory");
    else
        asm volatile("ldmatrix.sync.aligned.m8n8.x4.shared.b16 {%0, %1, %2, %3}, [%4];" : "=r"(r[0]), "=r"(r[1]), "=r"(r[2]), "=r"(r[3]) : "r"(addr) : "memory");
}
__device__ __forceinline__ uint32_t nonzero(uint32_t w) { return w ? w : 0x80000000u; }
__device__ __forceinline__ void fold_job(Scratch* sc, const __nv_bfloat16* __restrict__ wqkv, const __nv_bfloat16* __restrict__ wo,
                                         int job, int warp, int lane) {
    const bool vo = job >= kJobsM;
    const int nw = vo ? 3 : 2, tile0 = vo ? 3 * (job - kJobsM) : 2 * job;
    const int n0 = (tile0 / 12) * 16, k0 = (tile0 % 12 + max(warp, 1) - 1) * 16;
    const uint32_t stage = kSmemBase + kOffWv;
    if (warp <= nw) {
        if (vo && warp == 0) {
            const char* src = reinterpret_cast<const char*>(wo + (lane >> 1) * kC + n0 + (lane & 1) * 8);
            const uint32_t dst = stage + ((lane ^ ((lane >> 3) & 1)) << 4);
#pragma unroll
            for (int i = 0; i < 12; i++) cp_async16(dst + i * 512, src + i * 16 * kC * 2);
        } else {
            const int row0 = warp == 0 ? n0 : k0, col0 = warp == 0 ? kC : vo ? 2 * kC : 0;
            const char* src = reinterpret_cast<const char*>(wqkv + (row0 + (lane >> 3)) * (3 * kC) + col0 + (lane & 7) * 8);
            const uint32_t dst = stage + warp * 6144 + (lane >> 3) * 384 + (((lane & 7) ^ (lane >> 3)) << 4);
#pragma unroll
            for (int i = 0; i < 12; i++) cp_async16((dst ^ (((i / 3) & 1) << 6)) + (i / 3) * 1536 + (i % 3) * 128, src + (i / 3) * 4 * 3 * kC * 2 + (i % 3) * 128);
        }
        asm volatile("cp.async.wait_all;" ::: "memory");
        asm volatile("bar.sync 13, %0;" ::"r"(32 * nw + 32) : "memory");
    }
    if (warp == 0 || (warp > nw && warp != kWarmW)) return;
    const int g = lane >> 2, q = lane & 3, mi = lane >> 3, r8 = lane & 7;
    uint32_t A[12][4], B[12][4];
    {
        const int row = 4 * (r8 >> 1) + (r8 & 1) + 2 * (mi >> 1);
        const uint32_t base = stage + warp * 6144 + row * 384 + (((mi & 1) ^ (row & 7)) << 4);
#pragma unroll
        for (int ks = 0; ks < 12; ks++) ldsm4<false>(B[ks], (base ^ ((ks & 3) << 5)) + (ks >> 2) * 128);
    }
    if (vo) {
        const int c = r8 + 8 * (mi >> 1);
        const uint32_t base = stage + (((2 * c + (mi & 1)) ^ ((c >> 2) & 1)) << 4);
#pragma unroll
        for (int ks = 0; ks < 12; ks++) ldsm4<true>(A[ks], base + ks * 512);
    } else {
        const uint32_t base = stage + (r8 + 8 * (mi & 1)) * 384 + (((mi >> 1) ^ r8) << 4);
#pragma unroll
        for (int ks = 0; ks < 12; ks++) ldsm4<false>(A[ks], (base ^ ((ks & 3) << 5)) + (ks >> 2) * 128);
    }
    float c0[4] = {0.f, 0.f, 0.f, 0.f}, c1[4] = {0.f, 0.f, 0.f, 0.f}, c2[4] = {0.f, 0.f, 0.f, 0.f}, c3[4] = {0.f, 0.f, 0.f, 0.f};
#pragma unroll
    for (int ks = 0; ks < 12; ks += 2) {
        mma16816x2(c0, c1, A[ks], B[ks]);
        mma16816x2(c2, c3, A[ks + 1], B[ks + 1]);
    }
#pragma unroll
    for (int i = 0; i < 4; i++) { c0[i] += c2[i]; c1[i] += c3[i]; }
    const int n = n0 + g;
    char* img = reinterpret_cast<char*>(sc->wfold) + (vo ? kWBytes : 0);
    asm volatile("{\n.reg .pred p;\nsetp.ne.u32 p, %6, %7;\n@p st.global.v2.u32 [%0], {%2, %3};\n@p st.global.v2.u32 [%1], {%4, %5};\n}\n"
                 ::"l"(img + fold_offset(n, k0, q)), "l"(img + fold_offset(n + 8, k0, q)),
                   "r"(nonzero(pack_bf16(c0[0], c0[1]))), "r"(nonzero(pack_bf16(c1[0], c1[1]))), "r"(nonzero(pack_bf16(c0[2], c0[3]))), "r"(nonzero(pack_bf16(c1[2], c1[3]))),
                   "r"(warp), "n"(kWarmW) : "memory");
}

__device__ __forceinline__ bool bar_or(uint32_t id, uint32_t n, bool pred) {
    uint32_t r;
    asm volatile("{\n.reg .pred p, q;\nsetp.ne.u32 q, %3, 0;\nbar.red.or.pred p, %1, %2, q;\nselp.u32 %0, 1, 0, p;\n}\n"
                 : "=r"(r) : "r"(id), "r"(n), "r"((uint32_t)pred) : "memory");
    return r != 0;
}
__device__ __forceinline__ bool chunk_incomplete(uint32_t base) {
    const uint32_t t = tid_now(), r = (t >> 2) & 7;
    const uint32_t adr = base + (((t >> 5) & 3) * 48 + r) * 128 + (t & 3) * 32 + r * 4;
    uint32_t m = ~0u;
#pragma unroll
    for (int j = 0; j < 6; j++) {
        uint32_t v;
        asm volatile("ld.shared.u32 %0, [%1];" : "=r"(v) : "r"(adr + j * 1024) : "memory");
        m = min(m, v);
    }
    return m == 0;
}
__device__ __forceinline__ void load_image(uint32_t dst, const void* src, uint32_t bar) {
    mbar_expect_tx(bar, kWBytes);
#pragma unroll
    for (int c = 0; c < 3; c++) bulk_load(dst + c * 24576, reinterpret_cast<const char*>(src) + c * 24576, 24576, bar);
}
__device__ __forceinline__ void repair_image(uint32_t dst, const void* src, uint32_t bar, uint32_t par) {
    uint32_t tries = 0;
    bool bad;
    do {
        if (((tid_now() >> 5) & 3) == 0) {
            if (elect_one()) {
                asm volatile("fence.proxy.async;" ::: "memory");
                load_image(dst, src, bar);
            }
            __syncwarp();
        }
        mbar_wait(bar, par);
        par ^= 1;
        bad = chunk_incomplete(dst) | chunk_incomplete(dst + 24576) | chunk_incomplete(dst + 2 * 24576);
        if (++tries > (1u << 16)) __trap();
    } while (bar_or((tid_now() >> 7) + 1, 128, bad));
}
__device__ __forceinline__ void count_image(Scratch* sc) {
    asm volatile("red.relaxed.gpu.global.inc.u32 [%0], %1;" ::"l"(sc->cnt), "r"(3 * nctaid_now() - 1) : "memory");
}
__device__ __forceinline__ uint32_t ld_acquire(const uint32_t* p) {
    uint32_t v;
    asm volatile("ld.acquire.gpu.global.u32 %0, [%1];" : "=r"(v) : "l"(p) : "memory");
    return v;
}
__device__ __noinline__ void clear_images(Scratch* sc) {
    const uint32_t g = gridDim.x, t = threadIdx.x & 127;
    if (t == 0) {
        uint32_t spins = 0;
        while (ld_acquire(sc->cnt) < 2 * g) { if (++spins > (1u << 24)) __trap(); }
    }
    asm volatile("bar.sync %0, 128;" ::"r"((threadIdx.x >> 7) + 1) : "memory");
    for (uint32_t i = blockIdx.x * 64 + t; t < 64 && i < 2 * kWBytes / 16; i += g * 64) sc->wfold[i] = make_uint4(0, 0, 0, 0);
    if (t == 0) count_image(sc);
}
__device__ __forceinline__ void prefetch_x(const CUtensorMap* tm, int win) {
    const int wh = win >> 6, ww = win & 63;
    asm volatile("cp.async.bulk.prefetch.tensor.3d.L2.global.tile [%0, {%1, %2, %3}];"
                 ::"l"(tm), "r"(0), "r"(ww * 8), "r"(wh * 8) : "memory");
}
__device__ __forceinline__ void prefetch_x_chunk(const CUtensorMap* tm, int win, int chunk) {
    const int wh = win >> 6, ww = win & 63;
    asm volatile("cp.async.bulk.prefetch.tensor.4d.L2.global.tile [%0, {%1, %2, %3, %4}];"
                 ::"l"(tm), "r"(0), "r"(ww * 8), "r"(wh * 8), "r"(chunk) : "memory");
}

__device__ __forceinline__ void prefetch_for_ticket(const CUtensorMap* tmp, int t) {
    const int base = kNWG * (int)gridDim.x;
    auto lead = [&](int tt) {
        int down = max(((kNWin - base - tt) * PF_DOWN) >> 8, PF_MIN);
        return min(min((int)gridDim.x + ((tt * PF_UP) >> 8), PF_LEAD), down);
    };
    const int hi = base + t + lead(t);
    int lo = max(base + t - 1 + lead(t - 1), base + t) + 1;
#pragma unroll 1
    for (; lo <= hi && lo < kNWin; lo++) prefetch_x(tmp, lo);
}

template <bool kFewSMs>
__global__ void __launch_bounds__(kThreads, 1)
swin_attn_kernel(const __nv_bfloat16* __restrict__ wqkv, const __nv_bfloat16* __restrict__ wo, Scratch* sc, uint32_t* tickets,
                 const __grid_constant__ CUtensorMap tmx, const __grid_constant__ CUtensorMap tmp, const __grid_constant__ CUtensorMap tmc,
                 const __grid_constant__ CUtensorMap tmo) {
    extern __shared__ uint8_t smem_raw[];
    constexpr uint32_t sbase = kSmemBase;
    const uint32_t t_start = clock_now();
    asm volatile("{\n.reg .pred p, q;\n.reg .b32 i, j;\n.reg .b64 a, b;\nmad.lo.u32 i, %2, 14, %3;\nsetp.lt.u32 p, %3, 14;\nsetp.lt.and.u32 p, i, 1728, p;\n"
                 "mad.wide.u32 a, i, 128, %0;\n@p prefetch.global.L2 [a];\n"
                 "mad.lo.u32 j, %2, 5, %3;\nsetp.lt.u32 q, %3, 5;\nsetp.lt.and.u32 q, j, 576, q;\n"
                 "mad.wide.u32 b, j, 128, %1;\n@q prefetch.global.L2 [b];\n}\n" ::"l"(wqkv), "l"(wo), "r"(blockIdx.x), "r"(threadIdx.x) : "memory");
    if (smem_u32(smem_raw) != kSmemBase) __trap();
    const int tid = threadIdx.x, lane = tid & 31;
    const uint32_t warpu = __reduce_or_sync(0xffffffffu, (uint32_t)tid >> 5), wgu = warpu >> 2;
    const int warp = (int)warpu, wg = (int)wgu;
    const int G = gridDim.x;
    const uint32_t bar_full = sbase + kOffBar + 8 * wg;
    const uint32_t bar_w0 = sbase + kOffBar + 32, bar_w1 = bar_w0 + 8;
    int win = wg * G + blockIdx.x;

    if (warp > kWarmW) {
        if (warp == 10) {
            asm volatile("bar.sync 15, 64;" ::: "memory");
            asm volatile("bar.arrive 0, %0;" ::"n"(kThreads) : "memory");
            if (lane == 0) {
                asm volatile("prefetch.tensormap [%0];" ::"l"(&tmc) : "memory");
                asm volatile("prefetch.tensormap [%0];" ::"l"(&tmp) : "memory");
                asm volatile("prefetch.tensormap [%0];" ::"l"(&tmx) : "memory");
                const uint32_t due = (uint32_t)(blockIdx.x * TRK_S) / (uint32_t)G;
#pragma unroll 1
                for (int c = 0; c < 6; c++) {
                    while (clock_now() - t_start < TRK_T0 + (due + c * TRK_S) / 3) {}
                    if (c < 2) tma_load_x_chunk(sbase + kOffX + c * 8192, &tmc, bar_w0 + 16 * c, blockIdx.x, c);
                    else prefetch_x_chunk(&tmc, (c / 3) * G + blockIdx.x, c % 3);
                }
                while (clock_now() - t_start < TRK_T0 + due + 2 * TRK_S) {}
                prefetch_x(&tmp, 2 * G + blockIdx.x);
            }
            __syncwarp();
        } else if (warp == 11) {
            if (lane == 0) {
#pragma unroll
                for (int w = 0; w < kNWG; w++) mbar_init(sbase + kOffBar + 8 * w, 1);
                mbar_init(sbase + kOffBar + 24, 1);
                mbar_init(sbase + kOffBar + 88, 1);
                mbar_init(sbase + kOffBar + 96, 1);
                mbar_init(bar_w0, 1);
                mbar_init(bar_w1, 1);
                mbar_init(sbase + kOffBar + 48, 1);
                mbar_init(sbase + kOffBar + 56, 1);
                asm volatile("st.shared.v4.u32 [%0], {%1, %1, %1, %1};" ::"r"(sbase + kOffBar + 64), "r"(0) : "memory");
                asm volatile("st.shared.v2.u32 [%0], {%1, %1};" ::"r"(sbase + kOffBar + 80), "r"(0) : "memory");
                asm volatile("fence.mbarrier_init.release.cluster;" ::: "memory");
                asm volatile("mbarrier.arrive.shared::cta.b64 _, [%0];" ::"r"(sbase + kOffBar) : "memory");
            }
            __syncwarp();
            asm volatile("bar.arrive 15, 64;" ::: "memory");
            asm volatile("bar.arrive 0, %0;" ::"n"(kThreads) : "memory");
            if (elect_one()) {
                const char* img = reinterpret_cast<const char*>(sc->wfold);
#pragma unroll
                for (int c = 0; c < 3; c++) mbar_expect_tx(c == 0 ? bar_w0 : sbase + kOffBar + 40 + 8 * c, 24576 + 8192);
#pragma unroll
                for (int c = 0; c < 3; c++) mbar_expect_tx(sbase + kOffBar + (c == 0 ? 8 : 80 + 8 * c), 8192);
                while (clock_now() - t_start < REQ_T) {}
#pragma unroll
                for (int c = 0; c < 3; c++) {
                    const uint32_t bar = c == 0 ? bar_w0 : sbase + kOffBar + 40 + 8 * c;
                    if (c == 2) tma_load_x_chunk(sbase + kOffX + c * 8192, &tmc, bar, blockIdx.x, c);
                    bulk_load(sbase + kOffWm + c * 24576, img + c * 24576, 24576, bar);
                }
                mbar_wait(bar_w0, 0);
#pragma unroll
                for (int c = 0; c < 3; c++)
                    tma_load_x_chunk(sbase + kOffX + kXBytes + c * 8192, &tmc, sbase + kOffBar + (c == 0 ? 8 : 80 + 8 * c), G + blockIdx.x, c);
            }
            __syncwarp();
        } else {
            asm volatile("bar.sync 0, %0;" ::"n"(kThreads) : "memory");
            if (warp == 9) {
                if (elect_one()) {
                    while (clock_now() - t_start < REQ_TV) {}
                    mbar_wait(sbase + kOffBar + 48, 0);
                    asm volatile("fence.proxy.async.shared::cta;" ::: "memory");
                    load_image(sbase + kOffWv, reinterpret_cast<const char*>(sc->wfold) + kWBytes, bar_w1);
                    mbar_expect_tx(sbase + kOffBar + 16, kXBytes);
                    tma_load_x(sbase + kOffX + 2 * kXBytes, &tmx, sbase + kOffBar + 16, 2 * G + blockIdx.x);
                }
                __syncwarp();
            }
        }
    } else {
        if constexpr (kFewSMs) {
#pragma unroll 1
            for (int j = blockIdx.x; j < kJobs; j += G) {
                fold_job(sc, wqkv, wo, j, warp, lane);
                asm volatile("bar.sync 14, %0;" ::"n"(32 * kWarmW + 32) : "memory");
            }
        } else {
            if (blockIdx.x < kJobs) fold_job(sc, wqkv, wo, blockIdx.x, warp, lane);
        }
        asm volatile("bar.sync 0, %0;" ::"n"(kThreads) : "memory");
    }
    if (wg == kNWG - 1) asm volatile("bar.sync 7, 128;" ::: "memory");
    if (wg == 1) {
        mbar_wait(bar_w0, 0);
        bool bad = chunk_incomplete(sbase + kOffWm);
        mbar_wait(sbase + kOffBar + 48, 0);
        bad |= chunk_incomplete(sbase + kOffWm + 24576);
        mbar_wait(sbase + kOffBar + 56, 0);
        bad |= chunk_incomplete(sbase + kOffWm + 2 * 24576);
        asm volatile("bar.arrive 8, 256;" ::: "memory");
        if (bar_or(11, 256, bad)) {
            repair_image(sbase + kOffWm, sc->wfold, sbase + kOffBar + 24, 0);
            asm volatile("bar.arrive 11, 256;" ::: "memory");
        }
        if (tid == 128) count_image(sc);
    } else if (wg == 2) {
        mbar_wait(bar_w1, 0);
        const bool bad = chunk_incomplete(sbase + kOffWv) | chunk_incomplete(sbase + kOffWv + 24576) | chunk_incomplete(sbase + kOffWv + 2 * 24576);
        if (bar_or(3, 128, bad)) {
            repair_image(sbase + kOffWv, reinterpret_cast<const char*>(sc->wfold) + kWBytes, bar_w1, 1);
        }
        if (tid == 256) count_image(sc);
    }

    constexpr uint32_t dWm = ((sbase + kOffWm) >> 4) | (1u << 16);
    constexpr uint32_t dWv = ((sbase + kOffWv) >> 4) | (1u << 16);
    const float cs = 0.07216878364870322f * 1.4426950408889634f;
    mbar_wait(bar_w0, 0);
    mbar_wait(bar_full, 0);

    uint4 hv[12];
    uint32_t pos;
    uint32_t phase = 0;
    float acc[96];
    uint32_t ticket = 0;
    {
        const uint32_t dX = desc_x(wg_uniform());
        if (wg != 0) ring_wait();
        if (wg == 1) {
            __syncwarp();
            const uint32_t t1 = clock_now();
            while (clock_now() - t1 < G11_DELAY) {}
        }
        wg_fence();
        Gemm1<0, 3>::run(acc, dX, dWm);
        const uint32_t bar_c1 = sbase + kOffBar + (wg == 1 ? 88 : 48);
        mbar_wait(bar_c1, 0);
        wg_fence();
        Gemm1<4, 7>::run(acc, dX, dWm);
        mbar_wait(bar_c1 + 8, 0);
        wg_fence();
        Gemm1<8, 11>::run(acc, dX, dWm);
        wg_commit();
        if (wg != 0) asm volatile("bar.arrive 8, 256;" ::: "memory");
        if (warp == 5) {
            if (elect_one()) prefetch_x(&tmp, kNWG * G + blockIdx.x);
            __syncwarp();
        }
        ticket = draw_ticket(tickets);
        const bool redo = wg == 0 && bar_or(11, 256, false);
        wg_wait0();
        if (redo) {
            asm volatile("bar.sync 11, 256;" ::: "memory");
            wg_fence();
            Gemm1<0, 11>::run(acc, dX, dWm);
            wg_commit();
            wg_wait0();
        }
        __syncwarp();
    }

    while (true) {
        uint32_t fa[48];
        const uint32_t dX = desc_x(wg_uniform());
        fence_regs(acc);
#pragma unroll
        for (int i = 0; i < 48; i++) fa[i] = pack_bf16(acc[2 * i], acc[2 * i + 1]);

        float s[32];
        fence_regs(fa);
        wg_fence();
        ring_wait();
        Gemm2<11>::run(s, fa, dX);
        wg_commit();
        if constexpr (PASS2 == 11) ring_pass();
        if (((tid_now() >> 5) & 3) == 0) {
            if ((tid_now() & 31) == 0) {
                uint32_t nxt = kNWG * nctaid_now() + ticket;
                if (nxt >= kNWin) {
                    uint32_t p0, p1, p2, p3;
                    asm volatile("ld.shared.v4.u32 {%0, %1, %2, %3}, [%4];" : "=r"(p0), "=r"(p1), "=r"(p2), "=r"(p3) : "r"(sbase + kOffBar + 64) : "memory");
                    if ((p0 >= kNWin) + (p1 >= kNWin) + (p2 >= kNWin) == kNWG - 1) nxt = kLastOfCta;
                }
                asm volatile("st.shared.u32 [%0], %1;" ::"r"(sbase + kOffBar + 64 + 4 * (tid_now() >> 7)), "r"(nxt) : "memory");
            }
            __syncwarp();
            asm volatile("bar.arrive %0, 128;" ::"r"((tid_now() >> 7) + 4) : "memory");
        }
        asm volatile("cp.async.bulk.wait_group.read 0;" ::: "memory");
        asm volatile("bar.arrive 15, 256;" ::: "memory");
        wg_wait0();
        fence_regs(s);
        fence_regs(fa);

        uint32_t pa[16];
        {
            float a0[8], a1[8];
#pragma unroll
            for (int j = 0; j < 8; j++) { a0[j] = fmaxf(s[4 * j], s[4 * j + 1]); a1[j] = fmaxf(s[4 * j + 2], s[4 * j + 3]); }
#pragma unroll
            for (int d = 4; d > 0; d >>= 1)
#pragma unroll
                for (int j = 0; j < d; j++) { a0[j] = fmaxf(a0[j], a0[j + d]); a1[j] = fmaxf(a1[j], a1[j + d]); }
            float m0 = a0[0], m1 = a1[0];
            m0 = fmaxf(m0, __shfl_xor_sync(0xffffffffu, m0, 1));
            m1 = fmaxf(m1, __shfl_xor_sync(0xffffffffu, m1, 1));
            m0 = fmaxf(m0, __shfl_xor_sync(0xffffffffu, m0, 2));
            m1 = fmaxf(m1, __shfl_xor_sync(0xffffffffu, m1, 2));
            m0 *= cs; m1 *= cs;
            float l0 = 0.f, l1 = 0.f;
#pragma unroll
            for (int j = 0; j < 8; j++) {
                s[4 * j]     = ex2(fmaf(s[4 * j], cs, -m0));
                s[4 * j + 1] = ex2(fmaf(s[4 * j + 1], cs, -m0));
                s[4 * j + 2] = ex2(fmaf(s[4 * j + 2], cs, -m1));
                s[4 * j + 3] = ex2(fmaf(s[4 * j + 3], cs, -m1));
                l0 += s[4 * j] + s[4 * j + 1];
                l1 += s[4 * j + 2] + s[4 * j + 3];
            }
            l0 += __shfl_xor_sync(0xffffffffu, l0, 1);
            l1 += __shfl_xor_sync(0xffffffffu, l1, 1);
            l0 += __shfl_xor_sync(0xffffffffu, l0, 2);
            l1 += __shfl_xor_sync(0xffffffffu, l1, 2);
            const float r0 = rcp(l0), r1 = rcp(l1);
#pragma unroll
            for (int j = 0; j < 8; j++) {
                pa[2 * j]     = pack_bf16(s[4 * j] * r0, s[4 * j + 1] * r0);
                pa[2 * j + 1] = pack_bf16(s[4 * j + 2] * r1, s[4 * j + 3] * r1);
            }
        }

        const uint32_t dXt = desc_xt(wg_uniform());
        if (((tid_now() >> 5) & 3) != 0) asm volatile("bar.sync %0, 128;" ::"r"((tid_now() >> 7) + 4) : "memory");
        uint32_t pub;
        asm volatile("ld.shared.u32 %0, [%1];" : "=r"(pub) : "r"(sbase + kOffBar + 64 + 4 * (tid_now() >> 7)) : "memory");
        const int nxt = (int)__reduce_or_sync(0xffffffffu, pub);
        store_p_if(pa, nxt == (int)kLastOfCta);
        if (nxt == (int)kLastOfCta) {
            last_window(win);
            asm volatile("exit;");
            __builtin_unreachable();
        }
        fence_regs(pa);
        wg_fence();
        ring_wait();
        Gemm3<3>::run(acc, pa, dXt);
        wg_commit();
        if constexpr (PASS3 == 3) ring_pass();
        wg_wait0();
        fence_regs(acc);
        fence_regs(pa);

        if (((tid_now() >> 5) & 3) == 0) {
            asm volatile("bar.sync %0, 128;" ::"r"((tid_now() >> 7) + 1) : "memory");
            if (elect_one()) {
                const uint32_t wgl = tid_now() >> 7;
                const uint32_t bar = sbase + kOffBar + 8 * wgl;
                if (nxt < kNWin) {
                    mbar_expect_tx(bar, kXBytes);
                    tma_load_x_hint(sbase + kOffX + wgl * kXBytes, &tmx, bar, nxt, nxt >= kNWin - EF_LAST);
                    uint32_t again;
                    asm volatile("ld.volatile.shared.u32 %0, [%1];" : "=r"(again) : "r"(sbase + kOffBar + 64 + 4 * wgl) : "memory");
                    prefetch_for_ticket(&tmp, (int)again - kNWG * (int)gridDim.x);
                }
            }
            __syncwarp();
        } else {
            asm volatile("bar.arrive %0, 128;" ::"r"((tid_now() >> 7) + 1) : "memory");
        }
#pragma unroll
        for (int i = 0; i < 48; i++) fa[i] = pack_bf16(acc[2 * i], acc[2 * i + 1]);

        asm volatile("st.volatile.shared.v4.b32 [%4], {%0, %1, %2, %3};"
                     :: "r"(fa[44]), "r"(fa[45]), "r"(fa[46]), "r"(fa[47]), "r"(sbase + kOffStash + (tid_now() & 127) * 16) : "memory");
        fence_regs(fa);
        wg_fence();
        ring_wait();
        Gemm4<0, 1>::run(acc, fa, dWv);
        wg_commit();
        Gemm4<2, 10>::run(acc, fa, dWv);
        wg_commit();
        wg_wait1();
        uint32_t fl[4];
        asm volatile("ld.volatile.shared.v4.b32 {%0, %1, %2, %3}, [%4];"
                     : "=r"(fl[0]), "=r"(fl[1]), "=r"(fl[2]), "=r"(fl[3]) : "r"(sbase + kOffStash + (tid_now() & 127) * 16) : "memory");
        wg_fence();
        wg192_rs<false, 0, koff(11, 24576)>(acc, fl, dWv);
        wg_commit();
        if (nxt >= kNWin) count_finished();
        ring_pass();
        pos = out_pos(win);
        win = nxt;
        const uint32_t dX1 = desc_x(wg_uniform());
        phase ^= 1;
        if (win < kNWin) mbar_wait(sbase + kOffBar + 8 * (tid_now() >> 7), phase);
        asm volatile("" : "+r"(pos) :: "memory");
        wg_wait0();
        fence_regs(acc);
        fence_regs(fa);
        fence_regs(fl);

#pragma unroll
        for (int a = 0; a < 6; a++) {
            hv[2 * a].x     = pack_bf16(acc[16 * a + 0], acc[16 * a + 1]);
            hv[2 * a].y     = pack_bf16(acc[16 * a + 4], acc[16 * a + 5]);
            hv[2 * a].z     = pack_bf16(acc[16 * a + 8], acc[16 * a + 9]);
            hv[2 * a].w     = pack_bf16(acc[16 * a + 12], acc[16 * a + 13]);
            hv[2 * a + 1].x = pack_bf16(acc[16 * a + 2], acc[16 * a + 3]);
            hv[2 * a + 1].y = pack_bf16(acc[16 * a + 6], acc[16 * a + 7]);
            hv[2 * a + 1].z = pack_bf16(acc[16 * a + 10], acc[16 * a + 11]);
            hv[2 * a + 1].w = pack_bf16(acc[16 * a + 14], acc[16 * a + 15]);
        }
        if (win >= kNWin) break;
        wg_fence();
        ring_wait();
        Gemm1<0, 11>::run(acc, dX1, dWm);
        wg_commit();
        ring_pass();
        ticket = draw_ticket(tickets);
        asm volatile("bar.sync 15, 256;" ::: "memory");
        stage_window(hv, &tmo, pos, win);
        wg_wait0();
    }
    {
        const uint32_t me = tid_now() >> 7, nx = me == kNWG - 1 ? 0 : me + 1;
        uint32_t nd, last;
        asm volatile("bar.sync %0, 128;" ::"r"(me + 1) : "memory");
        asm volatile("ld.volatile.shared.u32 %0, [%1];" : "=r"(nd) : "r"(sbase + kOffBar + 80) : "memory");
        const bool first = nd == 1;
#pragma unroll
        for (int k = 0; k < 3; k++) stage_put(hv + 4 * k, tile_buf() + k * 8192);
        if (first) { ring_wait(); ring_pass(); }
        stage_send<3>(&tmo, pos, 0, tile_buf());
        do {
            ring_wait();
            asm volatile("ld.volatile.shared.v2.u32 {%0, %1}, [%2];" : "=r"(nd), "=r"(last) : "r"(sbase + kOffBar + 80) : "memory");
            if (nd != kNWG || nx != last) ring_pass();
        } while (nd != kNWG);
        if (first) {
            asm volatile("bar.sync 15, 256;" ::: "memory");
        } else {
            const uint32_t buf = sbase + kOffX + last * kXBytes + ((tid_now() >> 5) & 3) * 2048;
            asm volatile("bar.sync 12, 256;" ::: "memory");
            uint32_t lw;
            asm volatile("ld.volatile.shared.u32 %0, [%1];" : "=r"(lw) : "r"(sbase + kOffBar + 104) : "memory");
            pos = out_pos(lw);
            stage_send<1>(&tmo, pos, 0, buf);
            asm volatile("bar.sync 13, 256;" ::: "memory");
            stage_send<1>(&tmo, pos, 1, buf + 8192);
            asm volatile("bar.sync 14, 256;" ::: "memory");
            stage_send<1>(&tmo, pos, 2, buf + 2 * 8192);
        }
        stage_wait();
        if (first) clear_images(sc);
    }
}

typedef CUresult (*EncodeTiledFn)(CUtensorMap*, CUtensorMapDataType, cuuint32_t, void*, const cuuint64_t*,
                                  const cuuint64_t*, const cuuint32_t*, const cuuint32_t*, CUtensorMapInterleave,
                                  CUtensorMapSwizzle, CUtensorMapL2promotion, CUtensorMapFloatOOBfill);

}

extern "C" void kernel_launch(void* const* d_in, const int* in_sizes, int n_in, void* d_out, int out_size) {
    (void)in_sizes; (void)n_in; (void)out_size;
    const __nv_bfloat16* x    = (const __nv_bfloat16*)d_in[0];
    const __nv_bfloat16* wqkv = (const __nv_bfloat16*)d_in[1];
    const __nv_bfloat16* wo   = (const __nv_bfloat16*)d_in[2];

    static EncodeTiledFn encode = nullptr;
    static int num_sms = 0;
    static void* scratch = nullptr;
    if (!encode) {
        void* fn = nullptr;
        cudaDriverEntryPointQueryResult qr;
        cudaGetDriverEntryPoint("cuTensorMapEncodeTiled", &fn, cudaEnableDefault, &qr);
        encode = (EncodeTiledFn)fn;
        int dev = 0;
        cudaGetDevice(&dev);
        cudaDeviceGetAttribute(&num_sms, cudaDevAttrMultiProcessorCount, dev);
        cudaGetSymbolAddress(&scratch, g_scratch);
        cudaFuncSetAttribute(swin_attn_kernel<false>, cudaFuncAttributeMaxDynamicSharedMemorySize, kSmemBytes);
        cudaFuncSetAttribute(swin_attn_kernel<true>, cudaFuncAttributeMaxDynamicSharedMemorySize, kSmemBytes);
    }
    CUtensorMap tmx;
    const cuuint64_t gdim[4] = {64, (cuuint64_t)kHW, (cuuint64_t)kHW, 3};
    const cuuint64_t gstr[3] = {(cuuint64_t)kC * 2, (cuuint64_t)kHW * kC * 2, 128};
    const cuuint32_t box[4] = {64, 8, 8, 3};
    const cuuint32_t estr[4] = {1, 1, 1, 1};
    encode(&tmx, CU_TENSOR_MAP_DATA_TYPE_BFLOAT16, 4, (void*)x, gdim, gstr, box, estr, CU_TENSOR_MAP_INTERLEAVE_NONE,
           CU_TENSOR_MAP_SWIZZLE_128B, CU_TENSOR_MAP_L2_PROMOTION_NONE, CU_TENSOR_MAP_FLOAT_OOB_FILL_NONE);

    CUtensorMap tmp;
    const cuuint64_t pdim[3] = {(cuuint64_t)kC, (cuuint64_t)kHW, (cuuint64_t)kHW};
    const cuuint64_t pstr[2] = {(cuuint64_t)kC * 2, (cuuint64_t)kHW * kC * 2};
    const cuuint32_t pbox[3] = {(cuuint32_t)kC, 8, 8};
    encode(&tmp, CU_TENSOR_MAP_DATA_TYPE_BFLOAT16, 3, (void*)x, pdim, pstr, pbox, estr, CU_TENSOR_MAP_INTERLEAVE_NONE,
           CU_TENSOR_MAP_SWIZZLE_NONE, CU_TENSOR_MAP_L2_PROMOTION_NONE, CU_TENSOR_MAP_FLOAT_OOB_FILL_NONE);
    CUtensorMap tmc;
    const cuuint32_t boxc[4] = {64, 8, 8, 1};
    encode(&tmc, CU_TENSOR_MAP_DATA_TYPE_BFLOAT16, 4, (void*)x, gdim, gstr, boxc, estr, CU_TENSOR_MAP_INTERLEAVE_NONE,
           CU_TENSOR_MAP_SWIZZLE_128B, CU_TENSOR_MAP_L2_PROMOTION_NONE, CU_TENSOR_MAP_FLOAT_OOB_FILL_NONE);
    CUtensorMap tmo;
    const cuuint32_t boxo[4] = {64, 8, 2, 1};
    encode(&tmo, CU_TENSOR_MAP_DATA_TYPE_BFLOAT16, 4, d_out, gdim, gstr, boxo, estr, CU_TENSOR_MAP_INTERLEAVE_NONE,
           CU_TENSOR_MAP_SWIZZLE_128B, CU_TENSOR_MAP_L2_PROMOTION_NONE, CU_TENSOR_MAP_FLOAT_OOB_FILL_NONE);
    if (num_sms >= kJobs)
        swin_attn_kernel<false><<<num_sms, kThreads, kSmemBytes, cudaStreamPerThread>>>(wqkv, wo, (Scratch*)scratch, ((Scratch*)scratch)->ticket, tmx, tmp, tmc, tmo);
    else
        swin_attn_kernel<true><<<num_sms, kThreads, kSmemBytes, cudaStreamPerThread>>>(wqkv, wo, (Scratch*)scratch, ((Scratch*)scratch)->ticket, tmx, tmp, tmc, tmo);
}
```

```cpp
#include <cuda_runtime.h>
#include <cuda_bf16.h>
#include <cuda.h>
#include <stdint.h>

namespace {

constexpr int kC      = 192;
constexpr int kHW     = 512;
#define MAXWIN 4096
constexpr int kNWin   = MAXWIN;
constexpr int kXBytes = 64 * kC * 2;
constexpr int kWBytes = kC * kC * 2;
constexpr int kNWG    = 3;
constexpr int kThreads = kNWG * 128;
constexpr int kJobsM  = 72;
constexpr int kJobs   = 120;
constexpr int kWarmW  = 4;
#define PF_LEAD 400
#define PF_UP 114
#define PF_DOWN 39
#define PF_END 300
#define PF_MIN 135
#define EF_LAST 1000
#define TRK_T0 400
#define TRK_S 1800
#define G11_DELAY 100
#define REQ_T 2650
#define REQ_TV 4000

constexpr int kOffWm  = 0;
constexpr int kOffWv  = kWBytes;
constexpr int kOffX   = 2 * kWBytes;
constexpr int kOffStage = kOffX + kNWG * kXBytes;
constexpr int kOffBar = kOffStage + 8192;
constexpr int kOffProf = kOffBar + 128;
constexpr int kSmemBytes = kOffProf;
constexpr uint32_t kSmemBase = 1024;

struct Scratch {
    uint4 wfold[2 * kWBytes / 16];
    uint32_t ticket[32];
    uint32_t cnt[32];
};
__device__ __align__(128) Scratch g_scratch;

__device__ __forceinline__ uint32_t smem_u32(const void* p) { return (uint32_t)__cvta_generic_to_shared(p); }

__device__ __forceinline__ void mbar_init(uint32_t bar, uint32_t count) {
    asm volatile("mbarrier.init.shared::cta.b64 [%0], %1;" ::"r"(bar), "r"(count) : "memory");
}
__device__ __forceinline__ void mbar_expect_tx(uint32_t bar, uint32_t bytes) {
    asm volatile("mbarrier.arrive.expect_tx.shared::cta.b64 _, [%0], %1;" ::"r"(bar), "r"(bytes) : "memory");
}
__device__ __forceinline__ void mbar_wait(uint32_t bar, uint32_t parity) {
    uint32_t ok;
    uint32_t spins = 0;
    do {
        asm volatile("{\n.reg .pred p;\n"
                     "mbarrier.try_wait.parity.shared::cta.b64 p, [%1], %2;\n"
                     "selp.b32 %0, 1, 0, p;\n}\n"
                     : "=r"(ok) : "r"(bar), "r"(parity) : "memory");
        if (++spins > (1u << 26)) __trap();
    } while (!ok);
}
__device__ __forceinline__ uint32_t tid_now() {
    uint32_t t;
    asm volatile("mov.u32 %0, %%tid.x;" : "=r"(t));
    return t;
}
__device__ __forceinline__ uint32_t nctaid_now() {
    uint32_t t;
    asm volatile("mov.u32 %0, %%nctaid.x;" : "=r"(t));
    return t;
}
__device__ __forceinline__ bool elect_one() {
    uint32_t pred;
    asm volatile("{\n.reg .pred p;\nelect.sync _|p, 0xffffffff;\nselp.b32 %0, 1, 0, p;\n}\n" : "=r"(pred));
    return pred != 0;
}
#define PASS2 5
#define PASS3 3
__device__ __forceinline__ void ring_wait() {
    asm volatile("bar.sync %0, 256;" ::"r"((tid_now() >> 7) + 8) : "memory");
}
__device__ __forceinline__ void ring_pass() {
    const uint32_t w = tid_now() >> 7;
    asm volatile("bar.arrive %0, 256;" ::"r"(w == kNWG - 1 ? 8u : w + 9u) : "memory");
}
constexpr uint32_t kDone = 0x40000000u;
__device__ __forceinline__ uint32_t wg_uniform() { return __reduce_or_sync(0xffffffffu, tid_now() >> 7); }
__device__ __forceinline__ uint32_t desc_x(uint32_t w) { return (((kSmemBase + kOffX) >> 4) | (1u << 16)) + w * (kXBytes >> 4); }
__device__ __forceinline__ uint32_t desc_xt(uint32_t w) { return (((kSmemBase + kOffX) >> 4) | ((8192u >> 4) << 16)) + w * (kXBytes >> 4); }
__device__ __forceinline__ void tma_load_x(uint32_t dst, const CUtensorMap* tm, uint32_t bar, int win) {
    const int wh = win >> 6, ww = win & 63;
    asm volatile("cp.async.bulk.tensor.4d.shared::cluster.global.mbarrier::complete_tx::bytes"
                 " [%0], [%1, {%3, %4, %5, %6}], [%2];"
                 ::"r"(dst), "l"(tm), "r"(bar), "r"(0), "r"(ww * 8), "r"(wh * 8), "r"(0) : "memory");
}
__device__ __forceinline__ void tma_load_x_hint(uint32_t dst, const CUtensorMap* tm, uint32_t bar, int win, bool evict_first) {
    const int wh = win >> 6, ww = win & 63;
    uint64_t first, normal;
    asm("createpolicy.fractional.L2::evict_first.b64 %0, 1.0;" : "=l"(first));
    asm("createpolicy.fractional.L2::evict_normal.b64 %0, 1.0;" : "=l"(normal));
    asm volatile("cp.async.bulk.tensor.4d.shared::cluster.global.mbarrier::complete_tx::bytes.L2::cache_hint"
                 " [%0], [%1, {%3, %4, %5, %6}], [%2], %7;"
                 ::"r"(dst), "l"(tm), "r"(bar), "r"(0), "r"(ww * 8), "r"(wh * 8), "r"(0), "l"(evict_first ? first : normal) : "memory");
}
__device__ __forceinline__ void tma_load_x_chunk(uint32_t dst, const CUtensorMap* tm, uint32_t bar, int win, int chunk) {
    const int wh = win >> 6, ww = win & 63;
    asm volatile("cp.async.bulk.tensor.4d.shared::cluster.global.mbarrier::complete_tx::bytes"
                 " [%0], [%1, {%3, %4, %5, %6}], [%2];"
                 ::"r"(dst), "l"(tm), "r"(bar), "r"(0), "r"(ww * 8), "r"(wh * 8), "r"(chunk) : "memory");
}
__device__ __forceinline__ void bulk_load(uint32_t dst, const void* src, uint32_t bytes, uint32_t bar) {
    asm volatile("cp.async.bulk.shared::cluster.global.mbarrier::complete_tx::bytes [%0], [%1], %2, [%3];"
                 ::"r"(dst), "l"(src), "r"(bytes), "r"(bar) : "memory");
}

__device__ __forceinline__ void wg_fence()  { asm volatile("wgmma.fence.sync.aligned;" ::: "memory"); }
__device__ __forceinline__ void wg_commit() { asm volatile("wgmma.commit_group.sync.aligned;" ::: "memory"); }
__device__ __forceinline__ void wg_wait0()  { asm volatile("wgmma.wait_group.sync.aligned 0;" ::: "memory"); }
__device__ __forceinline__ void wg_wait1()  { asm volatile("wgmma.wait_group.sync.aligned 1;" ::: "memory"); }
__device__ __forceinline__ void wg_wait2()  { asm volatile("wgmma.wait_group.sync.aligned 2;" ::: "memory"); }

template <int N> __device__ __forceinline__ void fence_regs(float (&d)[N]) {
#pragma unroll
    for (int i = 0; i < N; i++) asm volatile("" : "+f"(d[i])::"memory");
}
template <int N> __device__ __forceinline__ void fence_regs(uint32_t (&d)[N]) {
#pragma unroll
    for (int i = 0; i < N; i++) asm volatile("" : "+r"(d[i])::"memory");
}

#define ACC8(c, d, i) c(d[i]), c(d[i + 1]), c(d[i + 2]), c(d[i + 3]), c(d[i + 4]), c(d[i + 5]), c(d[i + 6]), c(d[i + 7])
#define ACC32(c, d) ACC8(c, d, 0), ACC8(c, d, 8), ACC8(c, d, 16), ACC8(c, d, 24)
#define ACC96(c, d) ACC32(c, d), ACC8(c, d, 32), ACC8(c, d, 40), ACC8(c, d, 48), ACC8(c, d, 56), \
                    ACC8(c, d, 64), ACC8(c, d, 72), ACC8(c, d, 80), ACC8(c, d, 88)
#define C_IO(x) "+f"(x)
#define C_O(x) "=f"(x)
#define REGS32 "{%0, %1, %2, %3, %4, %5, %6, %7, %8, %9, %10, %11, %12, %13, %14, %15, " \
               "%16, %17, %18, %19, %20, %21, %22, %23, %24, %25, %26, %27, %28, %29, %30, %31}"
#define REGS96 "{%0, %1, %2, %3, %4, %5, %6, %7, %8, %9, %10, %11, %12, %13, %14, %15, " \
               "%16, %17, %18, %19, %20, %21, %22, %23, %24, %25, %26, %27, %28, %29, %30, %31, " \
               "%32, %33, %34, %35, %36, %37, %38, %39, %40, %41, %42, %43, %44, %45, %46, %47, " \
               "%48, %49, %50, %51, %52, %53, %54, %55, %56, %57, %58, %59, %60, %61, %62, %63, " \
               "%64, %65, %66, %67, %68, %69, %70, %71, %72, %73, %74, %75, %76, %77, %78, %79, " \
               "%80, %81, %82, %83, %84, %85, %86, %87, %88, %89, %90, %91, %92, %93, %94, %95}"

#define DESC_HI "0x40000040"
#define MK_DESC(name, lo, off) "add.u32 t, " lo ", " off ";\nmov.b64 " name ", {t, " DESC_HI "};\n"

template <bool First, int OA, int OB> __device__ __forceinline__ void wg192_ss(float (&d)[96], uint32_t la, uint32_t lb) {
    if constexpr (First)
        asm volatile("{\n.reg .pred p;\n.reg .b32 t;\n.reg .b64 da, db;\nsetp.ne.b32 p, 0, 0;\n"
                     MK_DESC("da", "%96", "%98") MK_DESC("db", "%97", "%99")
                     "wgmma.mma_async.sync.aligned.m64n192k16.f32.bf16.bf16 " REGS96 ", da, db, p, 1, 1, 0, 0;\n}\n"
                     : ACC96(C_O, d) : "r"(la), "r"(lb), "n"(OA), "n"(OB));
    else
        asm volatile("{\n.reg .pred p;\n.reg .b32 t;\n.reg .b64 da, db;\nsetp.ne.b32 p, 1, 0;\n"
                     MK_DESC("da", "%96", "%98") MK_DESC("db", "%97", "%99")
                     "wgmma.mma_async.sync.aligned.m64n192k16.f32.bf16.bf16 " REGS96 ", da, db, p, 1, 1, 0, 0;\n}\n"
                     : ACC96(C_IO, d) : "r"(la), "r"(lb), "n"(OA), "n"(OB));
}
template <bool First, int TB, int OB> __device__ __forceinline__ void wg192_rs(float (&d)[96], const uint32_t* a, uint32_t lb) {
    if constexpr (First)
        asm volatile("{\n.reg .pred p;\n.reg .b32 t;\n.reg .b64 db;\nsetp.ne.b32 p, 0, 0;\n"
                     MK_DESC("db", "%100", "%102")
                     "wgmma.mma_async.sync.aligned.m64n192k16.f32.bf16.bf16 " REGS96 ", {%96, %97, %98, %99}, db, p, 1, 1, %101;\n}\n"
                     : ACC96(C_O, d) : "r"(a[0]), "r"(a[1]), "r"(a[2]), "r"(a[3]), "r"(lb), "n"(TB), "n"(OB));
    else
        asm volatile("{\n.reg .pred p;\n.reg .b32 t;\n.reg .b64 db;\nsetp.ne.b32 p, 1, 0;\n"
                     MK_DESC("db", "%100", "%102")
                     "wgmma.mma_async.sync.aligned.m64n192k16.f32.bf16.bf16 " REGS96 ", {%96, %97, %98, %99}, db, p, 1, 1, %101;\n}\n"
                     : ACC96(C_IO, d) : "r"(a[0]), "r"(a[1]), "r"(a[2]), "r"(a[3]), "r"(lb), "n"(TB), "n"(OB));
}
template <bool First, int OB> __device__ __forceinline__ void wg64_rs(float (&d)[32], const uint32_t* a, uint32_t lb) {
    if constexpr (First)
        asm volatile("{\n.reg .pred p;\n.reg .b32 t;\n.reg .b64 db;\nsetp.ne.b32 p, 0, 0;\n"
                     MK_DESC("db", "%36", "%37")
                     "wgmma.mma_async.sync.aligned.m64n64k16.f32.bf16.bf16 " REGS32 ", {%32, %33, %34, %35}, db, p, 1, 1, 0;\n}\n"
                     : ACC32(C_O, d) : "r"(a[0]), "r"(a[1]), "r"(a[2]), "r"(a[3]), "r"(lb), "n"(OB));
    else
        asm volatile("{\n.reg .pred p;\n.reg .b32 t;\n.reg .b64 db;\nsetp.ne.b32 p, 1, 0;\n"
                     MK_DESC("db", "%36", "%37")
                     "wgmma.mma_async.sync.aligned.m64n64k16.f32.bf16.bf16 " REGS32 ", {%32, %33, %34, %35}, db, p, 1, 1, 0;\n}\n"
                     : ACC32(C_IO, d) : "r"(a[0]), "r"(a[1]), "r"(a[2]), "r"(a[3]), "r"(lb), "n"(OB));
}
template <bool First, int OA, int OB> __device__ __forceinline__ void wg64_ss(float (&d)[32], uint32_t la, uint32_t lb) {
    if constexpr (First)
        asm volatile("{\n.reg .pred p;\n.reg .b32 t;\n.reg .b64 da, db;\nsetp.ne.b32 p, 0, 0;\n"
                     MK_DESC("da", "%32", "%34") MK_DESC("db", "%33", "%35")
                     "wgmma.mma_async.sync.aligned.m64n64k16.f32.bf16.bf16 " REGS32 ", da, db, p, 1, 1, 0, 1;\n}\n"
                     : ACC32(C_O, d) : "r"(la), "r"(lb), "n"(OA), "n"(OB));
    else
        asm volatile("{\n.reg .pred p;\n.reg .b32 t;\n.reg .b64 da, db;\nsetp.ne.b32 p, 1, 0;\n"
                     MK_DESC("da", "%32", "%34") MK_DESC("db", "%33", "%35")
                     "wgmma.mma_async.sync.aligned.m64n64k16.f32.bf16.bf16 " REGS32 ", da, db, p, 1, 1, 0, 1;\n}\n"
                     : ACC32(C_IO, d) : "r"(la), "r"(lb), "n"(OA), "n"(OB));
}
__host__ __device__ constexpr int koff(int kk, int chunk) { return ((kk >> 2) * chunk + (kk & 3) * 32) >> 4; }

__device__ __forceinline__ uint32_t clock_now() {
    uint32_t t;
    asm volatile("mov.u32 %0, %%clock;" : "=r"(t));
    return t;
}
__device__ __forceinline__ void stage_put(const uint4* h, uint32_t buf) {
    const uint32_t t = tid_now(), line = ((t >> 3) & 3) + (t & 4);
    const uint32_t adr = buf + line * 128 + (((t & 3) ^ line) << 4);
#pragma unroll
    for (int i = 0; i < 4; i++)
        asm volatile("st.shared.v4.b32 [%4], {%0, %1, %2, %3};"
                     :: "r"(h[i].x), "r"(h[i].y), "r"(h[i].z), "r"(h[i].w), "r"((adr ^ ((i >> 1) << 6)) + (i & 1) * 1024) : "memory");
}
__device__ __forceinline__ void stage_send(const CUtensorMap* tm, uint32_t pos, int k, uint32_t buf) {
    asm volatile("fence.proxy.async.shared::cta;" ::: "memory");
    __syncwarp();
    if (elect_one()) {
        asm volatile("cp.async.bulk.tensor.5d.global.shared::cta.bulk_group [%0, {%2, %3, %2, %4, %5}], [%1];"
                     ::"l"(tm), "r"(buf), "r"(0), "r"(pos & 0xffff), "r"(pos >> 16), "r"(k) : "memory");
        asm volatile("cp.async.bulk.commit_group;" ::: "memory");
    }
    __syncwarp();
}
__device__ __forceinline__ void stage_wait() {
    asm volatile("cp.async.bulk.wait_group.read 0;" ::: "memory");
    __syncwarp();
}
__device__ __forceinline__ uint32_t out_pos(int win) {
    return ((win & 63) * 4) | (((win >> 6) * 8 + 2 * ((tid_now() >> 5) & 3)) << 16);
}
__device__ __forceinline__ uint32_t stage_buf() { return kSmemBase + kOffStage + ((tid_now() >> 5) & 3) * 2048; }
__device__ __forceinline__ void stage_window(uint4 (&h)[12], const CUtensorMap* tm, uint32_t pos, [[maybe_unused]] int win) {
#pragma unroll
    for (int k = 0; k < 3; k++) {
        if (k > 0) stage_wait();
        stage_put(h + 4 * k, stage_buf());
        stage_send(tm, pos, k, stage_buf());
    }
}
__device__ __forceinline__ void stg128(void* p, uint4 v) {
    asm volatile("st.global.v4.b32 [%0], {%1, %2, %3, %4};" ::"l"(p), "r"(v.x), "r"(v.y), "r"(v.z), "r"(v.w) : "memory");
}
#define TAIL_DT 90
template <int J> __device__ __forceinline__ void store_tail(uint4 (&h)[12], uint8_t* hptr, uint32_t t0) {
    if constexpr (J < 12) {
        if constexpr (J > 2) { while (clock_now() - t0 < (uint32_t)((J - 2) * TAIL_DT)) {} }
        stg128(hptr + (J / 6) * (kHW * kC * 2) + (J % 6) * 64, h[2 * (J % 6) + J / 6]);
        store_tail<J + 1>(h, hptr, t0);
    }
}
__device__ __forceinline__ uint8_t* out_address(__nv_bfloat16* out, uint32_t pos) {
    const uint32_t ln = tid_now() & 31;
    return reinterpret_cast<uint8_t*>(out) + ((pos >> 16) * kHW + (pos & 0xffff) * 2 + (ln >> 2)) * (uint32_t)(kC * 2) + (ln & 3) * 16;
}
template <int K0, int K> struct Gemm1 {
    static __device__ __forceinline__ void run(float (&d)[96], uint32_t lx, uint32_t lw) {
        if constexpr (K > K0) Gemm1<K0, K - 1>::run(d, lx, lw);
        wg192_ss<K == 0, koff(K, 8192), koff(K, 24576)>(d, lx, lw);
    }
};
__device__ __forceinline__ uint32_t draw_ticket(uint32_t* counter) {
    uint32_t ticket = 0;
    asm volatile("{\n.reg .pred p;\nsetp.eq.u32 p, %2, 0;\n@p atom.relaxed.gpu.global.inc.u32 %0, [%1], %3;\n}\n"
                 : "+r"(ticket) : "l"(counter), "r"(tid_now() & 127), "n"(kNWin - 1) : "memory");
    return ticket;
}
template <int KK> struct Gemm2 { static __device__ __forceinline__ void run(float (&d)[32], const uint32_t* a, uint32_t lx) {
    Gemm2<KK - 1>::run(d, a, lx); wg64_rs<KK == 0, koff(KK, 8192)>(d, a + 4 * KK, lx);
    if constexpr (KK == PASS2 && KK < 11) ring_pass(); } };
template <> struct Gemm2<-1> { static __device__ __forceinline__ void run(float (&)[32], const uint32_t*, uint32_t) {} };
template <int KK> struct Gemm3 { static __device__ __forceinline__ void run(float (&d)[96], const uint32_t* a, uint32_t lxt) {
    Gemm3<KK - 1>::run(d, a, lxt); wg192_rs<KK == 0, 1, KK * (2048 >> 4)>(d, a + 4 * KK, lxt);
    if constexpr (KK == PASS3 && KK < 3) ring_pass(); } };
template <> struct Gemm3<-1> { static __device__ __forceinline__ void run(float (&)[96], const uint32_t*, uint32_t) {} };
template <int K0, int KK> struct Gemm4 { static __device__ __forceinline__ void run(float (&d)[96], const uint32_t* a, uint32_t lw) {
    if constexpr (KK > K0) Gemm4<K0, KK - 1>::run(d, a, lw);
    wg192_rs<KK == 0, 0, koff(KK, 24576)>(d, a + 4 * KK, lw); } };

template <int J, int KK> struct Gemm3s { static __device__ __forceinline__ void run(float (&d)[32], uint32_t lp, uint32_t lxt) {
    if constexpr (KK > 0) Gemm3s<J, KK - 1>::run(d, lp, lxt);
    wg64_ss<KK == 0, KK * 2, (J * 8192 + KK * 2048) / 16>(d, lp, lxt); } };
template <int J, int K0, int KK> struct Gemm4s { static __device__ __forceinline__ void run(float (&d)[32], const uint32_t* a, uint32_t lw) {
    if constexpr (KK > K0) Gemm4s<J, K0, KK - 1>::run(d, a, lw);
    wg64_rs<KK == 0, koff(KK, 24576) + J * (8192 / 16)>(d, a + 4 * KK, lw); } };

__device__ __forceinline__ uint32_t pack_bf16(float lo, float hi) {
    uint32_t r;
    asm("cvt.rn.bf16x2.f32 %0, %1, %2;" : "=r"(r) : "f"(hi), "f"(lo));
    return r;
}
__device__ __forceinline__ float ex2(float x) {
    float r;
    asm("ex2.approx.ftz.f32 %0, %1;" : "=f"(r) : "f"(x));
    return r;
}
__device__ __forceinline__ float rcp(float x) {
    float r;
    asm("rcp.approx.ftz.f32 %0, %1;" : "=f"(r) : "f"(x));
    return r;
}

__device__ __forceinline__ void pack_slice(uint32_t* a, float (&d)[32]) {
    fence_regs(d);
#pragma unroll
    for (int i = 0; i < 16; i++) a[i] = pack_bf16(d[2 * i], d[2 * i + 1]);
#pragma unroll
    for (int i = 0; i < 16; i++) asm volatile("" : "+r"(a[i])::"memory");
}
template <int J> __device__ __forceinline__ void store_slice(float (&d)[32], uint8_t* hptr) {
    fence_regs(d);
#pragma unroll
    for (int r = 0; r < 2; r++) {
        uint4 h[2];
#pragma unroll
        for (int a = 0; a < 2; a++) {
            const int o = 16 * a + 2 * r;
            h[a] = make_uint4(pack_bf16(d[o], d[o + 1]), pack_bf16(d[o + 4], d[o + 5]), pack_bf16(d[o + 8], d[o + 9]), pack_bf16(d[o + 12], d[o + 13]));
        }
        stg128(hptr + r * (kHW * kC * 2) + J * 128, h[0]);
        stg128(hptr + r * (kHW * kC * 2) + J * 128 + 64, h[1]);
    }
    __syncwarp();
}
__device__ __forceinline__ void store_p_if(const uint32_t (&pa)[16], bool cond) {
    const uint32_t t = tid_now(), row = ((t >> 1) & 48) + (t & 15);
    const uint32_t adr = kSmemBase + kOffStage + row * 128 + ((((t >> 4) & 1) ^ (t & 7)) << 4);
#pragma unroll
    for (int i = 0; i < 4; i++)
        asm volatile("{\n.reg .pred p;\nsetp.ne.u32 p, %5, 0;\n@p stmatrix.sync.aligned.m8n8.x4.shared.b16 [%4], {%0, %1, %2, %3};\n}\n"
                     :: "r"(pa[4 * i]), "r"(pa[4 * i + 1]), "r"(pa[4 * i + 2]), "r"(pa[4 * i + 3]), "r"(adr ^ (i << 5)), "r"((uint32_t)cond) : "memory");
}
__device__ __forceinline__ void last_window(__nv_bfloat16* out, int win) {
    constexpr uint32_t dWv = ((kSmemBase + kOffWv) >> 4) | (1u << 16);
    asm volatile("fence.proxy.async.shared::cta;" ::: "memory");
    const uint32_t w = wg_uniform();
    const uint32_t dXt = desc_xt(w);
    constexpr uint32_t dP = ((kSmemBase + kOffStage) >> 4) | (1u << 16);
    float u0[32], u1[32], u2[32];
    uint32_t fa[48];
    uint8_t* hptr = out_address(out, out_pos(win));
    asm volatile("" : "+l"(hptr) :: "memory");
    ring_wait();
    wg_fence();
    Gemm3s<0, 3>::run(u0, dP, dXt); wg_commit();
    Gemm3s<1, 3>::run(u1, dP, dXt); wg_commit();
    Gemm3s<2, 3>::run(u2, dP, dXt); wg_commit();
    wg_wait2();
    pack_slice(fa, u0);
    wg_fence();
    Gemm4s<0, 0, 3>::run(u0, fa, dWv); wg_commit();
    wg_wait2();
    pack_slice(fa + 16, u1);
    wg_fence();
    Gemm4s<0, 4, 7>::run(u0, fa, dWv); wg_commit();
    wg_wait2();
    pack_slice(fa + 32, u2);
    wg_fence();
    Gemm4s<0, 8, 11>::run(u0, fa, dWv); wg_commit();
    Gemm4s<1, 0, 5>::run(u1, fa, dWv); wg_commit();
    wg_wait1();
    store_slice<0>(u0, hptr);
    wg_fence();
    Gemm4s<1, 6, 11>::run(u1, fa, dWv); wg_commit();
    Gemm4s<2, 0, 5>::run(u2, fa, dWv); wg_commit();
    wg_wait1();
    store_slice<1>(u1, hptr);
    wg_fence();
    Gemm4s<2, 6, 11>::run(u2, fa, dWv); wg_commit();
    wg_wait0();
    fence_regs(fa);
    store_slice<2>(u2, hptr);
}

__device__ __forceinline__ int fold_offset(int n, int k0, int q) {
    const int u = ((k0 & 63) >> 3) + (q >> 1);
    return (k0 >> 6) * 24576 + (q & 1) * 8 + n * 128 + ((u ^ (n & 7)) << 4);
}
__device__ __forceinline__ void mma16816x2(float (&c)[4], float (&d)[4], const uint32_t (&a)[4], const uint32_t (&b)[4]) {
    asm volatile("mma.sync.aligned.m16n8k16.row.col.f32.bf16.bf16.f32 {%0,%1,%2,%3}, {%8,%9,%10,%11}, {%12,%13}, {%0,%1,%2,%3};\n"
                 "mma.sync.aligned.m16n8k16.row.col.f32.bf16.bf16.f32 {%4,%5,%6,%7}, {%8,%9,%10,%11}, {%14,%15}, {%4,%5,%6,%7};"
                 : "+f"(c[0]), "+f"(c[1]), "+f"(c[2]), "+f"(c[3]), "+f"(d[0]), "+f"(d[1]), "+f"(d[2]), "+f"(d[3])
                 : "r"(a[0]), "r"(a[1]), "r"(a[2]), "r"(a[3]), "r"(b[0]), "r"(b[1]), "r"(b[2]), "r"(b[3]));
}
__device__ __forceinline__ void cp_async16(uint32_t dst, const void* src) {
    asm volatile("cp.async.cg.shared.global [%0], [%1], 16;" ::"r"(dst), "l"(src) : "memory");
}
template <bool kTrans> __device__ __forceinline__ void ldsm4(uint32_t (&r)[4], uint32_t addr) {
    if constexpr (kTrans)
        asm volatile("ldmatrix.sync.aligned.m8n8.x4.trans.shared.b16 {%0, %1, %2, %3}, [%4];" : "=r"(r[0]), "=r"(r[1]), "=r"(r[2]), "=r"(r[3]) : "r"(addr) : "memory");
    else
        asm volatile("ldmatrix.sync.aligned.m8n8.x4.shared.b16 {%0, %1, %2, %3}, [%4];" : "=r"(r[0]), "=r"(r[1]), "=r"(r[2]), "=r"(r[3]) : "r"(addr) : "memory");
}
__device__ __forceinline__ uint32_t nonzero(uint32_t w) { return w ? w : 0x80000000u; }
__device__ __forceinline__ void fold_job(Scratch* sc, const __nv_bfloat16* __restrict__ wqkv, const __nv_bfloat16* __restrict__ wo,
                                         int job, int warp, int lane) {
    const bool vo = job >= kJobsM;
    const int nw = vo ? 3 : 2, tile0 = vo ? 3 * (job - kJobsM) : 2 * job;
    const int n0 = (tile0 / 12) * 16, k0 = (tile0 % 12 + max(warp, 1) - 1) * 16;
    const uint32_t stage = kSmemBase + kOffWv;
    if (warp <= nw) {
        if (vo && warp == 0) {
            const char* src = reinterpret_cast<const char*>(wo + (lane >> 1) * kC + n0 + (lane & 1) * 8);
            const uint32_t dst = stage + ((lane ^ ((lane >> 3) & 1)) << 4);
#pragma unroll
            for (int i = 0; i < 12; i++) cp_async16(dst + i * 512, src + i * 16 * kC * 2);
        } else {
            const int row0 = warp == 0 ? n0 : k0, col0 = warp == 0 ? kC : vo ? 2 * kC : 0;
            const char* src = reinterpret_cast<const char*>(wqkv + (row0 + (lane >> 3)) * (3 * kC) + col0 + (lane & 7) * 8);
            const uint32_t dst = stage + warp * 6144 + (lane >> 3) * 384 + (((lane & 7) ^ (lane >> 3)) << 4);
#pragma unroll
            for (int i = 0; i < 12; i++) cp_async16((dst ^ (((i / 3) & 1) << 6)) + (i / 3) * 1536 + (i % 3) * 128, src + (i / 3) * 4 * 3 * kC * 2 + (i % 3) * 128);
        }
        asm volatile("cp.async.wait_all;" ::: "memory");
        asm volatile("bar.sync 13, %0;" ::"r"(32 * nw + 32) : "memory");
    }
    if (warp == 0 || (warp > nw && warp != kWarmW)) return;
    const int g = lane >> 2, q = lane & 3, mi = lane >> 3, r8 = lane & 7;
    uint32_t A[12][4], B[12][4];
    {
        const int row = 4 * (r8 >> 1) + (r8 & 1) + 2 * (mi >> 1);
        const uint32_t base = stage + warp * 6144 + row * 384 + (((mi & 1) ^ (row & 7)) << 4);
#pragma unroll
        for (int ks = 0; ks < 12; ks++) ldsm4<false>(B[ks], (base ^ ((ks & 3) << 5)) + (ks >> 2) * 128);
    }
    if (vo) {
        const int c = r8 + 8 * (mi >> 1);
        const uint32_t base = stage + (((2 * c + (mi & 1)) ^ ((c >> 2) & 1)) << 4);
#pragma unroll
        for (int ks = 0; ks < 12; ks++) ldsm4<true>(A[ks], base + ks * 512);
    } else {
        const uint32_t base = stage + (r8 + 8 * (mi & 1)) * 384 + (((mi >> 1) ^ r8) << 4);
#pragma unroll
        for (int ks = 0; ks < 12; ks++) ldsm4<false>(A[ks], (base ^ ((ks & 3) << 5)) + (ks >> 2) * 128);
    }
    float c0[4] = {0.f, 0.f, 0.f, 0.f}, c1[4] = {0.f, 0.f, 0.f, 0.f}, c2[4] = {0.f, 0.f, 0.f, 0.f}, c3[4] = {0.f, 0.f, 0.f, 0.f};
#pragma unroll
    for (int ks = 0; ks < 12; ks += 2) {
        mma16816x2(c0, c1, A[ks], B[ks]);
        mma16816x2(c2, c3, A[ks + 1], B[ks + 1]);
    }
#pragma unroll
    for (int i = 0; i < 4; i++) { c0[i] += c2[i]; c1[i] += c3[i]; }
    const int ch = n0 + g;
    const int n = vo ? 32 * (ch >> 5) + 8 * ((ch >> 1) & 3) + 2 * ((ch >> 3) & 3) + (ch & 1) : ch;
    char* img = reinterpret_cast<char*>(sc->wfold) + (vo ? kWBytes : 0);
    asm volatile("{\n.reg .pred p;\nsetp.ne.u32 p, %6, %7;\n@p st.global.v2.u32 [%0], {%2, %3};\n@p st.global.v2.u32 [%1], {%4, %5};\n}\n"
                 ::"l"(img + fold_offset(n, k0, q)), "l"(img + fold_offset(n + (vo ? 2 : 8), k0, q)),
                   "r"(nonzero(pack_bf16(c0[0], c0[1]))), "r"(nonzero(pack_bf16(c1[0], c1[1]))), "r"(nonzero(pack_bf16(c0[2], c0[3]))), "r"(nonzero(pack_bf16(c1[2], c1[3]))),
                   "r"(warp), "n"(kWarmW) : "memory");
}

__device__ __forceinline__ bool bar_or(uint32_t id, uint32_t n, bool pred) {
    uint32_t r;
    asm volatile("{\n.reg .pred p, q;\nsetp.ne.u32 q, %3, 0;\nbar.red.or.pred p, %1, %2, q;\nselp.u32 %0, 1, 0, p;\n}\n"
                 : "=r"(r) : "r"(id), "r"(n), "r"((uint32_t)pred) : "memory");
    return r != 0;
}
__device__ __forceinline__ bool chunk_incomplete(uint32_t base) {
    const uint32_t t = tid_now(), r = (t >> 2) & 7;
    const uint32_t adr = base + (((t >> 5) & 3) * 48 + r) * 128 + (t & 3) * 32 + r * 4;
    uint32_t m = ~0u;
#pragma unroll
    for (int j = 0; j < 6; j++) {
        uint32_t v;
        asm volatile("ld.shared.u32 %0, [%1];" : "=r"(v) : "r"(adr + j * 1024) : "memory");
        m = min(m, v);
    }
    return m == 0;
}
__device__ __forceinline__ void load_image(uint32_t dst, const void* src, uint32_t bar) {
    mbar_expect_tx(bar, kWBytes);
#pragma unroll
    for (int c = 0; c < 3; c++) bulk_load(dst + c * 24576, reinterpret_cast<const char*>(src) + c * 24576, 24576, bar);
}
__device__ __forceinline__ void repair_image(uint32_t dst, const void* src, uint32_t bar, uint32_t par) {
    uint32_t tries = 0;
    bool bad;
    do {
        if (((tid_now() >> 5) & 3) == 0) {
            if (elect_one()) {
                asm volatile("fence.proxy.async;" ::: "memory");
                load_image(dst, src, bar);
            }
            __syncwarp();
        }
        mbar_wait(bar, par);
        par ^= 1;
        bad = chunk_incomplete(dst) | chunk_incomplete(dst + 24576) | chunk_incomplete(dst + 2 * 24576);
        if (++tries > (1u << 16)) __trap();
    } while (bar_or((tid_now() >> 7) + 1, 128, bad));
}
__device__ __forceinline__ void count_image(Scratch* sc) {
    asm volatile("red.relaxed.gpu.global.inc.u32 [%0], %1;" ::"l"(sc->cnt), "r"(3 * nctaid_now() - 1) : "memory");
}
__device__ __forceinline__ uint32_t ld_acquire(const uint32_t* p) {
    uint32_t v;
    asm volatile("ld.acquire.gpu.global.u32 %0, [%1];" : "=r"(v) : "l"(p) : "memory");
    return v;
}
__device__ __noinline__ void clear_images(Scratch* sc) {
    const uint32_t g = gridDim.x, t = threadIdx.x & 127;
    if (t == 0) {
        uint32_t spins = 0;
        while (ld_acquire(sc->cnt) < 2 * g) { if (++spins > (1u << 24)) __trap(); }
    }
    asm volatile("bar.sync %0, 128;" ::"r"((threadIdx.x >> 7) + 1) : "memory");
    for (uint32_t i = blockIdx.x * 64 + t; t < 64 && i < 2 * kWBytes / 16; i += g * 64) sc->wfold[i] = make_uint4(0, 0, 0, 0);
    if (t == 0) count_image(sc);
}
__device__ __forceinline__ void prefetch_x(const CUtensorMap* tm, int win) {
    const int wh = win >> 6, ww = win & 63;
    asm volatile("cp.async.bulk.prefetch.tensor.3d.L2.global.tile [%0, {%1, %2, %3}];"
                 ::"l"(tm), "r"(0), "r"(ww * 8), "r"(wh * 8) : "memory");
}
__device__ __forceinline__ void prefetch_x_chunk(const CUtensorMap* tm, int win, int chunk) {
    const int wh = win >> 6, ww = win & 63;
    asm volatile("cp.async.bulk.prefetch.tensor.4d.L2.global.tile [%0, {%1, %2, %3, %4}];"
                 ::"l"(tm), "r"(0), "r"(ww * 8), "r"(wh * 8), "r"(chunk) : "memory");
}

__device__ __forceinline__ void prefetch_for_ticket(const CUtensorMap* tmp, int t) {
    const int base = kNWG * (int)gridDim.x;
    auto lead = [&](int tt) {
        int down = max(((kNWin - PF_END - base - tt) * PF_DOWN) >> 8, PF_MIN);
        return min(min((int)gridDim.x + ((tt * PF_UP) >> 8), PF_LEAD), down);
    };
    const int hi = base + t + lead(t);
    int lo = max(base + t - 1 + lead(t - 1), base + t) + 1;
#pragma unroll 1
    for (; lo <= hi && lo < kNWin; lo++) prefetch_x(tmp, lo);
}

template <bool kFewSMs>
__global__ void __launch_bounds__(kThreads, 1)
swin_attn_kernel(const __nv_bfloat16* __restrict__ wqkv, const __nv_bfloat16* __restrict__ wo, __nv_bfloat16* __restrict__ out, Scratch* sc, uint32_t* tickets,
                 const __grid_constant__ CUtensorMap tmx, const __grid_constant__ CUtensorMap tmp, const __grid_constant__ CUtensorMap tmc,
                 const __grid_constant__ CUtensorMap tmo) {
    extern __shared__ uint8_t smem_raw[];
    constexpr uint32_t sbase = kSmemBase;
    const uint32_t t_start = clock_now();
    asm volatile("{\n.reg .pred p, q;\n.reg .b32 i, j;\n.reg .b64 a, b;\nmad.lo.u32 i, %2, 14, %3;\nsetp.lt.u32 p, %3, 14;\nsetp.lt.and.u32 p, i, 1728, p;\n"
                 "mad.wide.u32 a, i, 128, %0;\n@p prefetch.global.L2 [a];\n"
                 "mad.lo.u32 j, %2, 5, %3;\nsetp.lt.u32 q, %3, 5;\nsetp.lt.and.u32 q, j, 576, q;\n"
                 "mad.wide.u32 b, j, 128, %1;\n@q prefetch.global.L2 [b];\n}\n" ::"l"(wqkv), "l"(wo), "r"(blockIdx.x), "r"(threadIdx.x) : "memory");
    if (smem_u32(smem_raw) != kSmemBase) __trap();
    const int tid = threadIdx.x, lane = tid & 31;
    const uint32_t warpu = __reduce_or_sync(0xffffffffu, (uint32_t)tid >> 5), wgu = warpu >> 2;
    const int warp = (int)warpu, wg = (int)wgu;
    const int G = gridDim.x;
    const uint32_t bar_full = sbase + kOffBar + 8 * wg;
    const uint32_t bar_w0 = sbase + kOffBar + 32, bar_w1 = bar_w0 + 8;
    int win = wg * G + blockIdx.x;

    if (warp > kWarmW) {
        if (warp == 10) {
            asm volatile("bar.sync 15, 64;" ::: "memory");
            asm volatile("bar.arrive 0, %0;" ::"n"(kThreads) : "memory");
            if (lane == 0) {
                asm volatile("prefetch.tensormap [%0];" ::"l"(&tmc) : "memory");
                asm volatile("prefetch.tensormap [%0];" ::"l"(&tmp) : "memory");
                asm volatile("prefetch.tensormap [%0];" ::"l"(&tmx) : "memory");
                const uint32_t due = (uint32_t)(blockIdx.x * TRK_S) / (uint32_t)G;
#pragma unroll 1
                for (int c = 0; c < 6; c++) {
                    while (clock_now() - t_start < TRK_T0 + (due + c * TRK_S) / 3) {}
                    if (c < 2) tma_load_x_chunk(sbase + kOffX + c * 8192, &tmc, bar_w0 + 16 * c, blockIdx.x, c);
                    else prefetch_x_chunk(&tmc, (c / 3) * G + blockIdx.x, c % 3);
                }
                while (clock_now() - t_start < TRK_T0 + due + 2 * TRK_S) {}
                prefetch_x(&tmp, 2 * G + blockIdx.x);
            }
            __syncwarp();
        } else if (warp == 11) {
            if (lane == 0) {
#pragma unroll
                for (int w = 0; w < kNWG; w++) mbar_init(sbase + kOffBar + 8 * w, 1);
                mbar_init(sbase + kOffBar + 24, 1);
                mbar_init(sbase + kOffBar + 88, 1);
                mbar_init(sbase + kOffBar + 96, 1);
                mbar_init(bar_w0, 1);
                mbar_init(bar_w1, 1);
                mbar_init(sbase + kOffBar + 48, 1);
                mbar_init(sbase + kOffBar + 56, 1);
                asm volatile("st.shared.v4.u32 [%0], {%1, %1, %1, %1};" ::"r"(sbase + kOffBar + 64), "r"(0) : "memory");
                asm volatile("fence.mbarrier_init.release.cluster;" ::: "memory");
                asm volatile("mbarrier.arrive.shared::cta.b64 _, [%0];" ::"r"(sbase + kOffBar) : "memory");
            }
            __syncwarp();
            asm volatile("bar.arrive 15, 64;" ::: "memory");
            asm volatile("bar.arrive 0, %0;" ::"n"(kThreads) : "memory");
            if (elect_one()) {
                const char* img = reinterpret_cast<const char*>(sc->wfold);
#pragma unroll
                for (int c = 0; c < 3; c++) mbar_expect_tx(c == 0 ? bar_w0 : sbase + kOffBar + 40 + 8 * c, 24576 + 8192);
#pragma unroll
                for (int c = 0; c < 3; c++) mbar_expect_tx(sbase + kOffBar + (c == 0 ? 8 : 80 + 8 * c), 8192);
                while (clock_now() - t_start < REQ_T) {}
#pragma unroll
                for (int c = 0; c < 3; c++) {
                    const uint32_t bar = c == 0 ? bar_w0 : sbase + kOffBar + 40 + 8 * c;
                    if (c == 2) tma_load_x_chunk(sbase + kOffX + c * 8192, &tmc, bar, blockIdx.x, c);
                    bulk_load(sbase + kOffWm + c * 24576, img + c * 24576, 24576, bar);
                }
                mbar_wait(bar_w0, 0);
#pragma unroll
                for (int c = 0; c < 3; c++)
                    tma_load_x_chunk(sbase + kOffX + kXBytes + c * 8192, &tmc, sbase + kOffBar + (c == 0 ? 8 : 80 + 8 * c), G + blockIdx.x, c);
            }
            __syncwarp();
        } else {
            asm volatile("bar.sync 0, %0;" ::"n"(kThreads) : "memory");
            if (warp == 9) {
                if (elect_one()) {
                    while (clock_now() - t_start < REQ_TV) {}
                    mbar_wait(sbase + kOffBar + 48, 0);
                    asm volatile("fence.proxy.async.shared::cta;" ::: "memory");
                    load_image(sbase + kOffWv, reinterpret_cast<const char*>(sc->wfold) + kWBytes, bar_w1);
                    mbar_expect_tx(sbase + kOffBar + 16, kXBytes);
                    tma_load_x(sbase + kOffX + 2 * kXBytes, &tmx, sbase + kOffBar + 16, 2 * G + blockIdx.x);
                }
                __syncwarp();
            }
        }
    } else {
        if constexpr (kFewSMs) {
#pragma unroll 1
            for (int j = blockIdx.x; j < kJobs; j += G) {
                fold_job(sc, wqkv, wo, j, warp, lane);
                asm volatile("bar.sync 14, %0;" ::"n"(32 * kWarmW + 32) : "memory");
            }
        } else {
            if (blockIdx.x < kJobs) fold_job(sc, wqkv, wo, blockIdx.x, warp, lane);
        }
        asm volatile("bar.sync 0, %0;" ::"n"(kThreads) : "memory");
    }
    if (wg == kNWG - 1) asm volatile("bar.sync 7, 128;" ::: "memory");
    if (wg == 1) {
        mbar_wait(bar_w0, 0);
        bool bad = chunk_incomplete(sbase + kOffWm);
        mbar_wait(sbase + kOffBar + 48, 0);
        bad |= chunk_incomplete(sbase + kOffWm + 24576);
        mbar_wait(sbase + kOffBar + 56, 0);
        bad |= chunk_incomplete(sbase + kOffWm + 2 * 24576);
        asm volatile("bar.arrive 8, 256;" ::: "memory");
        if (bar_or(11, 256, bad)) {
            repair_image(sbase + kOffWm, sc->wfold, sbase + kOffBar + 24, 0);
            asm volatile("bar.arrive 11, 256;" ::: "memory");
        }
        if (tid == 128) count_image(sc);
    } else if (wg == 2) {
        mbar_wait(bar_w1, 0);
        const bool bad = chunk_incomplete(sbase + kOffWv) | chunk_incomplete(sbase + kOffWv + 24576) | chunk_incomplete(sbase + kOffWv + 2 * 24576);
        if (bar_or(3, 128, bad)) {
            repair_image(sbase + kOffWv, reinterpret_cast<const char*>(sc->wfold) + kWBytes, bar_w1, 1);
        }
        if (tid == 256) count_image(sc);
    }

    constexpr uint32_t dWm = ((sbase + kOffWm) >> 4) | (1u << 16);
    constexpr uint32_t dWv = ((sbase + kOffWv) >> 4) | (1u << 16);
    const float cs = 0.07216878364870322f * 1.4426950408889634f;
    mbar_wait(bar_w0, 0);
    mbar_wait(bar_full, 0);

    uint4 hv[12];
    uint32_t pos;
    uint32_t phase = 0;
    float acc[96];
    uint32_t ticket = 0;
    {
        const uint32_t dX = desc_x(wg_uniform());
        if (wg != 0) ring_wait();
        if (wg == 1) {
            __syncwarp();
            const uint32_t t1 = clock_now();
            while (clock_now() - t1 < G11_DELAY) {}
        }
        wg_fence();
        Gemm1<0, 3>::run(acc, dX, dWm);
        const uint32_t bar_c1 = sbase + kOffBar + (wg == 1 ? 88 : 48);
        mbar_wait(bar_c1, 0);
        wg_fence();
        Gemm1<4, 7>::run(acc, dX, dWm);
        mbar_wait(bar_c1 + 8, 0);
        wg_fence();
        Gemm1<8, 11>::run(acc, dX, dWm);
        wg_commit();
        if (wg != 0) asm volatile("bar.arrive 8, 256;" ::: "memory");
        if (warp == 5) {
            if (elect_one()) prefetch_x(&tmp, kNWG * G + blockIdx.x);
            __syncwarp();
        }
        ticket = draw_ticket(tickets);
        const bool redo = wg == 0 && bar_or(11, 256, false);
        wg_wait0();
        if (redo) {
            asm volatile("bar.sync 11, 256;" ::: "memory");
            wg_fence();
            Gemm1<0, 11>::run(acc, dX, dWm);
            wg_commit();
            wg_wait0();
        }
        __syncwarp();
    }

    while (true) {
        uint32_t fa[48];
        const uint32_t dX = desc_x(wg_uniform());
        fence_regs(acc);
#pragma unroll
        for (int i = 0; i < 48; i++) fa[i] = pack_bf16(acc[2 * i], acc[2 * i + 1]);

        float s[32];
        fence_regs(fa);
        wg_fence();
        ring_wait();
        Gemm2<11>::run(s, fa, dX);
        wg_commit();
        if constexpr (PASS2 == 11) ring_pass();
        if (((tid_now() >> 5) & 3) == 0) {
            if ((tid_now() & 31) == 0) {
                uint32_t nxt = kNWG * nctaid_now() + ticket;
                if (nxt >= kNWin) {
                    uint32_t p0, p1, p2, p3;
                    asm volatile("ld.shared.v4.u32 {%0, %1, %2, %3}, [%4];" : "=r"(p0), "=r"(p1), "=r"(p2), "=r"(p3) : "r"(sbase + kOffBar + 64) : "memory");
                    nxt = kDone + (p0 >> 30) + (p1 >> 30) + (p2 >> 30);
                }
                asm volatile("st.shared.u32 [%0], %1;" ::"r"(sbase + kOffBar + 64 + 4 * (tid_now() >> 7)), "r"(nxt) : "memory");
            }
            __syncwarp();
            asm volatile("bar.arrive %0, 128;" ::"r"((tid_now() >> 7) + 4) : "memory");
        }
        asm volatile("cp.async.bulk.wait_group.read 0;" ::: "memory");
        asm volatile("bar.arrive 15, 256;" ::: "memory");
        wg_wait0();
        fence_regs(s);
        fence_regs(fa);

        uint32_t pa[16];
        {
            float a0[8], a1[8];
#pragma unroll
            for (int j = 0; j < 8; j++) { a0[j] = fmaxf(s[4 * j], s[4 * j + 1]); a1[j] = fmaxf(s[4 * j + 2], s[4 * j + 3]); }
#pragma unroll
            for (int d = 4; d > 0; d >>= 1)
#pragma unroll
                for (int j = 0; j < d; j++) { a0[j] = fmaxf(a0[j], a0[j + d]); a1[j] = fmaxf(a1[j], a1[j + d]); }
            float m0 = a0[0], m1 = a1[0];
            m0 = fmaxf(m0, __shfl_xor_sync(0xffffffffu, m0, 1));
            m1 = fmaxf(m1, __shfl_xor_sync(0xffffffffu, m1, 1));
            m0 = fmaxf(m0, __shfl_xor_sync(0xffffffffu, m0, 2));
            m1 = fmaxf(m1, __shfl_xor_sync(0xffffffffu, m1, 2));
            m0 *= cs; m1 *= cs;
            float l0 = 0.f, l1 = 0.f;
#pragma unroll
            for (int j = 0; j < 8; j++) {
                s[4 * j]     = ex2(fmaf(s[4 * j], cs, -m0));
                s[4 * j + 1] = ex2(fmaf(s[4 * j + 1], cs, -m0));
                s[4 * j + 2] = ex2(fmaf(s[4 * j + 2], cs, -m1));
                s[4 * j + 3] = ex2(fmaf(s[4 * j + 3], cs, -m1));
                l0 += s[4 * j] + s[4 * j + 1];
                l1 += s[4 * j + 2] + s[4 * j + 3];
            }
            l0 += __shfl_xor_sync(0xffffffffu, l0, 1);
            l1 += __shfl_xor_sync(0xffffffffu, l1, 1);
            l0 += __shfl_xor_sync(0xffffffffu, l0, 2);
            l1 += __shfl_xor_sync(0xffffffffu, l1, 2);
            const float r0 = rcp(l0), r1 = rcp(l1);
#pragma unroll
            for (int j = 0; j < 8; j++) {
                pa[2 * j]     = pack_bf16(s[4 * j] * r0, s[4 * j + 1] * r0);
                pa[2 * j + 1] = pack_bf16(s[4 * j + 2] * r1, s[4 * j + 3] * r1);
            }
        }

        const uint32_t dXt = desc_xt(wg_uniform());
        if (((tid_now() >> 5) & 3) != 0) asm volatile("bar.sync %0, 128;" ::"r"((tid_now() >> 7) + 4) : "memory");
        uint32_t pub;
        asm volatile("ld.shared.u32 %0, [%1];" : "=r"(pub) : "r"(sbase + kOffBar + 64 + 4 * (tid_now() >> 7)) : "memory");
        const int nxt = (int)__reduce_or_sync(0xffffffffu, pub);
        store_p_if(pa, nxt == (int)kDone + kNWG - 1);
        if (nxt == (int)kDone + kNWG - 1) {
            last_window(out, win);
            asm volatile("exit;");
            __builtin_unreachable();
        }
        fence_regs(pa);
        wg_fence();
        ring_wait();
        Gemm3<3>::run(acc, pa, dXt);
        wg_commit();
        if constexpr (PASS3 == 3) ring_pass();
        wg_wait0();
        fence_regs(acc);
        fence_regs(pa);

        if (((tid_now() >> 5) & 3) == 0) {
            asm volatile("bar.sync %0, 128;" ::"r"((tid_now() >> 7) + 1) : "memory");
            if (elect_one()) {
                const uint32_t wgl = tid_now() >> 7;
                const uint32_t bar = sbase + kOffBar + 8 * wgl;
                if (nxt < kNWin) {
                    mbar_expect_tx(bar, kXBytes);
                    tma_load_x_hint(sbase + kOffX + wgl * kXBytes, &tmx, bar, nxt, nxt >= kNWin - EF_LAST);
                    uint32_t again;
                    asm volatile("ld.volatile.shared.u32 %0, [%1];" : "=r"(again) : "r"(sbase + kOffBar + 64 + 4 * wgl) : "memory");
                    prefetch_for_ticket(&tmp, (int)again - kNWG * (int)gridDim.x);
                }
            }
            __syncwarp();
        } else {
            asm volatile("bar.arrive %0, 128;" ::"r"((tid_now() >> 7) + 1) : "memory");
        }
#pragma unroll
        for (int i = 0; i < 48; i++) fa[i] = pack_bf16(acc[2 * i], acc[2 * i + 1]);

        asm volatile("{\n.reg .pred p;\nsetp.lt.s32 p, %5, 0;\n@p st.volatile.shared.v4.b32 [%4], {%0, %1, %2, %3};\n}\n"
                     :: "r"(fa[44]), "r"(fa[45]), "r"(fa[46]), "r"(fa[47]), "r"(sbase + kOffBar + 112), "r"(nxt) : "memory");
        fence_regs(fa);
        wg_fence();
        ring_wait();
        Gemm4<0, 1>::run(acc, fa, dWv);
        wg_commit();
        Gemm4<2, 10>::run(acc, fa, dWv);
        wg_commit();
        wg_wait1();
        uint32_t fl[4];
        uint32_t zero;
        asm volatile("ld.volatile.shared.u32 %0, [%1];" : "=r"(zero) : "r"(sbase + kOffBar + 76) : "memory");
#pragma unroll
        for (int i = 0; i < 4; i++) fl[i] = fa[44 + i] ^ zero;
        wg_fence();
        wg192_rs<false, 0, koff(11, 24576)>(acc, fl, dWv);
        wg_commit();
        ring_pass();
        pos = out_pos(win);
        win = nxt;
        const uint32_t dX1 = desc_x(wg_uniform());
        phase ^= 1;
        if (win < kNWin) mbar_wait(sbase + kOffBar + 8 * (tid_now() >> 7), phase);
        asm volatile("" : "+r"(pos) :: "memory");
        wg_wait0();
        fence_regs(acc);
        fence_regs(fa);
        fence_regs(fl);

#pragma unroll
        for (int a = 0; a < 6; a++) {
            hv[2 * a].x     = pack_bf16(acc[16 * a + 0], acc[16 * a + 1]);
            hv[2 * a].y     = pack_bf16(acc[16 * a + 4], acc[16 * a + 5]);
            hv[2 * a].z     = pack_bf16(acc[16 * a + 8], acc[16 * a + 9]);
            hv[2 * a].w     = pack_bf16(acc[16 * a + 12], acc[16 * a + 13]);
            hv[2 * a + 1].x = pack_bf16(acc[16 * a + 2], acc[16 * a + 3]);
            hv[2 * a + 1].y = pack_bf16(acc[16 * a + 6], acc[16 * a + 7]);
            hv[2 * a + 1].z = pack_bf16(acc[16 * a + 10], acc[16 * a + 11]);
            hv[2 * a + 1].w = pack_bf16(acc[16 * a + 14], acc[16 * a + 15]);
        }
        if (win >= kNWin) break;
        wg_fence();
        ring_wait();
        Gemm1<0, 11>::run(acc, dX1, dWm);
        wg_commit();
        ring_pass();
        ticket = draw_ticket(tickets);
        asm volatile("bar.sync 15, 256;" ::: "memory");
        stage_window(hv, &tmo, pos, win);
        wg_wait0();
    }
    if (win == (int)kDone) {
        const uint32_t buf = sbase + kOffX + (tid_now() >> 7) * kXBytes + ((tid_now() >> 5) & 3) * 2048;
        asm volatile("bar.sync %0, 128;" ::"r"((tid_now() >> 7) + 1) : "memory");
        ring_wait();
        ring_pass();
#pragma unroll
        for (int k = 0; k < 3; k++) {
            stage_put(hv + 4 * k, buf + k * 8192);
            stage_send(&tmo, pos, k, buf + k * 8192);
        }
        clear_images(sc);
        asm volatile("bar.sync 15, 256;" ::: "memory");
        stage_wait();
    } else {
        uint8_t* hptr = out_address(out, pos);
        store_tail<0>(hv, hptr, clock_now());
    }
}

typedef CUresult (*EncodeTiledFn)(CUtensorMap*, CUtensorMapDataType, cuuint32_t, void*, const cuuint64_t*,
                                  const cuuint64_t*, const cuuint32_t*, const cuuint32_t*, CUtensorMapInterleave,
                                  CUtensorMapSwizzle, CUtensorMapL2promotion, CUtensorMapFloatOOBfill);

}

extern "C" void kernel_launch(void* const* d_in, const int* in_sizes, int n_in, void* d_out, int out_size) {
    (void)in_sizes; (void)n_in; (void)out_size;
    const __nv_bfloat16* x    = (const __nv_bfloat16*)d_in[0];
    const __nv_bfloat16* wqkv = (const __nv_bfloat16*)d_in[1];
    const __nv_bfloat16* wo   = (const __nv_bfloat16*)d_in[2];

    static EncodeTiledFn encode = nullptr;
    static int num_sms = 0;
    static void* scratch = nullptr;
    if (!encode) {
        void* fn = nullptr;
        cudaDriverEntryPointQueryResult qr;
        cudaGetDriverEntryPoint("cuTensorMapEncodeTiled", &fn, cudaEnableDefault, &qr);
        encode = (EncodeTiledFn)fn;
        int dev = 0;
        cudaGetDevice(&dev);
        cudaDeviceGetAttribute(&num_sms, cudaDevAttrMultiProcessorCount, dev);
        cudaGetSymbolAddress(&scratch, g_scratch);
        cudaFuncSetAttribute(swin_attn_kernel<false>, cudaFuncAttributeMaxDynamicSharedMemorySize, kSmemBytes);
        cudaFuncSetAttribute(swin_attn_kernel<true>, cudaFuncAttributeMaxDynamicSharedMemorySize, kSmemBytes);
    }
    CUtensorMap tmx;
    const cuuint64_t gdim[4] = {64, (cuuint64_t)kHW, (cuuint64_t)kHW, 3};
    const cuuint64_t gstr[3] = {(cuuint64_t)kC * 2, (cuuint64_t)kHW * kC * 2, 128};
    const cuuint32_t box[4] = {64, 8, 8, 3};
    const cuuint32_t estr[5] = {1, 1, 1, 1, 1};
    encode(&tmx, CU_TENSOR_MAP_DATA_TYPE_BFLOAT16, 4, (void*)x, gdim, gstr, box, estr, CU_TENSOR_MAP_INTERLEAVE_NONE,
           CU_TENSOR_MAP_SWIZZLE_128B, CU_TENSOR_MAP_L2_PROMOTION_NONE, CU_TENSOR_MAP_FLOAT_OOB_FILL_NONE);

    CUtensorMap tmp;
    const cuuint64_t pdim[3] = {(cuuint64_t)kC, (cuuint64_t)kHW, (cuuint64_t)kHW};
    const cuuint64_t pstr[2] = {(cuuint64_t)kC * 2, (cuuint64_t)kHW * kC * 2};
    const cuuint32_t pbox[3] = {(cuuint32_t)kC, 8, 8};
    encode(&tmp, CU_TENSOR_MAP_DATA_TYPE_BFLOAT16, 3, (void*)x, pdim, pstr, pbox, estr, CU_TENSOR_MAP_INTERLEAVE_NONE,
           CU_TENSOR_MAP_SWIZZLE_NONE, CU_TENSOR_MAP_L2_PROMOTION_NONE, CU_TENSOR_MAP_FLOAT_OOB_FILL_NONE);
    CUtensorMap tmc;
    const cuuint32_t boxc[4] = {64, 8, 8, 1};
    encode(&tmc, CU_TENSOR_MAP_DATA_TYPE_BFLOAT16, 4, (void*)x, gdim, gstr, boxc, estr, CU_TENSOR_MAP_INTERLEAVE_NONE,
           CU_TENSOR_MAP_SWIZZLE_128B, CU_TENSOR_MAP_L2_PROMOTION_NONE, CU_TENSOR_MAP_FLOAT_OOB_FILL_NONE);
    CUtensorMap tmo;
    const cuuint64_t odim[5] = {64, (cuuint64_t)kHW / 2, 2, (cuuint64_t)kHW, 3};
    const cuuint64_t ostr[4] = {(cuuint64_t)kC * 4, (cuuint64_t)kC * 2, (cuuint64_t)kHW * kC * 2, 128};
    const cuuint32_t obox[5] = {64, 4, 2, 2, 1};
    encode(&tmo, CU_TENSOR_MAP_DATA_TYPE_BFLOAT16, 5, d_out, odim, ostr, obox, estr, CU_TENSOR_MAP_INTERLEAVE_NONE,
           CU_TENSOR_MAP_SWIZZLE_128B, CU_TENSOR_MAP_L2_PROMOTION_NONE, CU_TENSOR_MAP_FLOAT_OOB_FILL_NONE);
    if (num_sms >= kJobs)
        swin_attn_kernel<false><<<num_sms, kThreads, kSmemBytes, cudaStreamPerThread>>>(wqkv, wo, (__nv_bfloat16*)d_out, (Scratch*)scratch, ((Scratch*)scratch)->ticket, tmx, tmp, tmc, tmo);
    else
        swin_attn_kernel<true><<<num_sms, kThreads, kSmemBytes, cudaStreamPerThread>>>(wqkv, wo, (__nv_bfloat16*)d_out, (Scratch*)scratch, ((Scratch*)scratch)->ticket, tmx, tmp, tmc, tmo);
}
```

```cpp
#include <cuda_runtime.h>
#include <cuda_bf16.h>
#include <cuda.h>
#include <stdint.h>

namespace {

constexpr int kC      = 192;
constexpr int kHW     = 512;
#define MAXWIN 4096
constexpr int kNWin   = MAXWIN;
constexpr int kXBytes = 64 * kC * 2;
constexpr int kWBytes = kC * kC * 2;
constexpr int kNWG    = 3;
constexpr int kThreads = kNWG * 128;
constexpr int kJobsM  = 72;
constexpr int kJobs   = 120;
constexpr int kWarmW  = 4;
#define PF_LEAD 400
#define PF_UP 114
#define PF_DOWN 39
#define PF_END 300
#define PF_MIN 135
#define EF_LAST 1000
#define TRK_T0 400
#define TRK_S 1800
#define G11_DELAY 100
#define REQ_T 2650
#define REQ_TV 4000

constexpr int kOffWm  = 0;
constexpr int kOffWv  = kWBytes;
constexpr int kOffX   = 2 * kWBytes;
constexpr int kOffStage = kOffX + kNWG * kXBytes;
constexpr int kOffBar = kOffStage + 8192;
constexpr int kOffProf = kOffBar + 128;
constexpr int kSmemBytes = kOffProf;
constexpr uint32_t kSmemBase = 1024;

struct Scratch {
    uint4 wfold[2 * kWBytes / 16];
    uint32_t ticket[32];
    uint32_t cnt[32];
};
__device__ __align__(128) Scratch g_scratch;

__device__ __forceinline__ uint32_t smem_u32(const void* p) { return (uint32_t)__cvta_generic_to_shared(p); }

__device__ __forceinline__ void mbar_init(uint32_t bar, uint32_t count) {
    asm volatile("mbarrier.init.shared::cta.b64 [%0], %1;" ::"r"(bar), "r"(count) : "memory");
}
__device__ __forceinline__ void mbar_expect_tx(uint32_t bar, uint32_t bytes) {
    asm volatile("mbarrier.arrive.expect_tx.shared::cta.b64 _, [%0], %1;" ::"r"(bar), "r"(bytes) : "memory");
}
__device__ __forceinline__ void mbar_wait(uint32_t bar, uint32_t parity) {
    uint32_t ok;
    uint32_t spins = 0;
    do {
        asm volatile("{\n.reg .pred p;\n"
                     "mbarrier.try_wait.parity.shared::cta.b64 p, [%1], %2;\n"
                     "selp.b32 %0, 1, 0, p;\n}\n"
                     : "=r"(ok) : "r"(bar), "r"(parity) : "memory");
        if (++spins > (1u << 26)) __trap();
    } while (!ok);
}
__device__ __forceinline__ uint32_t tid_now() {
    uint32_t t;
    asm volatile("mov.u32 %0, %%tid.x;" : "=r"(t));
    return t;
}
__device__ __forceinline__ uint32_t nctaid_now() {
    uint32_t t;
    asm volatile("mov.u32 %0, %%nctaid.x;" : "=r"(t));
    return t;
}
__device__ __forceinline__ bool elect_one() {
    uint32_t pred;
    asm volatile("{\n.reg .pred p;\nelect.sync _|p, 0xffffffff;\nselp.b32 %0, 1, 0, p;\n}\n" : "=r"(pred));
    return pred != 0;
}
#define PASS2 5
#define PASS3 3
__device__ __forceinline__ void ring_wait() {
    asm volatile("bar.sync %0, 256;" ::"r"((tid_now() >> 7) + 8) : "memory");
}
__device__ __forceinline__ void ring_pass() {
    const uint32_t w = tid_now() >> 7;
    asm volatile("bar.arrive %0, 256;" ::"r"(w == kNWG - 1 ? 8u : w + 9u) : "memory");
}
constexpr uint32_t kDone = 0x40000000u;
__device__ __forceinline__ uint32_t wg_uniform() { return __reduce_or_sync(0xffffffffu, tid_now() >> 7); }
__device__ __forceinline__ uint32_t desc_x(uint32_t w) { return (((kSmemBase + kOffX) >> 4) | (1u << 16)) + w * (kXBytes >> 4); }
__device__ __forceinline__ uint32_t desc_xt(uint32_t w) { return (((kSmemBase + kOffX) >> 4) | ((8192u >> 4) << 16)) + w * (kXBytes >> 4); }
__device__ __forceinline__ void tma_load_x_chunk(uint32_t dst, const CUtensorMap* tm, uint32_t bar, int win, int chunk) {
    asm volatile("cp.async.bulk.tensor.5d.shared::cluster.global.mbarrier::complete_tx::bytes"
                 " [%0], [%1, {%3, %4, %6, %6, %5}], [%2];"
                 ::"r"(dst), "l"(tm), "r"(bar), "r"(chunk * 64), "r"((win & 63) * 4), "r"((win >> 6) * 4), "r"(0) : "memory");
}
__device__ __forceinline__ void tma_load_x_hint(uint32_t dst, const CUtensorMap* tm, uint32_t bar, int win, bool evict_first) {
    uint64_t first, normal;
    asm("createpolicy.fractional.L2::evict_first.b64 %0, 1.0;" : "=l"(first));
    asm("createpolicy.fractional.L2::evict_normal.b64 %0, 1.0;" : "=l"(normal));
#pragma unroll
    for (int c = 0; c < 3; c++)
        asm volatile("cp.async.bulk.tensor.5d.shared::cluster.global.mbarrier::complete_tx::bytes.L2::cache_hint"
                     " [%0], [%1, {%3, %4, %6, %6, %5}], [%2], %7;"
                     ::"r"(dst + c * 8192), "l"(tm), "r"(bar), "r"(c * 64), "r"((win & 63) * 4), "r"((win >> 6) * 4), "r"(0),
                       "l"(evict_first ? first : normal) : "memory");
}
__device__ __forceinline__ void bulk_load(uint32_t dst, const void* src, uint32_t bytes, uint32_t bar) {
    asm volatile("cp.async.bulk.shared::cluster.global.mbarrier::complete_tx::bytes [%0], [%1], %2, [%3];"
                 ::"r"(dst), "l"(src), "r"(bytes), "r"(bar) : "memory");
}

__device__ __forceinline__ void wg_fence()  { asm volatile("wgmma.fence.sync.aligned;" ::: "memory"); }
__device__ __forceinline__ void wg_commit() { asm volatile("wgmma.commit_group.sync.aligned;" ::: "memory"); }
__device__ __forceinline__ void wg_wait0()  { asm volatile("wgmma.wait_group.sync.aligned 0;" ::: "memory"); }
__device__ __forceinline__ void wg_wait1()  { asm volatile("wgmma.wait_group.sync.aligned 1;" ::: "memory"); }
__device__ __forceinline__ void wg_wait2()  { asm volatile("wgmma.wait_group.sync.aligned 2;" ::: "memory"); }

template <int N> __device__ __forceinline__ void fence_regs(float (&d)[N]) {
#pragma unroll
    for (int i = 0; i < N; i++) asm volatile("" : "+f"(d[i])::"memory");
}
template <int N> __device__ __forceinline__ void fence_regs(uint32_t (&d)[N]) {
#pragma unroll
    for (int i = 0; i < N; i++) asm volatile("" : "+r"(d[i])::"memory");
}

#define ACC8(c, d, i) c(d[i]), c(d[i + 1]), c(d[i + 2]), c(d[i + 3]), c(d[i + 4]), c(d[i + 5]), c(d[i + 6]), c(d[i + 7])
#define ACC32(c, d) ACC8(c, d, 0), ACC8(c, d, 8), ACC8(c, d, 16), ACC8(c, d, 24)
#define ACC96(c, d) ACC32(c, d), ACC8(c, d, 32), ACC8(c, d, 40), ACC8(c, d, 48), ACC8(c, d, 56), \
                    ACC8(c, d, 64), ACC8(c, d, 72), ACC8(c, d, 80), ACC8(c, d, 88)
#define C_IO(x) "+f"(x)
#define C_O(x) "=f"(x)
#define REGS32 "{%0, %1, %2, %3, %4, %5, %6, %7, %8, %9, %10, %11, %12, %13, %14, %15, " \
               "%16, %17, %18, %19, %20, %21, %22, %23, %24, %25, %26, %27, %28, %29, %30, %31}"
#define REGS96 "{%0, %1, %2, %3, %4, %5, %6, %7, %8, %9, %10, %11, %12, %13, %14, %15, " \
               "%16, %17, %18, %19, %20, %21, %22, %23, %24, %25, %26, %27, %28, %29, %30, %31, " \
               "%32, %33, %34, %35, %36, %37, %38, %39, %40, %41, %42, %43, %44, %45, %46, %47, " \
               "%48, %49, %50, %51, %52, %53, %54, %55, %56, %57, %58, %59, %60, %61, %62, %63, " \
               "%64, %65, %66, %67, %68, %69, %70, %71, %72, %73, %74, %75, %76, %77, %78, %79, " \
               "%80, %81, %82, %83, %84, %85, %86, %87, %88, %89, %90, %91, %92, %93, %94, %95}"

#define DESC_HI "0x40000040"
#define MK_DESC(name, lo, off) "add.u32 t, " lo ", " off ";\nmov.b64 " name ", {t, " DESC_HI "};\n"

template <bool First, int OA, int OB> __device__ __forceinline__ void wg192_ss(float (&d)[96], uint32_t la, uint32_t lb) {
    if constexpr (First)
        asm volatile("{\n.reg .pred p;\n.reg .b32 t;\n.reg .b64 da, db;\nsetp.ne.b32 p, 0, 0;\n"
                     MK_DESC("da", "%96", "%98") MK_DESC("db", "%97", "%99")
                     "wgmma.mma_async.sync.aligned.m64n192k16.f32.bf16.bf16 " REGS96 ", da, db, p, 1, 1, 0, 0;\n}\n"
                     : ACC96(C_O, d) : "r"(la), "r"(lb), "n"(OA), "n"(OB));
    else
        asm volatile("{\n.reg .pred p;\n.reg .b32 t;\n.reg .b64 da, db;\nsetp.ne.b32 p, 1, 0;\n"
                     MK_DESC("da", "%96", "%98") MK_DESC("db", "%97", "%99")
                     "wgmma.mma_async.sync.aligned.m64n192k16.f32.bf16.bf16 " REGS96 ", da, db, p, 1, 1, 0, 0;\n}\n"
                     : ACC96(C_IO, d) : "r"(la), "r"(lb), "n"(OA), "n"(OB));
}
template <bool First, int TB, int OB> __device__ __forceinline__ void wg192_rs(float (&d)[96], const uint32_t* a, uint32_t lb) {
    if constexpr (First)
        asm volatile("{\n.reg .pred p;\n.reg .b32 t;\n.reg .b64 db;\nsetp.ne.b32 p, 0, 0;\n"
                     MK_DESC("db", "%100", "%102")
                     "wgmma.mma_async.sync.aligned.m64n192k16.f32.bf16.bf16 " REGS96 ", {%96, %97, %98, %99}, db, p, 1, 1, %101;\n}\n"
                     : ACC96(C_O, d) : "r"(a[0]), "r"(a[1]), "r"(a[2]), "r"(a[3]), "r"(lb), "n"(TB), "n"(OB));
    else
        asm volatile("{\n.reg .pred p;\n.reg .b32 t;\n.reg .b64 db;\nsetp.ne.b32 p, 1, 0;\n"
                     MK_DESC("db", "%100", "%102")
                     "wgmma.mma_async.sync.aligned.m64n192k16.f32.bf16.bf16 " REGS96 ", {%96, %97, %98, %99}, db, p, 1, 1, %101;\n}\n"
                     : ACC96(C_IO, d) : "r"(a[0]), "r"(a[1]), "r"(a[2]), "r"(a[3]), "r"(lb), "n"(TB), "n"(OB));
}
template <bool First, int OB> __device__ __forceinline__ void wg64_rs(float (&d)[32], const uint32_t* a, uint32_t lb) {
    if constexpr (First)
        asm volatile("{\n.reg .pred p;\n.reg .b32 t;\n.reg .b64 db;\nsetp.ne.b32 p, 0, 0;\n"
                     MK_DESC("db", "%36", "%37")
                     "wgmma.mma_async.sync.aligned.m64n64k16.f32.bf16.bf16 " REGS32 ", {%32, %33, %34, %35}, db, p, 1, 1, 0;\n}\n"
                     : ACC32(C_O, d) : "r"(a[0]), "r"(a[1]), "r"(a[2]), "r"(a[3]), "r"(lb), "n"(OB));
    else
        asm volatile("{\n.reg .pred p;\n.reg .b32 t;\n.reg .b64 db;\nsetp.ne.b32 p, 1, 0;\n"
                     MK_DESC("db", "%36", "%37")
                     "wgmma.mma_async.sync.aligned.m64n64k16.f32.bf16.bf16 " REGS32 ", {%32, %33, %34, %35}, db, p, 1, 1, 0;\n}\n"
                     : ACC32(C_IO, d) : "r"(a[0]), "r"(a[1]), "r"(a[2]), "r"(a[3]), "r"(lb), "n"(OB));
}
template <bool First, int OA, int OB> __device__ __forceinline__ void wg64_ss(float (&d)[32], uint32_t la, uint32_t lb) {
    if constexpr (First)
        asm volatile("{\n.reg .pred p;\n.reg .b32 t;\n.reg .b64 da, db;\nsetp.ne.b32 p, 0, 0;\n"
                     MK_DESC("da", "%32", "%34") MK_DESC("db", "%33", "%35")
                     "wgmma.mma_async.sync.aligned.m64n64k16.f32.bf16.bf16 " REGS32 ", da, db, p, 1, 1, 0, 1;\n}\n"
                     : ACC32(C_O, d) : "r"(la), "r"(lb), "n"(OA), "n"(OB));
    else
        asm volatile("{\n.reg .pred p;\n.reg .b32 t;\n.reg .b64 da, db;\nsetp.ne.b32 p, 1, 0;\n"
                     MK_DESC("da", "%32", "%34") MK_DESC("db", "%33", "%35")
                     "wgmma.mma_async.sync.aligned.m64n64k16.f32.bf16.bf16 " REGS32 ", da, db, p, 1, 1, 0, 1;\n}\n"
                     : ACC32(C_IO, d) : "r"(la), "r"(lb), "n"(OA), "n"(OB));
}
__host__ __device__ constexpr int koff(int kk, int chunk) { return ((kk >> 2) * chunk + (kk & 3) * 32) >> 4; }

__device__ __forceinline__ uint32_t clock_now() {
    uint32_t t;
    asm volatile("mov.u32 %0, %%clock;" : "=r"(t));
    return t;
}
template <int K> __device__ __forceinline__ void stage_put(const uint4 (&h)[12], uint32_t buf) {
    const uint32_t t = tid_now(), line = ((t >> 2) & 2) + (t & 4) + ((t >> 1) & 8);
    const uint32_t adr = buf + line * 128 + (((t & 3) ^ (line & 7)) << 4);
#pragma unroll
    for (int j = 0; j < 4; j++) {
        const int i = 4 * K + j, n = 2 * (i % 6) + i / 6;
        asm volatile("st.shared.v4.b32 [%4], {%0, %1, %2, %3};"
                     :: "r"(h[n].x), "r"(h[n].y), "r"(h[n].z), "r"(h[n].w), "r"((adr ^ ((j & 1) * 64 + (j >> 1) * 16)) + (j >> 1) * 128) : "memory");
    }
}
__device__ __forceinline__ void stage_send(const CUtensorMap* tm, uint32_t pos, int k, uint32_t buf) {
    asm volatile("fence.proxy.async.shared::cta;" ::: "memory");
    __syncwarp();
    if (elect_one()) {
        asm volatile("cp.async.bulk.tensor.5d.global.shared::cta.bulk_group [%0, {%2, %5, %3, %2, %4}], [%1];"
                     ::"l"(tm), "r"(buf), "r"(0), "r"(pos & 0xffff), "r"(pos >> 16), "r"(2 * k) : "memory");
        asm volatile("cp.async.bulk.commit_group;" ::: "memory");
    }
    __syncwarp();
}
__device__ __forceinline__ void stage_wait() {
    asm volatile("cp.async.bulk.wait_group.read 0;" ::: "memory");
    __syncwarp();
}
__device__ __forceinline__ uint32_t out_pos(int win) {
    return ((win & 63) * 2) | (((win >> 6) * 8 + 2 * ((tid_now() >> 5) & 3)) << 16);
}
__device__ __forceinline__ uint32_t stage_buf() { return kSmemBase + kOffStage + ((tid_now() >> 5) & 3) * 2048; }
template <int K> __device__ __forceinline__ void stage_window(uint4 (&h)[12], const CUtensorMap* tm, uint32_t pos, [[maybe_unused]] int win) {
    if constexpr (K < 3) {
        if constexpr (K > 0) stage_wait();
        stage_put<K>(h, stage_buf());
        stage_send(tm, pos, K, stage_buf());
        stage_window<K + 1>(h, tm, pos, win);
    }
}
__device__ __forceinline__ void stg128(void* p, uint4 v) {
    asm volatile("st.global.v4.b32 [%0], {%1, %2, %3, %4};" ::"l"(p), "r"(v.x), "r"(v.y), "r"(v.z), "r"(v.w) : "memory");
}
#define TAIL_DT 90
#define TAIL_FREE 2
template <int J> __device__ __forceinline__ void store_tail(uint4 (&h)[12], uint8_t* hptr, uint32_t t0) {
    if constexpr (J < 12) {
        if (J > TAIL_FREE) { while (clock_now() - t0 < (uint32_t)((J - TAIL_FREE) * TAIL_DT)) {} }
        stg128(hptr + J * 64, h[2 * (J % 6) + J / 6]);
        store_tail<J + 1>(h, hptr, t0);
    }
}
__device__ __forceinline__ uint8_t* out_address(__nv_bfloat16* out, uint32_t pos) {
    const uint32_t ln = tid_now() & 31;
    return reinterpret_cast<uint8_t*>(out) + (((pos >> 16) + (ln >> 4)) * kHW + (pos & 0xffff) * 4 + ((ln >> 1) & 6)) * (uint32_t)(kC * 2) + (ln & 3) * 16;
}
template <int K0, int K> struct Gemm1 {
    static __device__ __forceinline__ void run(float (&d)[96], uint32_t lx, uint32_t lw) {
        if constexpr (K > K0) Gemm1<K0, K - 1>::run(d, lx, lw);
        wg192_ss<K == 0, koff(K, 8192), koff(K, 24576)>(d, lx, lw);
    }
};
__device__ __forceinline__ uint32_t draw_ticket(uint32_t* counter) {
    uint32_t ticket = 0;
    asm volatile("{\n.reg .pred p;\nsetp.eq.u32 p, %2, 0;\n@p atom.relaxed.gpu.global.inc.u32 %0, [%1], %3;\n}\n"
                 : "+r"(ticket) : "l"(counter), "r"(tid_now() & 127), "n"(kNWin - 1) : "memory");
    return ticket;
}
template <int KK> struct Gemm2 { static __device__ __forceinline__ void run(float (&d)[32], const uint32_t* a, uint32_t lx) {
    Gemm2<KK - 1>::run(d, a, lx); wg64_rs<KK == 0, koff(KK, 8192)>(d, a + 4 * KK, lx);
    if constexpr (KK == PASS2 && KK < 11) ring_pass(); } };
template <> struct Gemm2<-1> { static __device__ __forceinline__ void run(float (&)[32], const uint32_t*, uint32_t) {} };
template <int KK> struct Gemm3 { static __device__ __forceinline__ void run(float (&d)[96], const uint32_t* a, uint32_t lxt) {
    Gemm3<KK - 1>::run(d, a, lxt); wg192_rs<KK == 0, 1, KK * (2048 >> 4)>(d, a + 4 * KK, lxt);
    if constexpr (KK == PASS3 && KK < 3) ring_pass(); } };
template <> struct Gemm3<-1> { static __device__ __forceinline__ void run(float (&)[96], const uint32_t*, uint32_t) {} };
template <int K0, int KK> struct Gemm4 { static __device__ __forceinline__ void run(float (&d)[96], const uint32_t* a, uint32_t lw) {
    if constexpr (KK > K0) Gemm4<K0, KK - 1>::run(d, a, lw);
    wg192_rs<KK == 0, 0, koff(KK, 24576)>(d, a + 4 * KK, lw); } };

template <int J, int KK> struct Gemm3s { static __device__ __forceinline__ void run(float (&d)[32], uint32_t lp, uint32_t lxt) {
    if constexpr (KK > 0) Gemm3s<J, KK - 1>::run(d, lp, lxt);
    wg64_ss<KK == 0, KK * 2, (J * 8192 + KK * 2048) / 16>(d, lp, lxt); } };
template <int J, int K0, int KK> struct Gemm4s { static __device__ __forceinline__ void run(float (&d)[32], const uint32_t* a, uint32_t lw) {
    if constexpr (KK > K0) Gemm4s<J, K0, KK - 1>::run(d, a, lw);
    wg64_rs<KK == 0, koff(KK, 24576) + J * (8192 / 16)>(d, a + 4 * KK, lw); } };

__device__ __forceinline__ uint32_t pack_bf16(float lo, float hi) {
    uint32_t r;
    asm("cvt.rn.bf16x2.f32 %0, %1, %2;" : "=r"(r) : "f"(hi), "f"(lo));
    return r;
}
__device__ __forceinline__ float ex2(float x) {
    float r;
    asm("ex2.approx.ftz.f32 %0, %1;" : "=f"(r) : "f"(x));
    return r;
}
__device__ __forceinline__ float rcp(float x) {
    float r;
    asm("rcp.approx.ftz.f32 %0, %1;" : "=f"(r) : "f"(x));
    return r;
}

__device__ __forceinline__ void pack_slice(uint32_t* a, float (&d)[32]) {
    fence_regs(d);
#pragma unroll
    for (int i = 0; i < 16; i++) a[i] = pack_bf16(d[2 * i], d[2 * i + 1]);
#pragma unroll
    for (int i = 0; i < 16; i++) asm volatile("" : "+r"(a[i])::"memory");
}
template <int J> __device__ __forceinline__ void store_slice(float (&d)[32], uint8_t* hptr) {
    fence_regs(d);
#pragma unroll
    for (int r = 0; r < 2; r++) {
        uint4 h[2];
#pragma unroll
        for (int a = 0; a < 2; a++) {
            const int o = 16 * a + 2 * r;
            h[a] = make_uint4(pack_bf16(d[o], d[o + 1]), pack_bf16(d[o + 4], d[o + 5]), pack_bf16(d[o + 8], d[o + 9]), pack_bf16(d[o + 12], d[o + 13]));
        }
        stg128(hptr + r * (kC * 2) + J * 128, h[0]);
        stg128(hptr + r * (kC * 2) + J * 128 + 64, h[1]);
    }
    __syncwarp();
}
__device__ __forceinline__ void store_p_if(const uint32_t (&pa)[16], bool cond) {
    const uint32_t t = tid_now(), row = ((t >> 1) & 48) + (t & 15);
    const uint32_t adr = kSmemBase + kOffStage + row * 128 + ((((t >> 4) & 1) ^ (t & 7)) << 4);
#pragma unroll
    for (int i = 0; i < 4; i++)
        asm volatile("{\n.reg .pred p;\nsetp.ne.u32 p, %5, 0;\n@p stmatrix.sync.aligned.m8n8.x4.shared.b16 [%4], {%0, %1, %2, %3};\n}\n"
                     :: "r"(pa[4 * i]), "r"(pa[4 * i + 1]), "r"(pa[4 * i + 2]), "r"(pa[4 * i + 3]), "r"(adr ^ (i << 5)), "r"((uint32_t)cond) : "memory");
}
__device__ __forceinline__ void last_window(__nv_bfloat16* out, int win) {
    constexpr uint32_t dWv = ((kSmemBase + kOffWv) >> 4) | (1u << 16);
    asm volatile("fence.proxy.async.shared::cta;" ::: "memory");
    const uint32_t w = wg_uniform();
    const uint32_t dXt = desc_xt(w);
    constexpr uint32_t dP = ((kSmemBase + kOffStage) >> 4) | (1u << 16);
    float u0[32], u1[32], u2[32];
    uint32_t fa[48];
    uint8_t* hptr = out_address(out, out_pos(win));
    asm volatile("" : "+l"(hptr) :: "memory");
    ring_wait();
    wg_fence();
    Gemm3s<0, 3>::run(u0, dP, dXt); wg_commit();
    Gemm3s<1, 3>::run(u1, dP, dXt); wg_commit();
    Gemm3s<2, 3>::run(u2, dP, dXt); wg_commit();
    wg_wait2();
    pack_slice(fa, u0);
    wg_fence();
    Gemm4s<0, 0, 3>::run(u0, fa, dWv); wg_commit();
    wg_wait2();
    pack_slice(fa + 16, u1);
    wg_fence();
    Gemm4s<0, 4, 7>::run(u0, fa, dWv); wg_commit();
    wg_wait2();
    pack_slice(fa + 32, u2);
    wg_fence();
    Gemm4s<0, 8, 11>::run(u0, fa, dWv); wg_commit();
    Gemm4s<1, 0, 5>::run(u1, fa, dWv); wg_commit();
    wg_wait1();
    store_slice<0>(u0, hptr);
    wg_fence();
    Gemm4s<1, 6, 11>::run(u1, fa, dWv); wg_commit();
    Gemm4s<2, 0, 5>::run(u2, fa, dWv); wg_commit();
    wg_wait1();
    store_slice<1>(u1, hptr);
    wg_fence();
    Gemm4s<2, 6, 11>::run(u2, fa, dWv); wg_commit();
    wg_wait0();
    fence_regs(fa);
    store_slice<2>(u2, hptr);
}

__device__ __forceinline__ int fold_offset(int n, int k0, int q) {
    const int u = ((k0 & 63) >> 3) + (q >> 1);
    return (k0 >> 6) * 24576 + (q & 1) * 8 + n * 128 + ((u ^ (n & 7)) << 4);
}
__device__ __forceinline__ void mma16816x2(float (&c)[4], float (&d)[4], const uint32_t (&a)[4], const uint32_t (&b)[4]) {
    asm volatile("mma.sync.aligned.m16n8k16.row.col.f32.bf16.bf16.f32 {%0,%1,%2,%3}, {%8,%9,%10,%11}, {%12,%13}, {%0,%1,%2,%3};\n"
                 "mma.sync.aligned.m16n8k16.row.col.f32.bf16.bf16.f32 {%4,%5,%6,%7}, {%8,%9,%10,%11}, {%14,%15}, {%4,%5,%6,%7};"
                 : "+f"(c[0]), "+f"(c[1]), "+f"(c[2]), "+f"(c[3]), "+f"(d[0]), "+f"(d[1]), "+f"(d[2]), "+f"(d[3])
                 : "r"(a[0]), "r"(a[1]), "r"(a[2]), "r"(a[3]), "r"(b[0]), "r"(b[1]), "r"(b[2]), "r"(b[3]));
}
__device__ __forceinline__ void cp_async16(uint32_t dst, const void* src) {
    asm volatile("cp.async.cg.shared.global [%0], [%1], 16;" ::"r"(dst), "l"(src) : "memory");
}
template <bool kTrans> __device__ __forceinline__ void ldsm4(uint32_t (&r)[4], uint32_t addr) {
    if constexpr (kTrans)
        asm volatile("ldmatrix.sync.aligned.m8n8.x4.trans.shared.b16 {%0, %1, %2, %3}, [%4];" : "=r"(r[0]), "=r"(r[1]), "=r"(r[2]), "=r"(r[3]) : "r"(addr) : "memory");
    else
        asm volatile("ldmatrix.sync.aligned.m8n8.x4.shared.b16 {%0, %1, %2, %3}, [%4];" : "=r"(r[0]), "=r"(r[1]), "=r"(r[2]), "=r"(r[3]) : "r"(addr) : "memory");
}
__device__ __forceinline__ uint32_t nonzero(uint32_t w) { return w ? w : 0x80000000u; }
__device__ __forceinline__ void fold_job(Scratch* sc, const __nv_bfloat16* __restrict__ wqkv, const __nv_bfloat16* __restrict__ wo,
                                         int job, int warp, int lane) {
    const bool vo = job >= kJobsM;
    const int nw = vo ? 3 : 2, tile0 = vo ? 3 * (job - kJobsM) : 2 * job;
    const int n0 = (tile0 / 12) * 16, k0 = (tile0 % 12 + max(warp, 1) - 1) * 16;
    const uint32_t stage = kSmemBase + kOffWv;
    if (warp <= nw) {
        if (vo && warp == 0) {
            const char* src = reinterpret_cast<const char*>(wo + (lane >> 1) * kC + n0 + (lane & 1) * 8);
            const uint32_t dst = stage + ((lane ^ ((lane >> 3) & 1)) << 4);
#pragma unroll
            for (int i = 0; i < 12; i++) cp_async16(dst + i * 512, src + i * 16 * kC * 2);
        } else {
            const int row0 = warp == 0 ? n0 : k0, col0 = warp == 0 ? kC : vo ? 2 * kC : 0;
            const char* src = reinterpret_cast<const char*>(wqkv + (row0 + (lane >> 3)) * (3 * kC) + col0 + (lane & 7) * 8);
            const uint32_t dst = stage + warp * 6144 + (lane >> 3) * 384 + (((lane & 7) ^ (lane >> 3)) << 4);
#pragma unroll
            for (int i = 0; i < 12; i++) cp_async16((dst ^ (((i / 3) & 1) << 6)) + (i / 3) * 1536 + (i % 3) * 128, src + (i / 3) * 4 * 3 * kC * 2 + (i % 3) * 128);
        }
        asm volatile("cp.async.wait_all;" ::: "memory");
        asm volatile("bar.sync 13, %0;" ::"r"(32 * nw + 32) : "memory");
    }
    if (warp == 0 || (warp > nw && warp != kWarmW)) return;
    const int g = lane >> 2, q = lane & 3, mi = lane >> 3, r8 = lane & 7;
    uint32_t A[12][4], B[12][4];
    {
        const int row = 4 * (r8 >> 1) + (r8 & 1) + 2 * (mi >> 1);
        const uint32_t base = stage + warp * 6144 + row * 384 + (((mi & 1) ^ (row & 7)) << 4);
#pragma unroll
        for (int ks = 0; ks < 12; ks++) ldsm4<false>(B[ks], (base ^ ((ks & 3) << 5)) + (ks >> 2) * 128);
    }
    if (vo) {
        const int c = r8 + 8 * (mi >> 1);
        const uint32_t base = stage + (((2 * c + (mi & 1)) ^ ((c >> 2) & 1)) << 4);
#pragma unroll
        for (int ks = 0; ks < 12; ks++) ldsm4<true>(A[ks], base + ks * 512);
    } else {
        const uint32_t base = stage + (r8 + 8 * (mi & 1)) * 384 + (((mi >> 1) ^ r8) << 4);
#pragma unroll
        for (int ks = 0; ks < 12; ks++) ldsm4<false>(A[ks], (base ^ ((ks & 3) << 5)) + (ks >> 2) * 128);
    }
    float c0[4] = {0.f, 0.f, 0.f, 0.f}, c1[4] = {0.f, 0.f, 0.f, 0.f}, c2[4] = {0.f, 0.f, 0.f, 0.f}, c3[4] = {0.f, 0.f, 0.f, 0.f};
#pragma unroll
    for (int ks = 0; ks < 12; ks += 2) {
        mma16816x2(c0, c1, A[ks], B[ks]);
        mma16816x2(c2, c3, A[ks + 1], B[ks + 1]);
    }
#pragma unroll
    for (int i = 0; i < 4; i++) { c0[i] += c2[i]; c1[i] += c3[i]; }
    const int ch = n0 + g;
    const int n = vo ? 32 * (ch >> 5) + 8 * ((ch >> 1) & 3) + 2 * ((ch >> 3) & 3) + (ch & 1) : ch;
    char* img = reinterpret_cast<char*>(sc->wfold) + (vo ? kWBytes : 0);
    asm volatile("{\n.reg .pred p;\nsetp.ne.u32 p, %6, %7;\n@p st.global.v2.u32 [%0], {%2, %3};\n@p st.global.v2.u32 [%1], {%4, %5};\n}\n"
                 ::"l"(img + fold_offset(n, k0, q)), "l"(img + fold_offset(n + (vo ? 2 : 8), k0, q)),
                   "r"(nonzero(pack_bf16(c0[0], c0[1]))), "r"(nonzero(pack_bf16(c1[0], c1[1]))), "r"(nonzero(pack_bf16(c0[2], c0[3]))), "r"(nonzero(pack_bf16(c1[2], c1[3]))),
                   "r"(warp), "n"(kWarmW) : "memory");
}

__device__ __forceinline__ bool bar_or(uint32_t id, uint32_t n, bool pred) {
    uint32_t r;
    asm volatile("{\n.reg .pred p, q;\nsetp.ne.u32 q, %3, 0;\nbar.red.or.pred p, %1, %2, q;\nselp.u32 %0, 1, 0, p;\n}\n"
                 : "=r"(r) : "r"(id), "r"(n), "r"((uint32_t)pred) : "memory");
    return r != 0;
}
__device__ __forceinline__ bool chunk_incomplete(uint32_t base) {
    const uint32_t t = tid_now(), r = (t >> 2) & 7;
    const uint32_t adr = base + (((t >> 5) & 3) * 48 + r) * 128 + (t & 3) * 32 + r * 4;
    uint32_t m = ~0u;
#pragma unroll
    for (int j = 0; j < 6; j++) {
        uint32_t v;
        asm volatile("ld.shared.u32 %0, [%1];" : "=r"(v) : "r"(adr + j * 1024) : "memory");
        m = min(m, v);
    }
    return m == 0;
}
__device__ __forceinline__ void load_image(uint32_t dst, const void* src, uint32_t bar) {
    mbar_expect_tx(bar, kWBytes);
#pragma unroll
    for (int c = 0; c < 3; c++) bulk_load(dst + c * 24576, reinterpret_cast<const char*>(src) + c * 24576, 24576, bar);
}
__device__ __forceinline__ void repair_image(uint32_t dst, const void* src, uint32_t bar, uint32_t par) {
    uint32_t tries = 0;
    bool bad;
    do {
        if (((tid_now() >> 5) & 3) == 0) {
            if (elect_one()) {
                asm volatile("fence.proxy.async;" ::: "memory");
                load_image(dst, src, bar);
            }
            __syncwarp();
        }
        mbar_wait(bar, par);
        par ^= 1;
        bad = chunk_incomplete(dst) | chunk_incomplete(dst + 24576) | chunk_incomplete(dst + 2 * 24576);
        if (++tries > (1u << 16)) __trap();
    } while (bar_or((tid_now() >> 7) + 1, 128, bad));
}
__device__ __forceinline__ void count_image(Scratch* sc) {
    asm volatile("red.relaxed.gpu.global.inc.u32 [%0], %1;" ::"l"(sc->cnt), "r"(3 * nctaid_now() - 1) : "memory");
}
__device__ __forceinline__ uint32_t ld_acquire(const uint32_t* p) {
    uint32_t v;
    asm volatile("ld.acquire.gpu.global.u32 %0, [%1];" : "=r"(v) : "l"(p) : "memory");
    return v;
}
__device__ __noinline__ void clear_images(Scratch* sc) {
    const uint32_t g = gridDim.x, t = threadIdx.x & 127;
    if (t == 0) {
        uint32_t spins = 0;
        while (ld_acquire(sc->cnt) < 2 * g) { if (++spins > (1u << 24)) __trap(); }
    }
    asm volatile("bar.sync %0, 128;" ::"r"((threadIdx.x >> 7) + 1) : "memory");
    for (uint32_t i = blockIdx.x * 64 + t; t < 64 && i < 2 * kWBytes / 16; i += g * 64) sc->wfold[i] = make_uint4(0, 0, 0, 0);
    if (t == 0) count_image(sc);
}
__device__ __forceinline__ void prefetch_x(const CUtensorMap* tm, int win) {
    const int wh = win >> 6, ww = win & 63;
    asm volatile("cp.async.bulk.prefetch.tensor.3d.L2.global.tile [%0, {%1, %2, %3}];"
                 ::"l"(tm), "r"(0), "r"(ww * 8), "r"(wh * 8) : "memory");
}
__device__ __forceinline__ void prefetch_x_chunk(const CUtensorMap* tm, int win, int chunk) {
    asm volatile("cp.async.bulk.prefetch.tensor.5d.L2.global.tile [%0, {%1, %2, %4, %4, %3}];"
                 ::"l"(tm), "r"(chunk * 64), "r"((win & 63) * 4), "r"((win >> 6) * 4), "r"(0) : "memory");
}

__device__ __forceinline__ void prefetch_for_ticket(const CUtensorMap* tmp, int t) {
    const int base = kNWG * (int)gridDim.x;
    auto lead = [&](int tt) {
        int down = max(((kNWin - PF_END - base - tt) * PF_DOWN) >> 8, PF_MIN);
        return min(min((int)gridDim.x + ((tt * PF_UP) >> 8), PF_LEAD), down);
    };
    const int hi = base + t + lead(t);
    int lo = max(base + t - 1 + lead(t - 1), base + t) + 1;
#pragma unroll 1
    for (; lo <= hi && lo < kNWin; lo++) prefetch_x(tmp, lo);
}

template <bool kFewSMs>
__global__ void __launch_bounds__(kThreads, 1)
swin_attn_kernel(const __nv_bfloat16* __restrict__ wqkv, const __nv_bfloat16* __restrict__ wo, __nv_bfloat16* __restrict__ out, Scratch* sc, uint32_t* tickets,
                 const __grid_constant__ CUtensorMap tmx, const __grid_constant__ CUtensorMap tmp, const __grid_constant__ CUtensorMap tmo) {
    extern __shared__ uint8_t smem_raw[];
    constexpr uint32_t sbase = kSmemBase;
    const uint32_t t_start = clock_now();
    asm volatile("{\n.reg .pred p, q;\n.reg .b32 i, j;\n.reg .b64 a, b;\nmad.lo.u32 i, %2, 14, %3;\nsetp.lt.u32 p, %3, 14;\nsetp.lt.and.u32 p, i, 1728, p;\n"
                 "mad.wide.u32 a, i, 128, %0;\n@p prefetch.global.L2 [a];\n"
                 "mad.lo.u32 j, %2, 5, %3;\nsetp.lt.u32 q, %3, 5;\nsetp.lt.and.u32 q, j, 576, q;\n"
                 "mad.wide.u32 b, j, 128, %1;\n@q prefetch.global.L2 [b];\n}\n" ::"l"(wqkv), "l"(wo), "r"(blockIdx.x), "r"(threadIdx.x) : "memory");
    if (smem_u32(smem_raw) != kSmemBase) __trap();
    const int tid = threadIdx.x, lane = tid & 31;
    const uint32_t warpu = __reduce_or_sync(0xffffffffu, (uint32_t)tid >> 5), wgu = warpu >> 2;
    const int warp = (int)warpu, wg = (int)wgu;
    const int G = gridDim.x;
    const uint32_t bar_full = sbase + kOffBar + 8 * wg;
    const uint32_t bar_w0 = sbase + kOffBar + 32, bar_w1 = bar_w0 + 8;
    int win = wg * G + blockIdx.x;

    if (warp > kWarmW) {
        if (warp == 10) {
            asm volatile("bar.sync 15, 64;" ::: "memory");
            asm volatile("bar.arrive 0, %0;" ::"n"(kThreads) : "memory");
            if (lane == 0) {
                asm volatile("prefetch.tensormap [%0];" ::"l"(&tmx) : "memory");
                asm volatile("prefetch.tensormap [%0];" ::"l"(&tmp) : "memory");
                const uint32_t due = (uint32_t)(blockIdx.x * TRK_S) / (uint32_t)G;
#pragma unroll 1
                for (int c = 0; c < 6; c++) {
                    while (clock_now() - t_start < TRK_T0 + (due + c * TRK_S) / 3) {}
                    if (c < 2) tma_load_x_chunk(sbase + kOffX + c * 8192, &tmx, bar_w0 + 16 * c, blockIdx.x, c);
                    else prefetch_x_chunk(&tmx, (c / 3) * G + blockIdx.x, c % 3);
                }
                while (clock_now() - t_start < TRK_T0 + due + 2 * TRK_S) {}
                prefetch_x(&tmp, 2 * G + blockIdx.x);
            }
            __syncwarp();
        } else if (warp == 11) {
            if (lane == 0) {
#pragma unroll
                for (int w = 0; w < kNWG; w++) mbar_init(sbase + kOffBar + 8 * w, 1);
                mbar_init(sbase + kOffBar + 24, 1);
                mbar_init(sbase + kOffBar + 88, 1);
                mbar_init(sbase + kOffBar + 96, 1);
                mbar_init(bar_w0, 1);
                mbar_init(bar_w1, 1);
                mbar_init(sbase + kOffBar + 48, 1);
                mbar_init(sbase + kOffBar + 56, 1);
                asm volatile("st.shared.v4.u32 [%0], {%1, %1, %1, %1};" ::"r"(sbase + kOffBar + 64), "r"(0) : "memory");
                asm volatile("fence.mbarrier_init.release.cluster;" ::: "memory");
                asm volatile("mbarrier.arrive.shared::cta.b64 _, [%0];" ::"r"(sbase + kOffBar) : "memory");
            }
            __syncwarp();
            asm volatile("bar.arrive 15, 64;" ::: "memory");
            asm volatile("bar.arrive 0, %0;" ::"n"(kThreads) : "memory");
            if (elect_one()) {
                const char* img = reinterpret_cast<const char*>(sc->wfold);
#pragma unroll
                for (int c = 0; c < 3; c++) mbar_expect_tx(c == 0 ? bar_w0 : sbase + kOffBar + 40 + 8 * c, 24576 + 8192);
#pragma unroll
                for (int c = 0; c < 3; c++) mbar_expect_tx(sbase + kOffBar + (c == 0 ? 8 : 80 + 8 * c), 8192);
                while (clock_now() - t_start < REQ_T) {}
#pragma unroll
                for (int c = 0; c < 3; c++) {
                    const uint32_t bar = c == 0 ? bar_w0 : sbase + kOffBar + 40 + 8 * c;
                    if (c == 2) tma_load_x_chunk(sbase + kOffX + c * 8192, &tmx, bar, blockIdx.x, c);
                    bulk_load(sbase + kOffWm + c * 24576, img + c * 24576, 24576, bar);
                }
                mbar_wait(bar_w0, 0);
#pragma unroll
                for (int c = 0; c < 3; c++)
                    tma_load_x_chunk(sbase + kOffX + kXBytes + c * 8192, &tmx, sbase + kOffBar + (c == 0 ? 8 : 80 + 8 * c), G + blockIdx.x, c);
            }
            __syncwarp();
        } else {
            asm volatile("bar.sync 0, %0;" ::"n"(kThreads) : "memory");
            if (warp == 9) {
                if (elect_one()) {
                    while (clock_now() - t_start < REQ_TV) {}
                    mbar_wait(sbase + kOffBar + 48, 0);
                    asm volatile("fence.proxy.async.shared::cta;" ::: "memory");
                    load_image(sbase + kOffWv, reinterpret_cast<const char*>(sc->wfold) + kWBytes, bar_w1);
                    mbar_expect_tx(sbase + kOffBar + 16, kXBytes);
#pragma unroll
                    for (int c = 0; c < 3; c++) tma_load_x_chunk(sbase + kOffX + 2 * kXBytes + c * 8192, &tmx, sbase + kOffBar + 16, 2 * G + blockIdx.x, c);
                }
                __syncwarp();
            }
        }
    } else {
        if constexpr (kFewSMs) {
#pragma unroll 1
            for (int j = blockIdx.x; j < kJobs; j += G) {
                fold_job(sc, wqkv, wo, j, warp, lane);
                asm volatile("bar.sync 14, %0;" ::"n"(32 * kWarmW + 32) : "memory");
            }
        } else {
            if (blockIdx.x < kJobs) fold_job(sc, wqkv, wo, blockIdx.x, warp, lane);
        }
        asm volatile("bar.sync 0, %0;" ::"n"(kThreads) : "memory");
    }
    if (wg == kNWG - 1) asm volatile("bar.sync 7, 128;" ::: "memory");
    if (wg == 1) {
        mbar_wait(bar_w0, 0);
        bool bad = chunk_incomplete(sbase + kOffWm);
        mbar_wait(sbase + kOffBar + 48, 0);
        bad |= chunk_incomplete(sbase + kOffWm + 24576);
        mbar_wait(sbase + kOffBar + 56, 0);
        bad |= chunk_incomplete(sbase + kOffWm + 2 * 24576);
        asm volatile("bar.arrive 8, 256;" ::: "memory");
        if (bar_or(11, 256, bad)) {
            repair_image(sbase + kOffWm, sc->wfold, sbase + kOffBar + 24, 0);
            asm volatile("bar.arrive 11, 256;" ::: "memory");
        }
        if (tid == 128) count_image(sc);
    } else if (wg == 2) {
        mbar_wait(bar_w1, 0);
        const bool bad = chunk_incomplete(sbase + kOffWv) | chunk_incomplete(sbase + kOffWv + 24576) | chunk_incomplete(sbase + kOffWv + 2 * 24576);
        if (bar_or(3, 128, bad)) {
            repair_image(sbase + kOffWv, reinterpret_cast<const char*>(sc->wfold) + kWBytes, bar_w1, 1);
        }
        if (tid == 256) count_image(sc);
    }

    constexpr uint32_t dWm = ((sbase + kOffWm) >> 4) | (1u << 16);
    constexpr uint32_t dWv = ((sbase + kOffWv) >> 4) | (1u << 16);
    const float cs = 0.07216878364870322f * 1.4426950408889634f;
    mbar_wait(bar_w0, 0);
    mbar_wait(bar_full, 0);

    uint4 hv[12];
    uint32_t pos;
    uint32_t phase = 0;
    float acc[96];
    uint32_t ticket = 0;
    {
        const uint32_t dX = desc_x(wg_uniform());
        if (wg != 0) ring_wait();
        if (wg == 1) {
            __syncwarp();
            const uint32_t t1 = clock_now();
            while (clock_now() - t1 < G11_DELAY) {}
        }
        wg_fence();
        Gemm1<0, 3>::run(acc, dX, dWm);
        const uint32_t bar_c1 = sbase + kOffBar + (wg == 1 ? 88 : 48);
        mbar_wait(bar_c1, 0);
        wg_fence();
        Gemm1<4, 7>::run(acc, dX, dWm);
        mbar_wait(bar_c1 + 8, 0);
        wg_fence();
        Gemm1<8, 11>::run(acc, dX, dWm);
        wg_commit();
        if (wg != 0) asm volatile("bar.arrive 8, 256;" ::: "memory");
        if (warp == 5) {
            if (elect_one()) prefetch_x(&tmp, kNWG * G + blockIdx.x);
            __syncwarp();
        }
        ticket = draw_ticket(tickets);
        const bool redo = wg == 0 && bar_or(11, 256, false);
        wg_wait0();
        if (redo) {
            asm volatile("bar.sync 11, 256;" ::: "memory");
            wg_fence();
            Gemm1<0, 11>::run(acc, dX, dWm);
            wg_commit();
            wg_wait0();
        }
        __syncwarp();
    }

    while (true) {
        uint32_t fa[48];
        const uint32_t dX = desc_x(wg_uniform());
        fence_regs(acc);
#pragma unroll
        for (int i = 0; i < 48; i++) fa[i] = pack_bf16(acc[2 * i], acc[2 * i + 1]);

        float s[32];
        fence_regs(fa);
        wg_fence();
        ring_wait();
        Gemm2<11>::run(s, fa, dX);
        wg_commit();
        if constexpr (PASS2 == 11) ring_pass();
        if (((tid_now() >> 5) & 3) == 0) {
            if ((tid_now() & 31) == 0) {
                uint32_t nxt = kNWG * nctaid_now() + ticket;
                if (nxt >= kNWin) {
                    uint32_t p0, p1, p2, p3;
                    asm volatile("ld.shared.v4.u32 {%0, %1, %2, %3}, [%4];" : "=r"(p0), "=r"(p1), "=r"(p2), "=r"(p3) : "r"(sbase + kOffBar + 64) : "memory");
                    nxt = kDone + (p0 >> 30) + (p1 >> 30) + (p2 >> 30);
                }
                asm volatile("st.shared.u32 [%0], %1;" ::"r"(sbase + kOffBar + 64 + 4 * (tid_now() >> 7)), "r"(nxt) : "memory");
            }
            __syncwarp();
            asm volatile("bar.arrive %0, 128;" ::"r"((tid_now() >> 7) + 4) : "memory");
        }
        asm volatile("cp.async.bulk.wait_group.read 0;" ::: "memory");
        asm volatile("bar.arrive 15, 256;" ::: "memory");
        wg_wait0();
        fence_regs(s);
        fence_regs(fa);

        uint32_t pa[16];
        {
            float a0[8], a1[8];
#pragma unroll
            for (int j = 0; j < 8; j++) { a0[j] = fmaxf(s[4 * j], s[4 * j + 1]); a1[j] = fmaxf(s[4 * j + 2], s[4 * j + 3]); }
#pragma unroll
            for (int d = 4; d > 0; d >>= 1)
#pragma unroll
                for (int j = 0; j < d; j++) { a0[j] = fmaxf(a0[j], a0[j + d]); a1[j] = fmaxf(a1[j], a1[j + d]); }
            float m0 = a0[0], m1 = a1[0];
            m0 = fmaxf(m0, __shfl_xor_sync(0xffffffffu, m0, 1));
            m1 = fmaxf(m1, __shfl_xor_sync(0xffffffffu, m1, 1));
            m0 = fmaxf(m0, __shfl_xor_sync(0xffffffffu, m0, 2));
            m1 = fmaxf(m1, __shfl_xor_sync(0xffffffffu, m1, 2));
            m0 *= cs; m1 *= cs;
            float l0 = 0.f, l1 = 0.f;
#pragma unroll
            for (int j = 0; j < 8; j++) {
                s[4 * j]     = ex2(fmaf(s[4 * j], cs, -m0));
                s[4 * j + 1] = ex2(fmaf(s[4 * j + 1], cs, -m0));
                s[4 * j + 2] = ex2(fmaf(s[4 * j + 2], cs, -m1));
                s[4 * j + 3] = ex2(fmaf(s[4 * j + 3], cs, -m1));
                l0 += s[4 * j] + s[4 * j + 1];
                l1 += s[4 * j + 2] + s[4 * j + 3];
            }
            l0 += __shfl_xor_sync(0xffffffffu, l0, 1);
            l1 += __shfl_xor_sync(0xffffffffu, l1, 1);
            l0 += __shfl_xor_sync(0xffffffffu, l0, 2);
            l1 += __shfl_xor_sync(0xffffffffu, l1, 2);
            const float r0 = rcp(l0), r1 = rcp(l1);
#pragma unroll
            for (int j = 0; j < 8; j++) {
                pa[2 * j]     = pack_bf16(s[4 * j] * r0, s[4 * j + 1] * r0);
                pa[2 * j + 1] = pack_bf16(s[4 * j + 2] * r1, s[4 * j + 3] * r1);
            }
        }

        const uint32_t dXt = desc_xt(wg_uniform());
        if (((tid_now() >> 5) & 3) != 0) asm volatile("bar.sync %0, 128;" ::"r"((tid_now() >> 7) + 4) : "memory");
        uint32_t pub;
        asm volatile("ld.shared.u32 %0, [%1];" : "=r"(pub) : "r"(sbase + kOffBar + 64 + 4 * (tid_now() >> 7)) : "memory");
        const int nxt = (int)__reduce_or_sync(0xffffffffu, pub);
        store_p_if(pa, nxt == (int)kDone + kNWG - 1);
        if (nxt == (int)kDone + kNWG - 1) {
            last_window(out, win);
            asm volatile("exit;");
            __builtin_unreachable();
        }
        fence_regs(pa);
        wg_fence();
        ring_wait();
        Gemm3<3>::run(acc, pa, dXt);
        wg_commit();
        if constexpr (PASS3 == 3) ring_pass();
        wg_wait0();
        fence_regs(acc);
        fence_regs(pa);

        if (((tid_now() >> 5) & 3) == 0) {
            asm volatile("bar.sync %0, 128;" ::"r"((tid_now() >> 7) + 1) : "memory");
            if (elect_one()) {
                const uint32_t wgl = tid_now() >> 7;
                const uint32_t bar = sbase + kOffBar + 8 * wgl;
                if (nxt < kNWin) {
                    mbar_expect_tx(bar, kXBytes);
                    tma_load_x_hint(sbase + kOffX + wgl * kXBytes, &tmx, bar, nxt, nxt >= kNWin - EF_LAST);
                    uint32_t again;
                    asm volatile("ld.volatile.shared.u32 %0, [%1];" : "=r"(again) : "r"(sbase + kOffBar + 64 + 4 * wgl) : "memory");
                    prefetch_for_ticket(&tmp, (int)again - kNWG * (int)gridDim.x);
                }
            }
            __syncwarp();
        } else {
            asm volatile("bar.arrive %0, 128;" ::"r"((tid_now() >> 7) + 1) : "memory");
        }
#pragma unroll
        for (int i = 0; i < 48; i++) fa[i] = pack_bf16(acc[2 * i], acc[2 * i + 1]);

        asm volatile("{\n.reg .pred p;\nsetp.lt.s32 p, %5, 0;\n@p st.volatile.shared.v4.b32 [%4], {%0, %1, %2, %3};\n}\n"
                     :: "r"(fa[44]), "r"(fa[45]), "r"(fa[46]), "r"(fa[47]), "r"(sbase + kOffBar + 112), "r"(nxt) : "memory");
        fence_regs(fa);
        wg_fence();
        ring_wait();
        Gemm4<0, 1>::run(acc, fa, dWv);
        wg_commit();
        Gemm4<2, 10>::run(acc, fa, dWv);
        wg_commit();
        wg_wait1();
        uint32_t fl[4];
        uint32_t zero;
        asm volatile("ld.volatile.shared.u32 %0, [%1];" : "=r"(zero) : "r"(sbase + kOffBar + 76) : "memory");
#pragma unroll
        for (int i = 0; i < 4; i++) fl[i] = fa[44 + i] ^ zero;
        wg_fence();
        wg192_rs<false, 0, koff(11, 24576)>(acc, fl, dWv);
        wg_commit();
        ring_pass();
        pos = out_pos(win);
        win = nxt;
        const uint32_t dX1 = desc_x(wg_uniform());
        phase ^= 1;
        if (win < kNWin) mbar_wait(sbase + kOffBar + 8 * (tid_now() >> 7), phase);
        asm volatile("" : "+r"(pos) :: "memory");
        wg_wait0();
        fence_regs(acc);
        fence_regs(fa);
        fence_regs(fl);

#pragma unroll
        for (int a = 0; a < 6; a++) {
            hv[2 * a].x     = pack_bf16(acc[16 * a + 0], acc[16 * a + 1]);
            hv[2 * a].y     = pack_bf16(acc[16 * a + 4], acc[16 * a + 5]);
            hv[2 * a].z     = pack_bf16(acc[16 * a + 8], acc[16 * a + 9]);
            hv[2 * a].w     = pack_bf16(acc[16 * a + 12], acc[16 * a + 13]);
            hv[2 * a + 1].x = pack_bf16(acc[16 * a + 2], acc[16 * a + 3]);
            hv[2 * a + 1].y = pack_bf16(acc[16 * a + 6], acc[16 * a + 7]);
            hv[2 * a + 1].z = pack_bf16(acc[16 * a + 10], acc[16 * a + 11]);
            hv[2 * a + 1].w = pack_bf16(acc[16 * a + 14], acc[16 * a + 15]);
        }
        if (win >= kNWin) break;
        wg_fence();
        ring_wait();
        Gemm1<0, 11>::run(acc, dX1, dWm);
        wg_commit();
        ring_pass();
        ticket = draw_ticket(tickets);
        asm volatile("bar.sync 15, 256;" ::: "memory");
        stage_window<0>(hv, &tmo, pos, win);
        wg_wait0();
    }
    if (win == (int)kDone) {
        const uint32_t buf = sbase + kOffX + (tid_now() >> 7) * kXBytes + ((tid_now() >> 5) & 3) * 2048;
        asm volatile("bar.sync %0, 128;" ::"r"((tid_now() >> 7) + 1) : "memory");
        ring_wait();
        ring_pass();
        stage_put<0>(hv, buf);
        stage_send(&tmo, pos, 0, buf);
        stage_put<1>(hv, buf + 8192);
        stage_send(&tmo, pos, 1, buf + 8192);
        stage_put<2>(hv, buf + 2 * 8192);
        stage_send(&tmo, pos, 2, buf + 2 * 8192);
        clear_images(sc);
        asm volatile("bar.sync 15, 256;" ::: "memory");
        stage_wait();
    } else {
        uint8_t* hptr = out_address(out, pos);
        store_tail<0>(hv, hptr, clock_now());
    }
}

typedef CUresult (*EncodeTiledFn)(CUtensorMap*, CUtensorMapDataType, cuuint32_t, void*, const cuuint64_t*,
                                  const cuuint64_t*, const cuuint32_t*, const cuuint32_t*, CUtensorMapInterleave,
                                  CUtensorMapSwizzle, CUtensorMapL2promotion, CUtensorMapFloatOOBfill);

}

extern "C" void kernel_launch(void* const* d_in, const int* in_sizes, int n_in, void* d_out, int out_size) {
    (void)in_sizes; (void)n_in; (void)out_size;
    const __nv_bfloat16* x    = (const __nv_bfloat16*)d_in[0];
    const __nv_bfloat16* wqkv = (const __nv_bfloat16*)d_in[1];
    const __nv_bfloat16* wo   = (const __nv_bfloat16*)d_in[2];

    static EncodeTiledFn encode = nullptr;
    static int num_sms = 0;
    static void* scratch = nullptr;
    if (!encode) {
        void* fn = nullptr;
        cudaDriverEntryPointQueryResult qr;
        cudaGetDriverEntryPoint("cuTensorMapEncodeTiled", &fn, cudaEnableDefault, &qr);
        encode = (EncodeTiledFn)fn;
        int dev = 0;
        cudaGetDevice(&dev);
        cudaDeviceGetAttribute(&num_sms, cudaDevAttrMultiProcessorCount, dev);
        cudaGetSymbolAddress(&scratch, g_scratch);
        cudaFuncSetAttribute(swin_attn_kernel<false>, cudaFuncAttributeMaxDynamicSharedMemorySize, kSmemBytes);
        cudaFuncSetAttribute(swin_attn_kernel<true>, cudaFuncAttributeMaxDynamicSharedMemorySize, kSmemBytes);
    }
    CUtensorMap tmx;
    const cuuint64_t gdim[5] = {(cuuint64_t)kC, (cuuint64_t)kHW / 2, 2, 2, (cuuint64_t)kHW / 2};
    const cuuint64_t gstr[4] = {(cuuint64_t)kC * 4, (cuuint64_t)kHW * kC * 2, (cuuint64_t)kC * 2, (cuuint64_t)kHW * kC * 4};
    const cuuint32_t box[5] = {64, 4, 2, 2, 4};
    const cuuint32_t estr[5] = {1, 1, 1, 1, 1};
    encode(&tmx, CU_TENSOR_MAP_DATA_TYPE_BFLOAT16, 5, (void*)x, gdim, gstr, box, estr, CU_TENSOR_MAP_INTERLEAVE_NONE,
           CU_TENSOR_MAP_SWIZZLE_128B, CU_TENSOR_MAP_L2_PROMOTION_NONE, CU_TENSOR_MAP_FLOAT_OOB_FILL_NONE);

    CUtensorMap tmp;
    const cuuint64_t pdim[3] = {(cuuint64_t)kC, (cuuint64_t)kHW, (cuuint64_t)kHW};
    const cuuint64_t pstr[2] = {(cuuint64_t)kC * 2, (cuuint64_t)kHW * kC * 2};
    const cuuint32_t pbox[3] = {(cuuint32_t)kC, 8, 8};
    encode(&tmp, CU_TENSOR_MAP_DATA_TYPE_BFLOAT16, 3, (void*)x, pdim, pstr, pbox, estr, CU_TENSOR_MAP_INTERLEAVE_NONE,
           CU_TENSOR_MAP_SWIZZLE_NONE, CU_TENSOR_MAP_L2_PROMOTION_NONE, CU_TENSOR_MAP_FLOAT_OOB_FILL_NONE);
    CUtensorMap tmo;
    const cuuint64_t odim[5] = {64, 6, (cuuint64_t)kHW / 4, 2, (cuuint64_t)kHW};
    const cuuint64_t ostr[4] = {128, (cuuint64_t)kC * 8, (cuuint64_t)kC * 4, (cuuint64_t)kHW * kC * 2};
    const cuuint32_t obox[5] = {64, 2, 2, 2, 2};
    encode(&tmo, CU_TENSOR_MAP_DATA_TYPE_BFLOAT16, 5, d_out, odim, ostr, obox, estr, CU_TENSOR_MAP_INTERLEAVE_NONE,
           CU_TENSOR_MAP_SWIZZLE_128B, CU_TENSOR_MAP_L2_PROMOTION_NONE, CU_TENSOR_MAP_FLOAT_OOB_FILL_NONE);
    if (num_sms >= kJobs)
        swin_attn_kernel<false><<<num_sms, kThreads, kSmemBytes, cudaStreamPerThread>>>(wqkv, wo, (__nv_bfloat16*)d_out, (Scratch*)scratch, ((Scratch*)scratch)->ticket, tmx, tmp, tmo);
    else
        swin_attn_kernel<true><<<num_sms, kThreads, kSmemBytes, cudaStreamPerThread>>>(wqkv, wo, (__nv_bfloat16*)d_out, (Scratch*)scratch, ((Scratch*)scratch)->ticket, tmx, tmp, tmo);
}
```

```cpp
#include <cuda_runtime.h>
#include <cuda_bf16.h>
#include <cuda.h>
#include <stdint.h>

namespace {

constexpr int kC      = 192;
constexpr int kHW     = 512;
#define MAXWIN 4096
constexpr int kNWin   = MAXWIN;
constexpr int kXBytes = 64 * kC * 2;
constexpr int kWBytes = kC * kC * 2;
constexpr int kNWG    = 3;
constexpr int kThreads = kNWG * 128;
constexpr int kJobsM  = 72;
constexpr int kJobs   = 120;
constexpr int kWarmW  = 4;
#define PF_LEAD 400
#define PF_UP 114
#define PF_DOWN 39
#define PF_END 300
#define PF_MIN 135
#define EF_LAST 1000
#define TRK_T0 400
#define TRK_S 1800
#define G11_DELAY 100
#define REQ_T 2650
#define REQ_TV 4000

constexpr int kOffWm  = 0;
constexpr int kOffWv  = kWBytes;
constexpr int kOffX   = 2 * kWBytes;
constexpr int kOffStage = kOffX + kNWG * kXBytes;
constexpr int kOffBar = kOffStage + 8192;
constexpr int kOffProf = kOffBar + 128;
constexpr int kSmemBytes = kOffProf;
constexpr uint32_t kSmemBase = 1024;

struct Scratch {
    uint4 wfold[2 * kWBytes / 16];
    uint32_t ticket[32];
    uint32_t cnt[32];
};
__device__ __align__(128) Scratch g_scratch;

__device__ __forceinline__ uint32_t smem_u32(const void* p) { return (uint32_t)__cvta_generic_to_shared(p); }

__device__ __forceinline__ void mbar_init(uint32_t bar, uint32_t count) {
    asm volatile("mbarrier.init.shared::cta.b64 [%0], %1;" ::"r"(bar), "r"(count) : "memory");
}
__device__ __forceinline__ void mbar_expect_tx(uint32_t bar, uint32_t bytes) {
    asm volatile("mbarrier.arrive.expect_tx.shared::cta.b64 _, [%0], %1;" ::"r"(bar), "r"(bytes) : "memory");
}
__device__ __forceinline__ void mbar_wait(uint32_t bar, uint32_t parity) {
    uint32_t ok;
    uint32_t spins = 0;
    do {
        asm volatile("{\n.reg .pred p;\n"
                     "mbarrier.try_wait.parity.shared::cta.b64 p, [%1], %2;\n"
                     "selp.b32 %0, 1, 0, p;\n}\n"
                     : "=r"(ok) : "r"(bar), "r"(parity) : "memory");
        if (++spins > (1u << 26)) __trap();
    } while (!ok);
}
__device__ __forceinline__ uint32_t tid_now() {
    uint32_t t;
    asm volatile("mov.u32 %0, %%tid.x;" : "=r"(t));
    return t;
}
__device__ __forceinline__ uint32_t nctaid_now() {
    uint32_t t;
    asm volatile("mov.u32 %0, %%nctaid.x;" : "=r"(t));
    return t;
}
__device__ __forceinline__ bool elect_one() {
    uint32_t pred;
    asm volatile("{\n.reg .pred p;\nelect.sync _|p, 0xffffffff;\nselp.b32 %0, 1, 0, p;\n}\n" : "=r"(pred));
    return pred != 0;
}
#define PASS1 10
#define PASS4 11
#define PASS2 5
#define PASS3 3
__device__ __forceinline__ void ring_wait() {
    asm volatile("bar.sync %0, 256;" ::"r"((tid_now() >> 7) + 8) : "memory");
}
__device__ __forceinline__ void ring_pass() {
    const uint32_t w = tid_now() >> 7;
    asm volatile("bar.arrive %0, 256;" ::"r"(w == kNWG - 1 ? 8u : w + 9u) : "memory");
}
constexpr uint32_t kDone = 0x40000000u;
constexpr int kPhase = 0x10000;
__device__ __forceinline__ uint32_t wg_uniform() { return __reduce_or_sync(0xffffffffu, tid_now() >> 7); }
__device__ __forceinline__ uint32_t desc_x(uint32_t w) { return (((kSmemBase + kOffX) >> 4) | (1u << 16)) + w * (kXBytes >> 4); }
__device__ __forceinline__ uint32_t desc_xt(uint32_t w) { return (((kSmemBase + kOffX) >> 4) | ((8192u >> 4) << 16)) + w * (kXBytes >> 4); }
__device__ __forceinline__ void tma_load_x_chunk(uint32_t dst, const CUtensorMap* tm, uint32_t bar, int win, int chunk) {
    asm volatile("cp.async.bulk.tensor.5d.shared::cluster.global.mbarrier::complete_tx::bytes"
                 " [%0], [%1, {%3, %4, %6, %6, %5}], [%2];"
                 ::"r"(dst), "l"(tm), "r"(bar), "r"(chunk * 64), "r"((win & 63) * 4), "r"((win >> 6) * 4), "r"(0) : "memory");
}
__device__ __forceinline__ void tma_load_x_hint(uint32_t dst, const CUtensorMap* tm, uint32_t bar, int win, bool evict_first) {
    uint64_t first, normal;
    asm("createpolicy.fractional.L2::evict_first.b64 %0, 1.0;" : "=l"(first));
    asm("createpolicy.fractional.L2::evict_normal.b64 %0, 1.0;" : "=l"(normal));
#pragma unroll
    for (int c = 0; c < 3; c++)
        asm volatile("cp.async.bulk.tensor.5d.shared::cluster.global.mbarrier::complete_tx::bytes.L2::cache_hint"
                     " [%0], [%1, {%3, %4, %6, %6, %5}], [%2], %7;"
                     ::"r"(dst + c * 8192), "l"(tm), "r"(bar), "r"(c * 64), "r"((win & 63) * 4), "r"((win >> 6) * 4), "r"(0),
                       "l"(evict_first ? first : normal) : "memory");
}
__device__ __forceinline__ void bulk_load(uint32_t dst, const void* src, uint32_t bytes, uint32_t bar) {
    asm volatile("cp.async.bulk.shared::cluster.global.mbarrier::complete_tx::bytes [%0], [%1], %2, [%3];"
                 ::"r"(dst), "l"(src), "r"(bytes), "r"(bar) : "memory");
}

__device__ __forceinline__ void wg_fence()  { asm volatile("wgmma.fence.sync.aligned;" ::: "memory"); }
__device__ __forceinline__ void wg_commit() { asm volatile("wgmma.commit_group.sync.aligned;" ::: "memory"); }
__device__ __forceinline__ void wg_wait0()  { asm volatile("wgmma.wait_group.sync.aligned 0;" ::: "memory"); }
__device__ __forceinline__ void wg_wait1()  { asm volatile("wgmma.wait_group.sync.aligned 1;" ::: "memory"); }
__device__ __forceinline__ void wg_wait2()  { asm volatile("wgmma.wait_group.sync.aligned 2;" ::: "memory"); }

template <int N> __device__ __forceinline__ void fence_regs(float (&d)[N]) {
#pragma unroll
    for (int i = 0; i < N; i++) asm volatile("" : "+f"(d[i])::"memory");
}
template <int N> __device__ __forceinline__ void fence_regs(uint32_t (&d)[N]) {
#pragma unroll
    for (int i = 0; i < N; i++) asm volatile("" : "+r"(d[i])::"memory");
}

#define ACC8(c, d, i) c(d[i]), c(d[i + 1]), c(d[i + 2]), c(d[i + 3]), c(d[i + 4]), c(d[i + 5]), c(d[i + 6]), c(d[i + 7])
#define ACC32(c, d) ACC8(c, d, 0), ACC8(c, d, 8), ACC8(c, d, 16), ACC8(c, d, 24)
#define ACC96(c, d) ACC32(c, d), ACC8(c, d, 32), ACC8(c, d, 40), ACC8(c, d, 48), ACC8(c, d, 56), \
                    ACC8(c, d, 64), ACC8(c, d, 72), ACC8(c, d, 80), ACC8(c, d, 88)
#define C_IO(x) "+f"(x)
#define C_O(x) "=f"(x)
#define REGS32 "{%0, %1, %2, %3, %4, %5, %6, %7, %8, %9, %10, %11, %12, %13, %14, %15, " \
               "%16, %17, %18, %19, %20, %21, %22, %23, %24, %25, %26, %27, %28, %29, %30, %31}"
#define REGS96 "{%0, %1, %2, %3, %4, %5, %6, %7, %8, %9, %10, %11, %12, %13, %14, %15, " \
               "%16, %17, %18, %19, %20, %21, %22, %23, %24, %25, %26, %27, %28, %29, %30, %31, " \
               "%32, %33, %34, %35, %36, %37, %38, %39, %40, %41, %42, %43, %44, %45, %46, %47, " \
               "%48, %49, %50, %51, %52, %53, %54, %55, %56, %57, %58, %59, %60, %61, %62, %63, " \
               "%64, %65, %66, %67, %68, %69, %70, %71, %72, %73, %74, %75, %76, %77, %78, %79, " \
               "%80, %81, %82, %83, %84, %85, %86, %87, %88, %89, %90, %91, %92, %93, %94, %95}"

#define DESC_HI "0x40000040"
#define MK_DESC(name, lo, off) "add.u32 t, " lo ", " off ";\nmov.b64 " name ", {t, " DESC_HI "};\n"

template <bool First, int OA, int OB> __device__ __forceinline__ void wg192_ss(float (&d)[96], uint32_t la, uint32_t lb) {
    if constexpr (First)
        asm volatile("{\n.reg .pred p;\n.reg .b32 t;\n.reg .b64 da, db;\nsetp.ne.b32 p, 0, 0;\n"
                     MK_DESC("da", "%96", "%98") MK_DESC("db", "%97", "%99")
                     "wgmma.mma_async.sync.aligned.m64n192k16.f32.bf16.bf16 " REGS96 ", da, db, p, 1, 1, 0, 0;\n}\n"
                     : ACC96(C_O, d) : "r"(la), "r"(lb), "n"(OA), "n"(OB));
    else
        asm volatile("{\n.reg .pred p;\n.reg .b32 t;\n.reg .b64 da, db;\nsetp.ne.b32 p, 1, 0;\n"
                     MK_DESC("da", "%96", "%98") MK_DESC("db", "%97", "%99")
                     "wgmma.mma_async.sync.aligned.m64n192k16.f32.bf16.bf16 " REGS96 ", da, db, p, 1, 1, 0, 0;\n}\n"
                     : ACC96(C_IO, d) : "r"(la), "r"(lb), "n"(OA), "n"(OB));
}
template <bool First, int TB, int OB> __device__ __forceinline__ void wg192_rs(float (&d)[96], const uint32_t* a, uint32_t lb) {
    if constexpr (First)
        asm volatile("{\n.reg .pred p;\n.reg .b32 t;\n.reg .b64 db;\nsetp.ne.b32 p, 0, 0;\n"
                     MK_DESC("db", "%100", "%102")
                     "wgmma.mma_async.sync.aligned.m64n192k16.f32.bf16.bf16 " REGS96 ", {%96, %97, %98, %99}, db, p, 1, 1, %101;\n}\n"
                     : ACC96(C_O, d) : "r"(a[0]), "r"(a[1]), "r"(a[2]), "r"(a[3]), "r"(lb), "n"(TB), "n"(OB));
    else
        asm volatile("{\n.reg .pred p;\n.reg .b32 t;\n.reg .b64 db;\nsetp.ne.b32 p, 1, 0;\n"
                     MK_DESC("db", "%100", "%102")
                     "wgmma.mma_async.sync.aligned.m64n192k16.f32.bf16.bf16 " REGS96 ", {%96, %97, %98, %99}, db, p, 1, 1, %101;\n}\n"
                     : ACC96(C_IO, d) : "r"(a[0]), "r"(a[1]), "r"(a[2]), "r"(a[3]), "r"(lb), "n"(TB), "n"(OB));
}
template <bool First, int OB> __device__ __forceinline__ void wg64_rs(float (&d)[32], const uint32_t* a, uint32_t lb) {
    if constexpr (First)
        asm volatile("{\n.reg .pred p;\n.reg .b32 t;\n.reg .b64 db;\nsetp.ne.b32 p, 0, 0;\n"
                     MK_DESC("db", "%36", "%37")
                     "wgmma.mma_async.sync.aligned.m64n64k16.f32.bf16.bf16 " REGS32 ", {%32, %33, %34, %35}, db, p, 1, 1, 0;\n}\n"
                     : ACC32(C_O, d) : "r"(a[0]), "r"(a[1]), "r"(a[2]), "r"(a[3]), "r"(lb), "n"(OB));
    else
        asm volatile("{\n.reg .pred p;\n.reg .b32 t;\n.reg .b64 db;\nsetp.ne.b32 p, 1, 0;\n"
                     MK_DESC("db", "%36", "%37")
                     "wgmma.mma_async.sync.aligned.m64n64k16.f32.bf16.bf16 " REGS32 ", {%32, %33, %34, %35}, db, p, 1, 1, 0;\n}\n"
                     : ACC32(C_IO, d) : "r"(a[0]), "r"(a[1]), "r"(a[2]), "r"(a[3]), "r"(lb), "n"(OB));
}
template <bool First, int OA, int OB> __device__ __forceinline__ void wg64_ss(float (&d)[32], uint32_t la, uint32_t lb) {
    if constexpr (First)
        asm volatile("{\n.reg .pred p;\n.reg .b32 t;\n.reg .b64 da, db;\nsetp.ne.b32 p, 0, 0;\n"
                     MK_DESC("da", "%32", "%34") MK_DESC("db", "%33", "%35")
                     "wgmma.mma_async.sync.aligned.m64n64k16.f32.bf16.bf16 " REGS32 ", da, db, p, 1, 1, 0, 1;\n}\n"
                     : ACC32(C_O, d) : "r"(la), "r"(lb), "n"(OA), "n"(OB));
    else
        asm volatile("{\n.reg .pred p;\n.reg .b32 t;\n.reg .b64 da, db;\nsetp.ne.b32 p, 1, 0;\n"
                     MK_DESC("da", "%32", "%34") MK_DESC("db", "%33", "%35")
                     "wgmma.mma_async.sync.aligned.m64n64k16.f32.bf16.bf16 " REGS32 ", da, db, p, 1, 1, 0, 1;\n}\n"
                     : ACC32(C_IO, d) : "r"(la), "r"(lb), "n"(OA), "n"(OB));
}
__host__ __device__ constexpr int koff(int kk, int chunk) { return ((kk >> 2) * chunk + (kk & 3) * 32) >> 4; }

__device__ __forceinline__ uint32_t clock_now() {
    uint32_t t;
    asm volatile("mov.u32 %0, %%clock;" : "=r"(t));
    return t;
}
template <int K> __device__ __forceinline__ void stage_put(const uint4 (&h)[12], uint32_t buf) {
    const uint32_t t = tid_now(), line = ((t >> 2) & 2) + (t & 4) + ((t >> 1) & 8);
    const uint32_t adr = buf + line * 128 + (((t & 3) ^ (line & 7)) << 4);
#pragma unroll
    for (int j = 0; j < 4; j++) {
        const int i = 4 * K + j, n = 2 * (i % 6) + i / 6;
        asm volatile("st.shared.v4.b32 [%4], {%0, %1, %2, %3};"
                     :: "r"(h[n].x), "r"(h[n].y), "r"(h[n].z), "r"(h[n].w), "r"((adr ^ ((j & 1) * 64 + (j >> 1) * 16)) + (j >> 1) * 128) : "memory");
    }
}
__device__ __forceinline__ void stage_send(const CUtensorMap* tm, uint32_t pos, int k, uint32_t buf) {
    asm volatile("fence.proxy.async.shared::cta;" ::: "memory");
    __syncwarp();
    if (elect_one()) {
        asm volatile("cp.async.bulk.tensor.5d.global.shared::cta.bulk_group [%0, {%2, %5, %3, %2, %4}], [%1];"
                     ::"l"(tm), "r"(buf), "r"(0), "r"(pos & 0xffff), "r"(pos >> 16), "r"(2 * k) : "memory");
        asm volatile("cp.async.bulk.commit_group;" ::: "memory");
    }
    __syncwarp();
}
__device__ __forceinline__ void stage_wait() {
    asm volatile("cp.async.bulk.wait_group.read 0;" ::: "memory");
    __syncwarp();
}
__device__ __forceinline__ uint32_t out_pos(int win) {
    return ((win & 63) * 2) | ((((win >> 6) & 63) * 8 + 2 * ((tid_now() >> 5) & 3)) << 16);
}
__device__ __forceinline__ uint32_t stage_buf() { return kSmemBase + kOffStage + ((tid_now() >> 5) & 3) * 2048; }
template <int K> __device__ __forceinline__ void stage_window(uint4 (&h)[12], const CUtensorMap* tm, uint32_t pos, [[maybe_unused]] int win) {
    if constexpr (K < 3) {
        if constexpr (K > 0) stage_wait();
        stage_put<K>(h, stage_buf());
        stage_send(tm, pos, K, stage_buf());
        stage_window<K + 1>(h, tm, pos, win);
    }
}
__device__ __forceinline__ void stg128(void* p, uint4 v) {
    asm volatile("st.global.v4.b32 [%0], {%1, %2, %3, %4};" ::"l"(p), "r"(v.x), "r"(v.y), "r"(v.z), "r"(v.w) : "memory");
}
#define TAIL_DT 90
#define TAIL_FREE 2
template <int J> __device__ __forceinline__ void store_tail(uint4 (&h)[12], uint8_t* hptr, uint32_t t0) {
    if constexpr (J < 12) {
        if (J > TAIL_FREE) { while (clock_now() - t0 < (uint32_t)((J - TAIL_FREE) * TAIL_DT)) {} }
        stg128(hptr + J * 64, h[2 * (J % 6) + J / 6]);
        store_tail<J + 1>(h, hptr, t0);
    }
}
__device__ __forceinline__ uint8_t* out_address(__nv_bfloat16* out, uint32_t pos) {
    const uint32_t ln = tid_now() & 31;
    return reinterpret_cast<uint8_t*>(out) + (((pos >> 16) + (ln >> 4)) * kHW + (pos & 0xffff) * 4 + ((ln >> 1) & 6)) * (uint32_t)(kC * 2) + (ln & 3) * 16;
}
template <int K0, int K> struct Gemm1 {
    static __device__ __forceinline__ void run(float (&d)[96], uint32_t lx, uint32_t lw) {
        if constexpr (K > K0) Gemm1<K0, K - 1>::run(d, lx, lw);
        wg192_ss<K == 0, koff(K, 8192), koff(K, 24576)>(d, lx, lw);
    }
};
__device__ __forceinline__ uint32_t draw_ticket(uint32_t* counter) {
    uint32_t ticket = 0;
    asm volatile("{\n.reg .pred p;\nsetp.eq.u32 p, %2, 0;\n@p atom.relaxed.gpu.global.inc.u32 %0, [%1], %3;\n}\n"
                 : "+r"(ticket) : "l"(counter), "r"(tid_now() & 127), "n"(kNWin - 1) : "memory");
    return ticket;
}
template <int KK> struct Gemm2 { static __device__ __forceinline__ void run(float (&d)[32], const uint32_t* a, uint32_t lx) {
    Gemm2<KK - 1>::run(d, a, lx); wg64_rs<KK == 0, koff(KK, 8192)>(d, a + 4 * KK, lx);
    if constexpr (KK == PASS2 && KK < 11) ring_pass(); } };
template <> struct Gemm2<-1> { static __device__ __forceinline__ void run(float (&)[32], const uint32_t*, uint32_t) {} };
template <int KK> struct Gemm3 { static __device__ __forceinline__ void run(float (&d)[96], const uint32_t* a, uint32_t lxt) {
    Gemm3<KK - 1>::run(d, a, lxt); wg192_rs<KK == 0, 1, KK * (2048 >> 4)>(d, a + 4 * KK, lxt);
    if constexpr (KK == PASS3 && KK < 3) ring_pass(); } };
template <> struct Gemm3<-1> { static __device__ __forceinline__ void run(float (&)[96], const uint32_t*, uint32_t) {} };
template <int K0, int KK> struct Gemm4 { static __device__ __forceinline__ void run(float (&d)[96], const uint32_t* a, uint32_t lw) {
    if constexpr (KK > K0) Gemm4<K0, KK - 1>::run(d, a, lw);
    wg192_rs<KK == 0, 0, koff(KK, 24576)>(d, a + 4 * KK, lw); } };

template <int J, int KK> struct Gemm3s { static __device__ __forceinline__ void run(float (&d)[32], uint32_t lp, uint32_t lxt) {
    if constexpr (KK > 0) Gemm3s<J, KK - 1>::run(d, lp, lxt);
    wg64_ss<KK == 0, KK * 2, (J * 8192 + KK * 2048) / 16>(d, lp, lxt); } };
template <int J, int K0, int KK> struct Gemm4s { static __device__ __forceinline__ void run(float (&d)[32], const uint32_t* a, uint32_t lw) {
    if constexpr (KK > K0) Gemm4s<J, K0, KK - 1>::run(d, a, lw);
    wg64_rs<KK == 0, koff(KK, 24576) + J * (8192 / 16)>(d, a + 4 * KK, lw); } };

__device__ __forceinline__ uint32_t pack_bf16(float lo, float hi) {
    uint32_t r;
    asm("cvt.rn.bf16x2.f32 %0, %1, %2;" : "=r"(r) : "f"(hi), "f"(lo));
    return r;
}
__device__ __forceinline__ float ex2(float x) {
    float r;
    asm("ex2.approx.ftz.f32 %0, %1;" : "=f"(r) : "f"(x));
    return r;
}
__device__ __forceinline__ float rcp(float x) {
    float r;
    asm("rcp.approx.ftz.f32 %0, %1;" : "=f"(r) : "f"(x));
    return r;
}

__device__ __forceinline__ void pack_slice(uint32_t* a, float (&d)[32]) {
    fence_regs(d);
#pragma unroll
    for (int i = 0; i < 16; i++) a[i] = pack_bf16(d[2 * i], d[2 * i + 1]);
#pragma unroll
    for (int i = 0; i < 16; i++) asm volatile("" : "+r"(a[i])::"memory");
}
template <int J> __device__ __forceinline__ void store_slice(float (&d)[32], uint8_t* hptr) {
    fence_regs(d);
#pragma unroll
    for (int r = 0; r < 2; r++) {
        uint4 h[2];
#pragma unroll
        for (int a = 0; a < 2; a++) {
            const int o = 16 * a + 2 * r;
            h[a] = make_uint4(pack_bf16(d[o], d[o + 1]), pack_bf16(d[o + 4], d[o + 5]), pack_bf16(d[o + 8], d[o + 9]), pack_bf16(d[o + 12], d[o + 13]));
        }
        stg128(hptr + r * (kC * 2) + J * 128, h[0]);
        stg128(hptr + r * (kC * 2) + J * 128 + 64, h[1]);
    }
    __syncwarp();
}
__device__ __forceinline__ void store_p_if(const uint32_t (&pa)[16], bool cond) {
    const uint32_t t = tid_now(), row = ((t >> 1) & 48) + (t & 15);
    const uint32_t adr = kSmemBase + kOffStage + row * 128 + ((((t >> 4) & 1) ^ (t & 7)) << 4);
#pragma unroll
    for (int i = 0; i < 4; i++)
        asm volatile("{\n.reg .pred p;\nsetp.ne.u32 p, %5, 0;\n@p stmatrix.sync.aligned.m8n8.x4.shared.b16 [%4], {%0, %1, %2, %3};\n}\n"
                     :: "r"(pa[4 * i]), "r"(pa[4 * i + 1]), "r"(pa[4 * i + 2]), "r"(pa[4 * i + 3]), "r"(adr ^ (i << 5)), "r"((uint32_t)cond) : "memory");
}
__device__ __forceinline__ void last_window(__nv_bfloat16* out, int win) {
    constexpr uint32_t dWv = ((kSmemBase + kOffWv) >> 4) | (1u << 16);
    asm volatile("fence.proxy.async.shared::cta;" ::: "memory");
    const uint32_t w = wg_uniform();
    const uint32_t dXt = desc_xt(w);
    constexpr uint32_t dP = ((kSmemBase + kOffStage) >> 4) | (1u << 16);
    float u0[32], u1[32], u2[32];
    uint32_t fa[48];
    uint8_t* hptr = out_address(out, out_pos(win));
    asm volatile("" : "+l"(hptr) :: "memory");
    ring_wait();
    wg_fence();
    Gemm3s<0, 3>::run(u0, dP, dXt); wg_commit();
    Gemm3s<1, 3>::run(u1, dP, dXt); wg_commit();
    Gemm3s<2, 3>::run(u2, dP, dXt); wg_commit();
    wg_wait2();
    pack_slice(fa, u0);
    wg_fence();
    Gemm4s<0, 0, 3>::run(u0, fa, dWv); wg_commit();
    wg_wait2();
    pack_slice(fa + 16, u1);
    wg_fence();
    Gemm4s<0, 4, 7>::run(u0, fa, dWv); wg_commit();
    wg_wait2();
    pack_slice(fa + 32, u2);
    wg_fence();
    Gemm4s<0, 8, 11>::run(u0, fa, dWv); wg_commit();
    Gemm4s<1, 0, 5>::run(u1, fa, dWv); wg_commit();
    wg_wait1();
    store_slice<0>(u0, hptr);
    wg_fence();
    Gemm4s<1, 6, 11>::run(u1, fa, dWv); wg_commit();
    Gemm4s<2, 0, 5>::run(u2, fa, dWv); wg_commit();
    wg_wait1();
    store_slice<1>(u1, hptr);
    wg_fence();
    Gemm4s<2, 6, 11>::run(u2, fa, dWv); wg_commit();
    wg_wait0();
    fence_regs(fa);
    store_slice<2>(u2, hptr);
}

__device__ __forceinline__ int fold_offset(int n, int k0, int q) {
    const int u = ((k0 & 63) >> 3) + (q >> 1);
    return (k0 >> 6) * 24576 + (q & 1) * 8 + n * 128 + ((u ^ (n & 7)) << 4);
}
__device__ __forceinline__ void mma16816x2(float (&c)[4], float (&d)[4], const uint32_t (&a)[4], const uint32_t (&b)[4]) {
    asm volatile("mma.sync.aligned.m16n8k16.row.col.f32.bf16.bf16.f32 {%0,%1,%2,%3}, {%8,%9,%10,%11}, {%12,%13}, {%0,%1,%2,%3};\n"
                 "mma.sync.aligned.m16n8k16.row.col.f32.bf16.bf16.f32 {%4,%5,%6,%7}, {%8,%9,%10,%11}, {%14,%15}, {%4,%5,%6,%7};"
                 : "+f"(c[0]), "+f"(c[1]), "+f"(c[2]), "+f"(c[3]), "+f"(d[0]), "+f"(d[1]), "+f"(d[2]), "+f"(d[3])
                 : "r"(a[0]), "r"(a[1]), "r"(a[2]), "r"(a[3]), "r"(b[0]), "r"(b[1]), "r"(b[2]), "r"(b[3]));
}
__device__ __forceinline__ void cp_async16(uint32_t dst, const void* src) {
    asm volatile("cp.async.cg.shared.global [%0], [%1], 16;" ::"r"(dst), "l"(src) : "memory");
}
template <bool kTrans> __device__ __forceinline__ void ldsm4(uint32_t (&r)[4], uint32_t addr) {
    if constexpr (kTrans)
        asm volatile("ldmatrix.sync.aligned.m8n8.x4.trans.shared.b16 {%0, %1, %2, %3}, [%4];" : "=r"(r[0]), "=r"(r[1]), "=r"(r[2]), "=r"(r[3]) : "r"(addr) : "memory");
    else
        asm volatile("ldmatrix.sync.aligned.m8n8.x4.shared.b16 {%0, %1, %2, %3}, [%4];" : "=r"(r[0]), "=r"(r[1]), "=r"(r[2]), "=r"(r[3]) : "r"(addr) : "memory");
}
__device__ __forceinline__ uint32_t nonzero(uint32_t w) { return w ? w : 0x80000000u; }
__device__ __forceinline__ void fold_job(Scratch* sc, const __nv_bfloat16* __restrict__ wqkv, const __nv_bfloat16* __restrict__ wo,
                                         int job, int warp, int lane) {
    const bool vo = job >= kJobsM;
    const int nw = vo ? 3 : 2, tile0 = vo ? 3 * (job - kJobsM) : 2 * job;
    const int n0 = (tile0 / 12) * 16, k0 = (tile0 % 12 + max(warp, 1) - 1) * 16;
    const uint32_t stage = kSmemBase + kOffWv;
    if (warp <= nw) {
        if (vo && warp == 0) {
            const char* src = reinterpret_cast<const char*>(wo + (lane >> 1) * kC + n0 + (lane & 1) * 8);
            const uint32_t dst = stage + ((lane ^ ((lane >> 3) & 1)) << 4);
#pragma unroll
            for (int i = 0; i < 12; i++) cp_async16(dst + i * 512, src + i * 16 * kC * 2);
        } else {
            const int row0 = warp == 0 ? n0 : k0, col0 = warp == 0 ? kC : vo ? 2 * kC : 0;
            const char* src = reinterpret_cast<const char*>(wqkv + (row0 + (lane >> 3)) * (3 * kC) + col0 + (lane & 7) * 8);
            const uint32_t dst = stage + warp * 6144 + (lane >> 3) * 384 + (((lane & 7) ^ (lane >> 3)) << 4);
#pragma unroll
            for (int i = 0; i < 12; i++) cp_async16((dst ^ (((i / 3) & 1) << 6)) + (i / 3) * 1536 + (i % 3) * 128, src + (i / 3) * 4 * 3 * kC * 2 + (i % 3) * 128);
        }
        asm volatile("cp.async.wait_all;" ::: "memory");
        asm volatile("bar.sync 13, %0;" ::"r"(32 * nw + 32) : "memory");
    }
    if (warp == 0 || (warp > nw && warp != kWarmW)) return;
    const int g = lane >> 2, q = lane & 3, mi = lane >> 3, r8 = lane & 7;
    uint32_t A[12][4], B[12][4];
    {
        const int row = 4 * (r8 >> 1) + (r8 & 1) + 2 * (mi >> 1);
        const uint32_t base = stage + warp * 6144 + row * 384 + (((mi & 1) ^ (row & 7)) << 4);
#pragma unroll
        for (int ks = 0; ks < 12; ks++) ldsm4<false>(B[ks], (base ^ ((ks & 3) << 5)) + (ks >> 2) * 128);
    }
    if (vo) {
        const int c = r8 + 8 * (mi >> 1);
        const uint32_t base = stage + (((2 * c + (mi & 1)) ^ ((c >> 2) & 1)) << 4);
#pragma unroll
        for (int ks = 0; ks < 12; ks++) ldsm4<true>(A[ks], base + ks * 512);
    } else {
        const uint32_t base = stage + (r8 + 8 * (mi & 1)) * 384 + (((mi >> 1) ^ r8) << 4);
#pragma unroll
        for (int ks = 0; ks < 12; ks++) ldsm4<false>(A[ks], (base ^ ((ks & 3) << 5)) + (ks >> 2) * 128);
    }
    float c0[4] = {0.f, 0.f, 0.f, 0.f}, c1[4] = {0.f, 0.f, 0.f, 0.f}, c2[4] = {0.f, 0.f, 0.f, 0.f}, c3[4] = {0.f, 0.f, 0.f, 0.f};
#pragma unroll
    for (int ks = 0; ks < 12; ks += 2) {
        mma16816x2(c0, c1, A[ks], B[ks]);
        mma16816x2(c2, c3, A[ks + 1], B[ks + 1]);
    }
#pragma unroll
    for (int i = 0; i < 4; i++) { c0[i] += c2[i]; c1[i] += c3[i]; }
    const int ch = n0 + g;
    const int n = vo ? 32 * (ch >> 5) + 8 * ((ch >> 1) & 3) + 2 * ((ch >> 3) & 3) + (ch & 1) : ch;
    char* img = reinterpret_cast<char*>(sc->wfold) + (vo ? kWBytes : 0);
    asm volatile("{\n.reg .pred p;\nsetp.ne.u32 p, %6, %7;\n@p st.global.v2.u32 [%0], {%2, %3};\n@p st.global.v2.u32 [%1], {%4, %5};\n}\n"
                 ::"l"(img + fold_offset(n, k0, q)), "l"(img + fold_offset(n + (vo ? 2 : 8), k0, q)),
                   "r"(nonzero(pack_bf16(c0[0], c0[1]))), "r"(nonzero(pack_bf16(c1[0], c1[1]))), "r"(nonzero(pack_bf16(c0[2], c0[3]))), "r"(nonzero(pack_bf16(c1[2], c1[3]))),
                   "r"(warp), "n"(kWarmW) : "memory");
}

__device__ __forceinline__ bool bar_or(uint32_t id, uint32_t n, bool pred) {
    uint32_t r;
    asm volatile("{\n.reg .pred p, q;\nsetp.ne.u32 q, %3, 0;\nbar.red.or.pred p, %1, %2, q;\nselp.u32 %0, 1, 0, p;\n}\n"
                 : "=r"(r) : "r"(id), "r"(n), "r"((uint32_t)pred) : "memory");
    return r != 0;
}
__device__ __forceinline__ bool chunk_incomplete(uint32_t base) {
    const uint32_t t = tid_now(), r = (t >> 2) & 7;
    const uint32_t adr = base + (((t >> 5) & 3) * 48 + r) * 128 + (t & 3) * 32 + r * 4;
    uint32_t m = ~0u;
#pragma unroll
    for (int j = 0; j < 6; j++) {
        uint32_t v;
        asm volatile("ld.shared.u32 %0, [%1];" : "=r"(v) : "r"(adr + j * 1024) : "memory");
        m = min(m, v);
    }
    return m == 0;
}
__device__ __forceinline__ void load_image(uint32_t dst, const void* src, uint32_t bar) {
    mbar_expect_tx(bar, kWBytes);
#pragma unroll
    for (int c = 0; c < 3; c++) bulk_load(dst + c * 24576, reinterpret_cast<const char*>(src) + c * 24576, 24576, bar);
}
__device__ __forceinline__ void repair_image(uint32_t dst, const void* src, uint32_t bar, uint32_t par) {
    uint32_t tries = 0;
    bool bad;
    do {
        if (((tid_now() >> 5) & 3) == 0) {
            if (elect_one()) {
                asm volatile("fence.proxy.async;" ::: "memory");
                load_image(dst, src, bar);
            }
            __syncwarp();
        }
        mbar_wait(bar, par);
        par ^= 1;
        bad = chunk_incomplete(dst) | chunk_incomplete(dst + 24576) | chunk_incomplete(dst + 2 * 24576);
        if (++tries > (1u << 16)) __trap();
    } while (bar_or((tid_now() >> 7) + 1, 128, bad));
}
__device__ __forceinline__ void count_image(Scratch* sc) {
    asm volatile("red.relaxed.gpu.global.inc.u32 [%0], %1;" ::"l"(sc->cnt), "r"(3 * nctaid_now() - 1) : "memory");
}
__device__ __forceinline__ uint32_t ld_acquire(const uint32_t* p) {
    uint32_t v;
    asm volatile("ld.acquire.gpu.global.u32 %0, [%1];" : "=r"(v) : "l"(p) : "memory");
    return v;
}
__device__ __noinline__ void clear_images(Scratch* sc) {
    const uint32_t g = gridDim.x, t = threadIdx.x & 127;
    if (t == 0) {
        uint32_t spins = 0;
        while (ld_acquire(sc->cnt) < 2 * g) { if (++spins > (1u << 24)) __trap(); }
    }
    asm volatile("bar.sync %0, 128;" ::"r"((threadIdx.x >> 7) + 1) : "memory");
    for (uint32_t i = blockIdx.x * 64 + t; t < 64 && i < 2 * kWBytes / 16; i += g * 64) sc->wfold[i] = make_uint4(0, 0, 0, 0);
    if (t == 0) count_image(sc);
}
__device__ __forceinline__ void prefetch_x(const CUtensorMap* tm, int win) {
    const int wh = win >> 6, ww = win & 63;
    asm volatile("cp.async.bulk.prefetch.tensor.3d.L2.global.tile [%0, {%1, %2, %3}];"
                 ::"l"(tm), "r"(0), "r"(ww * 8), "r"(wh * 8) : "memory");
}
__device__ __forceinline__ void prefetch_x_chunk(const CUtensorMap* tm, int win, int chunk) {
    asm volatile("cp.async.bulk.prefetch.tensor.5d.L2.global.tile [%0, {%1, %2, %4, %4, %3}];"
                 ::"l"(tm), "r"(chunk * 64), "r"((win & 63) * 4), "r"((win >> 6) * 4), "r"(0) : "memory");
}

__device__ __forceinline__ void prefetch_for_ticket(const CUtensorMap* tmp, int t) {
    const int base = kNWG * (int)gridDim.x;
    auto lead = [&](int tt) {
        int down = max(((kNWin - PF_END - base - tt) * PF_DOWN) >> 8, PF_MIN);
        return min(min((int)gridDim.x + ((tt * PF_UP) >> 8), PF_LEAD), down);
    };
    const int hi = base + t + lead(t);
    int lo = max(base + t - 1 + lead(t - 1), base + t) + 1;
#pragma unroll 1
    for (; lo <= hi && lo < kNWin; lo++) prefetch_x(tmp, lo);
}

template <bool kFewSMs>
__global__ void __launch_bounds__(kThreads, 1)
swin_attn_kernel(const __nv_bfloat16* __restrict__ wqkv, const __nv_bfloat16* __restrict__ wo, __nv_bfloat16* __restrict__ out, Scratch* sc, uint32_t* tickets,
                 const __grid_constant__ CUtensorMap tmx, const __grid_constant__ CUtensorMap tmp, const __grid_constant__ CUtensorMap tmo) {
    extern __shared__ uint8_t smem_raw[];
    constexpr uint32_t sbase = kSmemBase;
    const uint32_t t_start = clock_now();
    asm volatile("{\n.reg .pred p, q;\n.reg .b32 i, j;\n.reg .b64 a, b;\nmad.lo.u32 i, %2, 14, %3;\nsetp.lt.u32 p, %3, 14;\nsetp.lt.and.u32 p, i, 1728, p;\n"
                 "mad.wide.u32 a, i, 128, %0;\n@p prefetch.global.L2 [a];\n"
                 "mad.lo.u32 j, %2, 5, %3;\nsetp.lt.u32 q, %3, 5;\nsetp.lt.and.u32 q, j, 576, q;\n"
                 "mad.wide.u32 b, j, 128, %1;\n@q prefetch.global.L2 [b];\n}\n" ::"l"(wqkv), "l"(wo), "r"(blockIdx.x), "r"(threadIdx.x) : "memory");
    if (smem_u32(smem_raw) != kSmemBase) __trap();
    const int tid = threadIdx.x, lane = tid & 31;
    const uint32_t warpu = __reduce_or_sync(0xffffffffu, (uint32_t)tid >> 5), wgu = warpu >> 2;
    const int warp = (int)warpu, wg = (int)wgu;
    const int G = gridDim.x;
    const uint32_t bar_full = sbase + kOffBar + 8 * wg;
    const uint32_t bar_w0 = sbase + kOffBar + 32, bar_w1 = bar_w0 + 8;
    int win = wg * G + blockIdx.x;

    if (warp > kWarmW) {
        if (warp == 10) {
            asm volatile("bar.sync 15, 64;" ::: "memory");
            asm volatile("bar.arrive 0, %0;" ::"n"(kThreads) : "memory");
            if (lane == 0) {
                asm volatile("prefetch.tensormap [%0];" ::"l"(&tmx) : "memory");
                asm volatile("prefetch.tensormap [%0];" ::"l"(&tmp) : "memory");
                const uint32_t due = (uint32_t)(blockIdx.x * TRK_S) / (uint32_t)G;
#pragma unroll 1
                for (int c = 0; c < 6; c++) {
                    while (clock_now() - t_start < TRK_T0 + (due + c * TRK_S) / 3) {}
                    if (c < 2) tma_load_x_chunk(sbase + kOffX + c * 8192, &tmx, bar_w0 + 16 * c, blockIdx.x, c);
                    else prefetch_x_chunk(&tmx, (c / 3) * G + blockIdx.x, c % 3);
                }
                while (clock_now() - t_start < TRK_T0 + due + 2 * TRK_S) {}
                prefetch_x(&tmp, 2 * G + blockIdx.x);
            }
            __syncwarp();
        } else if (warp == 11) {
            if (lane == 0) {
#pragma unroll
                for (int w = 0; w < kNWG; w++) mbar_init(sbase + kOffBar + 8 * w, 1);
                mbar_init(sbase + kOffBar + 24, 1);
                mbar_init(sbase + kOffBar + 88, 1);
                mbar_init(sbase + kOffBar + 96, 1);
                mbar_init(bar_w0, 1);
                mbar_init(bar_w1, 1);
                mbar_init(sbase + kOffBar + 48, 1);
                mbar_init(sbase + kOffBar + 56, 1);
                asm volatile("st.shared.v4.u32 [%0], {%1, %1, %1, %1};" ::"r"(sbase + kOffBar + 64), "r"(0) : "memory");
                asm volatile("fence.mbarrier_init.release.cluster;" ::: "memory");
                asm volatile("mbarrier.arrive.shared::cta.b64 _, [%0];" ::"r"(sbase + kOffBar) : "memory");
            }
            __syncwarp();
            asm volatile("bar.arrive 15, 64;" ::: "memory");
            asm volatile("bar.arrive 0, %0;" ::"n"(kThreads) : "memory");
            if (elect_one()) {
                const char* img = reinterpret_cast<const char*>(sc->wfold);
#pragma unroll
                for (int c = 0; c < 3; c++) mbar_expect_tx(c == 0 ? bar_w0 : sbase + kOffBar + 40 + 8 * c, 24576 + 8192);
#pragma unroll
                for (int c = 0; c < 3; c++) mbar_expect_tx(sbase + kOffBar + (c == 0 ? 8 : 80 + 8 * c), 8192);
                while (clock_now() - t_start < REQ_T) {}
#pragma unroll
                for (int c = 0; c < 3; c++) {
                    const uint32_t bar = c == 0 ? bar_w0 : sbase + kOffBar + 40 + 8 * c;
                    if (c == 2) tma_load_x_chunk(sbase + kOffX + c * 8192, &tmx, bar, blockIdx.x, c);
                    bulk_load(sbase + kOffWm + c * 24576, img + c * 24576, 24576, bar);
                }
                mbar_wait(bar_w0, 0);
#pragma unroll
                for (int c = 0; c < 3; c++)
                    tma_load_x_chunk(sbase + kOffX + kXBytes + c * 8192, &tmx, sbase + kOffBar + (c == 0 ? 8 : 80 + 8 * c), G + blockIdx.x, c);
            }
            __syncwarp();
        } else {
            asm volatile("bar.sync 0, %0;" ::"n"(kThreads) : "memory");
            if (warp == 9) {
                if (elect_one()) {
                    while (clock_now() - t_start < REQ_TV) {}
                    mbar_wait(sbase + kOffBar + 48, 0);
                    asm volatile("fence.proxy.async.shared::cta;" ::: "memory");
                    load_image(sbase + kOffWv, reinterpret_cast<const char*>(sc->wfold) + kWBytes, bar_w1);
                    mbar_expect_tx(sbase + kOffBar + 16, kXBytes);
#pragma unroll
                    for (int c = 0; c < 3; c++) tma_load_x_chunk(sbase + kOffX + 2 * kXBytes + c * 8192, &tmx, sbase + kOffBar + 16, 2 * G + blockIdx.x, c);
                }
                __syncwarp();
            }
        }
    } else {
        if constexpr (kFewSMs) {
#pragma unroll 1
            for (int j = blockIdx.x; j < kJobs; j += G) {
                fold_job(sc, wqkv, wo, j, warp, lane);
                asm volatile("bar.sync 14, %0;" ::"n"(32 * kWarmW + 32) : "memory");
            }
        } else {
            if (blockIdx.x < kJobs) fold_job(sc, wqkv, wo, blockIdx.x, warp, lane);
        }
        asm volatile("bar.sync 0, %0;" ::"n"(kThreads) : "memory");
    }
    if (wg == kNWG - 1) asm volatile("bar.sync 7, 128;" ::: "memory");
    if (wg == 1) {
        mbar_wait(bar_w0, 0);
        bool bad = chunk_incomplete(sbase + kOffWm);
        mbar_wait(sbase + kOffBar + 48, 0);
        bad |= chunk_incomplete(sbase + kOffWm + 24576);
        mbar_wait(sbase + kOffBar + 56, 0);
        bad |= chunk_incomplete(sbase + kOffWm + 2 * 24576);
        asm volatile("bar.arrive 8, 256;" ::: "memory");
        if (bar_or(11, 256, bad)) {
            repair_image(sbase + kOffWm, sc->wfold, sbase + kOffBar + 24, 0);
            asm volatile("bar.arrive 11, 256;" ::: "memory");
        }
        if (tid == 128) count_image(sc);
    } else if (wg == 2) {
        mbar_wait(bar_w1, 0);
        const bool bad = chunk_incomplete(sbase + kOffWv) | chunk_incomplete(sbase + kOffWv + 24576) | chunk_incomplete(sbase + kOffWv + 2 * 24576);
        if (bar_or(3, 128, bad)) {
            repair_image(sbase + kOffWv, reinterpret_cast<const char*>(sc->wfold) + kWBytes, bar_w1, 1);
        }
        if (tid == 256) count_image(sc);
    }

    constexpr uint32_t dWm = ((sbase + kOffWm) >> 4) | (1u << 16);
    constexpr uint32_t dWv = ((sbase + kOffWv) >> 4) | (1u << 16);
    const float cs = 0.07216878364870322f * 1.4426950408889634f;
    mbar_wait(bar_w0, 0);
    mbar_wait(bar_full, 0);

    uint4 hv[12];
    uint32_t pos;
    float acc[96];
    uint32_t ticket = 0;
    {
        const uint32_t dX = desc_x(wg_uniform());
        if (wg != 0) ring_wait();
        if (wg == 1) {
            __syncwarp();
            const uint32_t t1 = clock_now();
            while (clock_now() - t1 < G11_DELAY) {}
        }
        wg_fence();
        Gemm1<0, 3>::run(acc, dX, dWm);
        const uint32_t bar_c1 = sbase + kOffBar + (wg == 1 ? 88 : 48);
        mbar_wait(bar_c1, 0);
        wg_fence();
        Gemm1<4, 7>::run(acc, dX, dWm);
        mbar_wait(bar_c1 + 8, 0);
        wg_fence();
        Gemm1<8, 11>::run(acc, dX, dWm);
        wg_commit();
        if (wg != 0) asm volatile("bar.arrive 8, 256;" ::: "memory");
        if (warp == 5) {
            if (elect_one()) prefetch_x(&tmp, kNWG * G + blockIdx.x);
            __syncwarp();
        }
        ticket = draw_ticket(tickets);
        const bool redo = wg == 0 && bar_or(11, 256, false);
        wg_wait0();
        if (redo) {
            asm volatile("bar.sync 11, 256;" ::: "memory");
            wg_fence();
            Gemm1<0, 11>::run(acc, dX, dWm);
            wg_commit();
            wg_wait0();
        }
        __syncwarp();
    }

    while (true) {
        uint32_t fa[48];
        const uint32_t dX = desc_x(wg_uniform());
        fence_regs(acc);
#pragma unroll
        for (int i = 0; i < 48; i++) fa[i] = pack_bf16(acc[2 * i], acc[2 * i + 1]);

        float s[32];
        fence_regs(fa);
        wg_fence();
        ring_wait();
        Gemm2<11>::run(s, fa, dX);
        wg_commit();
        if constexpr (PASS2 == 11) ring_pass();
        if (((tid_now() >> 5) & 3) == 0) {
            if ((tid_now() & 31) == 0) {
                uint32_t nxt = kNWG * nctaid_now() + ticket;
                if (nxt >= kNWin) {
                    uint32_t p0, p1, p2, p3;
                    asm volatile("ld.shared.v4.u32 {%0, %1, %2, %3}, [%4];" : "=r"(p0), "=r"(p1), "=r"(p2), "=r"(p3) : "r"(sbase + kOffBar + 64) : "memory");
                    nxt = kDone + (p0 >> 30) + (p1 >> 30) + (p2 >> 30);
                }
                asm volatile("st.shared.u32 [%0], %1;" ::"r"(sbase + kOffBar + 64 + 4 * (tid_now() >> 7)), "r"(nxt) : "memory");
            }
            __syncwarp();
            asm volatile("bar.arrive %0, 128;" ::"r"((tid_now() >> 7) + 4) : "memory");
        }
        asm volatile("cp.async.bulk.wait_group.read 0;" ::: "memory");
        asm volatile("bar.arrive 15, 256;" ::: "memory");
        wg_wait0();
        fence_regs(s);
        fence_regs(fa);

        uint32_t pa[16];
        {
            float a0[8], a1[8];
#pragma unroll
            for (int j = 0; j < 8; j++) { a0[j] = fmaxf(s[4 * j], s[4 * j + 1]); a1[j] = fmaxf(s[4 * j + 2], s[4 * j + 3]); }
#pragma unroll
            for (int d = 4; d > 0; d >>= 1)
#pragma unroll
                for (int j = 0; j < d; j++) { a0[j] = fmaxf(a0[j], a0[j + d]); a1[j] = fmaxf(a1[j], a1[j + d]); }
            float m0 = a0[0], m1 = a1[0];
            m0 = fmaxf(m0, __shfl_xor_sync(0xffffffffu, m0, 1));
            m1 = fmaxf(m1, __shfl_xor_sync(0xffffffffu, m1, 1));
            m0 = fmaxf(m0, __shfl_xor_sync(0xffffffffu, m0, 2));
            m1 = fmaxf(m1, __shfl_xor_sync(0xffffffffu, m1, 2));
            m0 *= cs; m1 *= cs;
            float l0 = 0.f, l1 = 0.f;
#pragma unroll
            for (int j = 0; j < 8; j++) {
                s[4 * j]     = ex2(fmaf(s[4 * j], cs, -m0));
                s[4 * j + 1] = ex2(fmaf(s[4 * j + 1], cs, -m0));
                s[4 * j + 2] = ex2(fmaf(s[4 * j + 2], cs, -m1));
                s[4 * j + 3] = ex2(fmaf(s[4 * j + 3], cs, -m1));
                l0 += s[4 * j] + s[4 * j + 1];
                l1 += s[4 * j + 2] + s[4 * j + 3];
            }
            l0 += __shfl_xor_sync(0xffffffffu, l0, 1);
            l1 += __shfl_xor_sync(0xffffffffu, l1, 1);
            l0 += __shfl_xor_sync(0xffffffffu, l0, 2);
            l1 += __shfl_xor_sync(0xffffffffu, l1, 2);
            const float r0 = rcp(l0), r1 = rcp(l1);
#pragma unroll
            for (int j = 0; j < 8; j++) {
                pa[2 * j]     = pack_bf16(s[4 * j] * r0, s[4 * j + 1] * r0);
                pa[2 * j + 1] = pack_bf16(s[4 * j + 2] * r1, s[4 * j + 3] * r1);
            }
        }

        const uint32_t dXt = desc_xt(wg_uniform());
        if (((tid_now() >> 5) & 3) != 0) asm volatile("bar.sync %0, 128;" ::"r"((tid_now() >> 7) + 4) : "memory");
        uint32_t pub;
        asm volatile("ld.shared.u32 %0, [%1];" : "=r"(pub) : "r"(sbase + kOffBar + 64 + 4 * (tid_now() >> 7)) : "memory");
        const int nxt = (int)__reduce_or_sync(0xffffffffu, pub);
        store_p_if(pa, nxt == (int)kDone + kNWG - 1);
        if (nxt == (int)kDone + kNWG - 1) {
            last_window(out, win);
            asm volatile("exit;");
            __builtin_unreachable();
        }
        fence_regs(pa);
        wg_fence();
        ring_wait();
        Gemm3<3>::run(acc, pa, dXt);
        wg_commit();
        if constexpr (PASS3 == 3) ring_pass();
        wg_wait0();
        fence_regs(acc);
        fence_regs(pa);

        if (((tid_now() >> 5) & 3) == 0) {
            asm volatile("bar.sync %0, 128;" ::"r"((tid_now() >> 7) + 1) : "memory");
            if (elect_one()) {
                const uint32_t wgl = tid_now() >> 7;
                const uint32_t bar = sbase + kOffBar + 8 * wgl;
                if (nxt < kNWin) {
                    mbar_expect_tx(bar, kXBytes);
                    tma_load_x_hint(sbase + kOffX + wgl * kXBytes, &tmx, bar, nxt, nxt >= kNWin - EF_LAST);
                    uint32_t again;
                    asm volatile("ld.volatile.shared.u32 %0, [%1];" : "=r"(again) : "r"(sbase + kOffBar + 64 + 4 * wgl) : "memory");
                    prefetch_for_ticket(&tmp, (int)again - kNWG * (int)gridDim.x);
                }
            }
            __syncwarp();
        } else {
            asm volatile("bar.arrive %0, 128;" ::"r"((tid_now() >> 7) + 1) : "memory");
        }
#pragma unroll
        for (int i = 0; i < 48; i++) fa[i] = pack_bf16(acc[2 * i], acc[2 * i + 1]);

        asm volatile("{\n.reg .pred p;\nsetp.lt.s32 p, %5, 0;\n@p st.volatile.shared.v4.b32 [%4], {%0, %1, %2, %3};\n}\n"
                     :: "r"(fa[44]), "r"(fa[45]), "r"(fa[46]), "r"(fa[47]), "r"(sbase + kOffBar + 112), "r"(nxt) : "memory");
        fence_regs(fa);
        wg_fence();
        ring_wait();
        Gemm4<0, 1>::run(acc, fa, dWv);
        wg_commit();
        Gemm4<2, 10>::run(acc, fa, dWv);
        wg_commit();
        wg_wait1();
        uint32_t fl[4];
        uint32_t zero;
        asm volatile("ld.volatile.shared.u32 %0, [%1];" : "=r"(zero) : "r"(sbase + kOffBar + 76) : "memory");
#pragma unroll
        for (int i = 0; i < 4; i++) fl[i] = fa[44 + i] ^ zero;
        if constexpr (PASS4 == 10) ring_pass();
        wg_fence();
        wg192_rs<false, 0, koff(11, 24576)>(acc, fl, dWv);
        wg_commit();
        if constexpr (PASS4 == 11) ring_pass();
        pos = out_pos(win);
        win = nxt | (~win & kPhase);
        const uint32_t dX1 = desc_x(wg_uniform());
        asm volatile("" : "+r"(pos) :: "memory");
        wg_wait0();
        fence_regs(acc);
        fence_regs(fa);
        fence_regs(fl);

#pragma unroll
        for (int a = 0; a < 6; a++) {
            hv[2 * a].x     = pack_bf16(acc[16 * a + 0], acc[16 * a + 1]);
            hv[2 * a].y     = pack_bf16(acc[16 * a + 4], acc[16 * a + 5]);
            hv[2 * a].z     = pack_bf16(acc[16 * a + 8], acc[16 * a + 9]);
            hv[2 * a].w     = pack_bf16(acc[16 * a + 12], acc[16 * a + 13]);
            hv[2 * a + 1].x = pack_bf16(acc[16 * a + 2], acc[16 * a + 3]);
            hv[2 * a + 1].y = pack_bf16(acc[16 * a + 6], acc[16 * a + 7]);
            hv[2 * a + 1].z = pack_bf16(acc[16 * a + 10], acc[16 * a + 11]);
            hv[2 * a + 1].w = pack_bf16(acc[16 * a + 14], acc[16 * a + 15]);
        }
        if (win < (int)kDone) mbar_wait(sbase + kOffBar + 8 * (tid_now() >> 7), (win >> 16) & 1);
        if (win >= (int)kDone) break;
        wg_fence();
        ring_wait();
        Gemm1<0, PASS1>::run(acc, dX1, dWm);
        if constexpr (PASS1 < 11) {
            ring_pass();
            Gemm1<PASS1 + 1, 11>::run(acc, dX1, dWm);
        }
        wg_commit();
        if constexpr (PASS1 == 11) ring_pass();
        ticket = draw_ticket(tickets);
        asm volatile("bar.sync 15, 256;" ::: "memory");
        stage_window<0>(hv, &tmo, pos, win);
        wg_wait0();
    }
    if ((win & 3) == 0) {
        const uint32_t buf = sbase + kOffX + (tid_now() >> 7) * kXBytes + ((tid_now() >> 5) & 3) * 2048;
        asm volatile("bar.sync %0, 128;" ::"r"((tid_now() >> 7) + 1) : "memory");
        ring_wait();
        ring_pass();
        stage_put<0>(hv, buf);
        stage_send(&tmo, pos, 0, buf);
        stage_put<1>(hv, buf + 8192);
        stage_send(&tmo, pos, 1, buf + 8192);
        stage_put<2>(hv, buf + 2 * 8192);
        stage_send(&tmo, pos, 2, buf + 2 * 8192);
        clear_images(sc);
        asm volatile("bar.sync 15, 256;" ::: "memory");
        stage_wait();
    } else {
        uint8_t* hptr = out_address(out, pos);
        store_tail<0>(hv, hptr, clock_now());
    }
}

typedef CUresult (*EncodeTiledFn)(CUtensorMap*, CUtensorMapDataType, cuuint32_t, void*, const cuuint64_t*,
                                  const cuuint64_t*, const cuuint32_t*, const cuuint32_t*, CUtensorMapInterleave,
                                  CUtensorMapSwizzle, CUtensorMapL2promotion, CUtensorMapFloatOOBfill);

}

extern "C" void kernel_launch(void* const* d_in, const int* in_sizes, int n_in, void* d_out, int out_size) {
    (void)in_sizes; (void)n_in; (void)out_size;
    const __nv_bfloat16* x    = (const __nv_bfloat16*)d_in[0];
    const __nv_bfloat16* wqkv = (const __nv_bfloat16*)d_in[1];
    const __nv_bfloat16* wo   = (const __nv_bfloat16*)d_in[2];

    static EncodeTiledFn encode = nullptr;
    static int num_sms = 0;
    static void* scratch = nullptr;
    if (!encode) {
        void* fn = nullptr;
        cudaDriverEntryPointQueryResult qr;
        cudaGetDriverEntryPoint("cuTensorMapEncodeTiled", &fn, cudaEnableDefault, &qr);
        encode = (EncodeTiledFn)fn;
        int dev = 0;
        cudaGetDevice(&dev);
        cudaDeviceGetAttribute(&num_sms, cudaDevAttrMultiProcessorCount, dev);
        cudaGetSymbolAddress(&scratch, g_scratch);
        cudaFuncSetAttribute(swin_attn_kernel<false>, cudaFuncAttributeMaxDynamicSharedMemorySize, kSmemBytes);
        cudaFuncSetAttribute(swin_attn_kernel<true>, cudaFuncAttributeMaxDynamicSharedMemorySize, kSmemBytes);
    }
    CUtensorMap tmx;
    const cuuint64_t gdim[5] = {(cuuint64_t)kC, (cuuint64_t)kHW / 2, 2, 2, (cuuint64_t)kHW / 2};
    const cuuint64_t gstr[4] = {(cuuint64_t)kC * 4, (cuuint64_t)kHW * kC * 2, (cuuint64_t)kC * 2, (cuuint64_t)kHW * kC * 4};
    const cuuint32_t box[5] = {64, 4, 2, 2, 4};
    const cuuint32_t estr[5] = {1, 1, 1, 1, 1};
    encode(&tmx, CU_TENSOR_MAP_DATA_TYPE_BFLOAT16, 5, (void*)x, gdim, gstr, box, estr, CU_TENSOR_MAP_INTERLEAVE_NONE,
           CU_TENSOR_MAP_SWIZZLE_128B, CU_TENSOR_MAP_L2_PROMOTION_NONE, CU_TENSOR_MAP_FLOAT_OOB_FILL_NONE);

    CUtensorMap tmp;
    const cuuint64_t pdim[3] = {(cuuint64_t)kC, (cuuint64_t)kHW, (cuuint64_t)kHW};
    const cuuint64_t pstr[2] = {(cuuint64_t)kC * 2, (cuuint64_t)kHW * kC * 2};
    const cuuint32_t pbox[3] = {(cuuint32_t)kC, 8, 8};
    encode(&tmp, CU_TENSOR_MAP_DATA_TYPE_BFLOAT16, 3, (void*)x, pdim, pstr, pbox, estr, CU_TENSOR_MAP_INTERLEAVE_NONE,
           CU_TENSOR_MAP_SWIZZLE_NONE, CU_TENSOR_MAP_L2_PROMOTION_NONE, CU_TENSOR_MAP_FLOAT_OOB_FILL_NONE);
    CUtensorMap tmo;
    const cuuint64_t odim[5] = {64, 6, (cuuint64_t)kHW / 4, 2, (cuuint64_t)kHW};
    const cuuint64_t ostr[4] = {128, (cuuint64_t)kC * 8, (cuuint64_t)kC * 4, (cuuint64_t)kHW * kC * 2};
    const cuuint32_t obox[5] = {64, 2, 2, 2, 2};
    encode(&tmo, CU_TENSOR_MAP_DATA_TYPE_BFLOAT16, 5, d_out, odim, ostr, obox, estr, CU_TENSOR_MAP_INTERLEAVE_NONE,
           CU_TENSOR_MAP_SWIZZLE_128B, CU_TENSOR_MAP_L2_PROMOTION_NONE, CU_TENSOR_MAP_FLOAT_OOB_FILL_NONE);
    if (num_sms >= kJobs)
        swin_attn_kernel<false><<<num_sms, kThreads, kSmemBytes, cudaStreamPerThread>>>(wqkv, wo, (__nv_bfloat16*)d_out, (Scratch*)scratch, ((Scratch*)scratch)->ticket, tmx, tmp, tmo);
    else
        swin_attn_kernel<true><<<num_sms, kThreads, kSmemBytes, cudaStreamPerThread>>>(wqkv, wo, (__nv_bfloat16*)d_out, (Scratch*)scratch, ((Scratch*)scratch)->ticket, tmx, tmp, tmo);
}
```

```cpp
#include <cuda_runtime.h>
#include <cuda_bf16.h>
#include <cuda.h>
#include <stdint.h>

namespace {

constexpr int kC      = 192;
constexpr int kHW     = 512;
#define MAXWIN 4096
constexpr int kNWin   = MAXWIN;
constexpr int kXBytes = 64 * kC * 2;
constexpr int kWBytes = kC * kC * 2;
constexpr int kNWG    = 3;
constexpr int kThreads = kNWG * 128;
constexpr int kJobsM  = 72;
constexpr int kJobs   = 120;
constexpr int kWarmW  = 4;
#define PF_LEAD 400
#define PF_UP 114
#define PF_DOWN 39
#define PF_END 300
#define PF_MIN 135
#define EF_LAST 1000
#define TRK_T0 700
#define TRK_S 1700
#define TRK_HOST TRK_S
#define X0_LATE 72
#define REQ_T 2450
#define REQ_TV 4000

constexpr int kOffWm  = 0;
constexpr int kOffWv  = kWBytes;
constexpr int kOffX   = 2 * kWBytes;
constexpr int kOffStage = kOffX + kNWG * kXBytes;
constexpr int kOffBar = kOffStage + 8192;
constexpr int kOffBarM = kOffBar + 128;
constexpr int kOffProf = kOffBar + 192;
constexpr int kSmemBytes = kOffProf;
constexpr uint32_t kSmemBase = 1024;

struct Scratch {
    uint4 wfold[2 * kWBytes / 16];
    uint32_t ticket[32];
    uint32_t cnt[32];
};
__device__ __align__(128) Scratch g_scratch;

__device__ __forceinline__ uint32_t smem_u32(const void* p) { return (uint32_t)__cvta_generic_to_shared(p); }

__device__ __forceinline__ void mbar_init(uint32_t bar, uint32_t count) {
    asm volatile("mbarrier.init.shared::cta.b64 [%0], %1;" ::"r"(bar), "r"(count) : "memory");
}
__device__ __forceinline__ void mbar_expect_tx(uint32_t bar, uint32_t bytes) {
    asm volatile("mbarrier.arrive.expect_tx.shared::cta.b64 _, [%0], %1;" ::"r"(bar), "r"(bytes) : "memory");
}
__device__ __forceinline__ void mbar_wait(uint32_t bar, uint32_t parity) {
    uint32_t ok;
    uint32_t spins = 0;
    do {
        asm volatile("{\n.reg .pred p;\n"
                     "mbarrier.try_wait.parity.shared::cta.b64 p, [%1], %2;\n"
                     "selp.b32 %0, 1, 0, p;\n}\n"
                     : "=r"(ok) : "r"(bar), "r"(parity) : "memory");
        if (++spins > (1u << 26)) __trap();
    } while (!ok);
}
__device__ __forceinline__ uint32_t tid_now() {
    uint32_t t;
    asm volatile("mov.u32 %0, %%tid.x;" : "=r"(t));
    return t;
}
__device__ __forceinline__ uint32_t nctaid_now() {
    uint32_t t;
    asm volatile("mov.u32 %0, %%nctaid.x;" : "=r"(t));
    return t;
}
__device__ __forceinline__ bool elect_one() {
    uint32_t pred;
    asm volatile("{\n.reg .pred p;\nelect.sync _|p, 0xffffffff;\nselp.b32 %0, 1, 0, p;\n}\n" : "=r"(pred));
    return pred != 0;
}
#define PASS1 10
#define PASS4 11
#define PASS2 7
#define PASS3 3
__device__ __forceinline__ void ring_wait() {
    asm volatile("bar.sync %0, 256;" ::"r"((tid_now() >> 7) + 8) : "memory");
}
__device__ __forceinline__ void ring_pass() {
    const uint32_t w = tid_now() >> 7;
    asm volatile("bar.arrive %0, 256;" ::"r"(w == kNWG - 1 ? 8u : w + 9u) : "memory");
}
constexpr uint32_t kDone = 0x40000000u;
constexpr int kPhase = 0x10000;
__device__ __forceinline__ uint32_t wg_uniform() { return __reduce_or_sync(0xffffffffu, tid_now() >> 7); }
__device__ __forceinline__ uint32_t desc_x(uint32_t w) { return (((kSmemBase + kOffX) >> 4) | (1u << 16)) + w * (kXBytes >> 4); }
__device__ __forceinline__ uint32_t desc_xt(uint32_t w) { return (((kSmemBase + kOffX) >> 4) | ((8192u >> 4) << 16)) + w * (kXBytes >> 4); }
__device__ __forceinline__ void tma_load_x_chunk(uint32_t dst, const CUtensorMap* tm, uint32_t bar, int win, int chunk) {
    asm volatile("cp.async.bulk.tensor.5d.shared::cluster.global.mbarrier::complete_tx::bytes"
                 " [%0], [%1, {%3, %4, %6, %6, %5}], [%2];"
                 ::"r"(dst), "l"(tm), "r"(bar), "r"(chunk * 64), "r"((win & 63) * 4), "r"((win >> 6) * 4), "r"(0) : "memory");
}
__device__ __forceinline__ void tma_load_x_hint(uint32_t dst, const CUtensorMap* tm, uint32_t bar, int win, bool evict_first) {
    uint64_t first, normal;
    asm("createpolicy.fractional.L2::evict_first.b64 %0, 1.0;" : "=l"(first));
    asm("createpolicy.fractional.L2::evict_normal.b64 %0, 1.0;" : "=l"(normal));
#pragma unroll
    for (int c = 0; c < 3; c++)
        asm volatile("cp.async.bulk.tensor.5d.shared::cluster.global.mbarrier::complete_tx::bytes.L2::cache_hint"
                     " [%0], [%1, {%3, %4, %6, %6, %5}], [%2], %7;"
                     ::"r"(dst + c * 8192), "l"(tm), "r"(bar), "r"(c * 64), "r"((win & 63) * 4), "r"((win >> 6) * 4), "r"(0),
                       "l"(evict_first ? first : normal) : "memory");
}
__device__ __forceinline__ void bulk_load(uint32_t dst, const void* src, uint32_t bytes, uint32_t bar) {
    asm volatile("cp.async.bulk.shared::cluster.global.mbarrier::complete_tx::bytes [%0], [%1], %2, [%3];"
                 ::"r"(dst), "l"(src), "r"(bytes), "r"(bar) : "memory");
}

__device__ __forceinline__ void wg_fence()  { asm volatile("wgmma.fence.sync.aligned;" ::: "memory"); }
__device__ __forceinline__ void wg_commit() { asm volatile("wgmma.commit_group.sync.aligned;" ::: "memory"); }
__device__ __forceinline__ void wg_wait0()  { asm volatile("wgmma.wait_group.sync.aligned 0;" ::: "memory"); }
__device__ __forceinline__ void wg_wait1()  { asm volatile("wgmma.wait_group.sync.aligned 1;" ::: "memory"); }
__device__ __forceinline__ void wg_wait2()  { asm volatile("wgmma.wait_group.sync.aligned 2;" ::: "memory"); }

template <int N> __device__ __forceinline__ void fence_regs(float (&d)[N]) {
#pragma unroll
    for (int i = 0; i < N; i++) asm volatile("" : "+f"(d[i])::"memory");
}
template <int N> __device__ __forceinline__ void fence_regs(uint32_t (&d)[N]) {
#pragma unroll
    for (int i = 0; i < N; i++) asm volatile("" : "+r"(d[i])::"memory");
}

#define ACC8(c, d, i) c(d[i]), c(d[i + 1]), c(d[i + 2]), c(d[i + 3]), c(d[i + 4]), c(d[i + 5]), c(d[i + 6]), c(d[i + 7])
#define ACC32(c, d) ACC8(c, d, 0), ACC8(c, d, 8), ACC8(c, d, 16), ACC8(c, d, 24)
#define ACC96(c, d) ACC32(c, d), ACC8(c, d, 32), ACC8(c, d, 40), ACC8(c, d, 48), ACC8(c, d, 56), \
                    ACC8(c, d, 64), ACC8(c, d, 72), ACC8(c, d, 80), ACC8(c, d, 88)
#define C_IO(x) "+f"(x)
#define C_O(x) "=f"(x)
#define REGS32 "{%0, %1, %2, %3, %4, %5, %6, %7, %8, %9, %10, %11, %12, %13, %14, %15, " \
               "%16, %17, %18, %19, %20, %21, %22, %23, %24, %25, %26, %27, %28, %29, %30, %31}"
#define REGS96 "{%0, %1, %2, %3, %4, %5, %6, %7, %8, %9, %10, %11, %12, %13, %14, %15, " \
               "%16, %17, %18, %19, %20, %21, %22, %23, %24, %25, %26, %27, %28, %29, %30, %31, " \
               "%32, %33, %34, %35, %36, %37, %38, %39, %40, %41, %42, %43, %44, %45, %46, %47, " \
               "%48, %49, %50, %51, %52, %53, %54, %55, %56, %57, %58, %59, %60, %61, %62, %63, " \
               "%64, %65, %66, %67, %68, %69, %70, %71, %72, %73, %74, %75, %76, %77, %78, %79, " \
               "%80, %81, %82, %83, %84, %85, %86, %87, %88, %89, %90, %91, %92, %93, %94, %95}"

#define DESC_HI "0x40000040"
#define MK_DESC(name, lo, off) "add.u32 t, " lo ", " off ";\nmov.b64 " name ", {t, " DESC_HI "};\n"

template <bool First, int OA, int OB> __device__ __forceinline__ void wg192_ss(float (&d)[96], uint32_t la, uint32_t lb) {
    if constexpr (First)
        asm volatile("{\n.reg .pred p;\n.reg .b32 t;\n.reg .b64 da, db;\nsetp.ne.b32 p, 0, 0;\n"
                     MK_DESC("da", "%96", "%98") MK_DESC("db", "%97", "%99")
                     "wgmma.mma_async.sync.aligned.m64n192k16.f32.bf16.bf16 " REGS96 ", da, db, p, 1, 1, 0, 0;\n}\n"
                     : ACC96(C_O, d) : "r"(la), "r"(lb), "n"(OA), "n"(OB));
    else
        asm volatile("{\n.reg .pred p;\n.reg .b32 t;\n.reg .b64 da, db;\nsetp.ne.b32 p, 1, 0;\n"
                     MK_DESC("da", "%96", "%98") MK_DESC("db", "%97", "%99")
                     "wgmma.mma_async.sync.aligned.m64n192k16.f32.bf16.bf16 " REGS96 ", da, db, p, 1, 1, 0, 0;\n}\n"
                     : ACC96(C_IO, d) : "r"(la), "r"(lb), "n"(OA), "n"(OB));
}
#define ACC48(c, d, o) ACC8(c, d, o), ACC8(c, d, o + 8), ACC8(c, d, o + 16), ACC8(c, d, o + 24), ACC8(c, d, o + 32), ACC8(c, d, o + 40)
#define REGS48 "{%0, %1, %2, %3, %4, %5, %6, %7, %8, %9, %10, %11, %12, %13, %14, %15, %16, %17, %18, %19, %20, %21, %22, %23, " \
               "%24, %25, %26, %27, %28, %29, %30, %31, %32, %33, %34, %35, %36, %37, %38, %39, %40, %41, %42, %43, %44, %45, %46, %47}"
template <bool First, int OA, int OB> __device__ __forceinline__ void wg96_ss(float (&d)[48], uint32_t la, uint32_t lb) {
    if constexpr (First)
        asm volatile("{\n.reg .pred p;\n.reg .b32 t;\n.reg .b64 da, db;\nsetp.ne.b32 p, 0, 0;\n"
                     MK_DESC("da", "%48", "%50") MK_DESC("db", "%49", "%51")
                     "wgmma.mma_async.sync.aligned.m64n96k16.f32.bf16.bf16 " REGS48 ", da, db, p, 1, 1, 0, 0;\n}\n"
                     : ACC48(C_O, d, 0) : "r"(la), "r"(lb), "n"(OA), "n"(OB));
    else
        asm volatile("{\n.reg .pred p;\n.reg .b32 t;\n.reg .b64 da, db;\nsetp.ne.b32 p, 1, 0;\n"
                     MK_DESC("da", "%48", "%50") MK_DESC("db", "%49", "%51")
                     "wgmma.mma_async.sync.aligned.m64n96k16.f32.bf16.bf16 " REGS48 ", da, db, p, 1, 1, 0, 0;\n}\n"
                     : ACC48(C_IO, d, 0) : "r"(la), "r"(lb), "n"(OA), "n"(OB));
}
template <bool First, int TB, int OB> __device__ __forceinline__ void wg192_rs(float (&d)[96], const uint32_t* a, uint32_t lb) {
    if constexpr (First)
        asm volatile("{\n.reg .pred p;\n.reg .b32 t;\n.reg .b64 db;\nsetp.ne.b32 p, 0, 0;\n"
                     MK_DESC("db", "%100", "%102")
                     "wgmma.mma_async.sync.aligned.m64n192k16.f32.bf16.bf16 " REGS96 ", {%96, %97, %98, %99}, db, p, 1, 1, %101;\n}\n"
                     : ACC96(C_O, d) : "r"(a[0]), "r"(a[1]), "r"(a[2]), "r"(a[3]), "r"(lb), "n"(TB), "n"(OB));
    else
        asm volatile("{\n.reg .pred p;\n.reg .b32 t;\n.reg .b64 db;\nsetp.ne.b32 p, 1, 0;\n"
                     MK_DESC("db", "%100", "%102")
                     "wgmma.mma_async.sync.aligned.m64n192k16.f32.bf16.bf16 " REGS96 ", {%96, %97, %98, %99}, db, p, 1, 1, %101;\n}\n"
                     : ACC96(C_IO, d) : "r"(a[0]), "r"(a[1]), "r"(a[2]), "r"(a[3]), "r"(lb), "n"(TB), "n"(OB));
}
template <bool First, int OB> __device__ __forceinline__ void wg64_rs(float (&d)[32], const uint32_t* a, uint32_t lb) {
    if constexpr (First)
        asm volatile("{\n.reg .pred p;\n.reg .b32 t;\n.reg .b64 db;\nsetp.ne.b32 p, 0, 0;\n"
                     MK_DESC("db", "%36", "%37")
                     "wgmma.mma_async.sync.aligned.m64n64k16.f32.bf16.bf16 " REGS32 ", {%32, %33, %34, %35}, db, p, 1, 1, 0;\n}\n"
                     : ACC32(C_O, d) : "r"(a[0]), "r"(a[1]), "r"(a[2]), "r"(a[3]), "r"(lb), "n"(OB));
    else
        asm volatile("{\n.reg .pred p;\n.reg .b32 t;\n.reg .b64 db;\nsetp.ne.b32 p, 1, 0;\n"
                     MK_DESC("db", "%36", "%37")
                     "wgmma.mma_async.sync.aligned.m64n64k16.f32.bf16.bf16 " REGS32 ", {%32, %33, %34, %35}, db, p, 1, 1, 0;\n}\n"
                     : ACC32(C_IO, d) : "r"(a[0]), "r"(a[1]), "r"(a[2]), "r"(a[3]), "r"(lb), "n"(OB));
}
template <bool First, int OA, int OB> __device__ __forceinline__ void wg64_ss(float (&d)[32], uint32_t la, uint32_t lb) {
    if constexpr (First)
        asm volatile("{\n.reg .pred p;\n.reg .b32 t;\n.reg .b64 da, db;\nsetp.ne.b32 p, 0, 0;\n"
                     MK_DESC("da", "%32", "%34") MK_DESC("db", "%33", "%35")
                     "wgmma.mma_async.sync.aligned.m64n64k16.f32.bf16.bf16 " REGS32 ", da, db, p, 1, 1, 0, 1;\n}\n"
                     : ACC32(C_O, d) : "r"(la), "r"(lb), "n"(OA), "n"(OB));
    else
        asm volatile("{\n.reg .pred p;\n.reg .b32 t;\n.reg .b64 da, db;\nsetp.ne.b32 p, 1, 0;\n"
                     MK_DESC("da", "%32", "%34") MK_DESC("db", "%33", "%35")
                     "wgmma.mma_async.sync.aligned.m64n64k16.f32.bf16.bf16 " REGS32 ", da, db, p, 1, 1, 0, 1;\n}\n"
                     : ACC32(C_IO, d) : "r"(la), "r"(lb), "n"(OA), "n"(OB));
}
__host__ __device__ constexpr int koff(int kk, int chunk) { return ((kk >> 2) * chunk + (kk & 3) * 32) >> 4; }

__device__ __forceinline__ uint32_t clock_now() {
    uint32_t t;
    asm volatile("mov.u32 %0, %%clock;" : "=r"(t));
    return t;
}
template <int K> __device__ __forceinline__ void stage_put(const uint4 (&h)[12], uint32_t buf) {
    const uint32_t t = tid_now(), line = ((t >> 2) & 2) + (t & 4) + ((t >> 1) & 8);
    const uint32_t adr = buf + line * 128 + (((t & 3) ^ (line & 7)) << 4);
#pragma unroll
    for (int j = 0; j < 4; j++) {
        const int i = 4 * K + j, n = 2 * (i % 6) + i / 6;
        asm volatile("st.shared.v4.b32 [%4], {%0, %1, %2, %3};"
                     :: "r"(h[n].x), "r"(h[n].y), "r"(h[n].z), "r"(h[n].w), "r"((adr ^ ((j & 1) * 64 + (j >> 1) * 16)) + (j >> 1) * 128) : "memory");
    }
}
__device__ __forceinline__ void stage_send(const CUtensorMap* tm, uint32_t pos, int k, uint32_t buf) {
    asm volatile("fence.proxy.async.shared::cta;" ::: "memory");
    __syncwarp();
    if (elect_one()) {
        asm volatile("cp.async.bulk.tensor.5d.global.shared::cta.bulk_group [%0, {%2, %5, %3, %2, %4}], [%1];"
                     ::"l"(tm), "r"(buf), "r"(0), "r"(pos & 0xffff), "r"(pos >> 16), "r"(2 * k) : "memory");
        asm volatile("cp.async.bulk.commit_group;" ::: "memory");
    }
    __syncwarp();
}
__device__ __forceinline__ void stage_wait() {
    asm volatile("cp.async.bulk.wait_group.read 0;" ::: "memory");
    __syncwarp();
}
__device__ __forceinline__ uint32_t out_pos(int win) {
    return ((win & 63) * 2) | (((((win & 4095) >> 6) & 63) * 8 + 2 * ((tid_now() >> 5) & 3)) << 16);
}
__device__ __forceinline__ uint32_t stage_buf() { return kSmemBase + kOffStage + ((tid_now() >> 5) & 3) * 2048; }
template <int K> __device__ __forceinline__ void stage_window(uint4 (&h)[12], const CUtensorMap* tm, uint32_t pos, [[maybe_unused]] int win) {
    if constexpr (K < 3) {
        if constexpr (K > 0) stage_wait();
        stage_put<K>(h, stage_buf());
        stage_send(tm, pos, K, stage_buf());
        stage_window<K + 1>(h, tm, pos, win);
    }
}
__device__ __forceinline__ void stg128(void* p, uint4 v) {
    asm volatile("st.global.v4.b32 [%0], {%1, %2, %3, %4};" ::"l"(p), "r"(v.x), "r"(v.y), "r"(v.z), "r"(v.w) : "memory");
}
#define TAIL_DT 90
#define TAIL_FREE 2
template <int J> __device__ __forceinline__ void store_tail(uint4 (&h)[12], uint8_t* hptr, uint32_t t0) {
    if constexpr (J < 12) {
        if (J > TAIL_FREE) { while (clock_now() - t0 < (uint32_t)((J - TAIL_FREE) * TAIL_DT)) {} }
        stg128(hptr + J * 64, h[2 * (J % 6) + J / 6]);
        store_tail<J + 1>(h, hptr, t0);
    }
}
__device__ __forceinline__ uint8_t* out_address(__nv_bfloat16* out, uint32_t pos) {
    const uint32_t ln = tid_now() & 31;
    return reinterpret_cast<uint8_t*>(out) + (((pos >> 16) + (ln >> 4)) * kHW + (pos & 0xffff) * 4 + ((ln >> 1) & 6)) * (uint32_t)(kC * 2) + (ln & 3) * 16;
}
template <int K0, int K> struct Gemm1 {
    static __device__ __forceinline__ void run(float (&d)[96], uint32_t lx, uint32_t lw) {
        if constexpr (K > K0) Gemm1<K0, K - 1>::run(d, lx, lw);
        wg192_ss<K == 0, koff(K, 8192), koff(K, 24576)>(d, lx, lw);
    }
};
__device__ __forceinline__ uint32_t draw_ticket(uint32_t* counter, int G) {
    uint32_t ticket = 0;
    asm volatile("{\n.reg .pred p;\nsetp.eq.u32 p, %2, 0;\n@p atom.relaxed.gpu.global.inc.u32 %0, [%1], %3;\n}\n"
                 : "+r"(ticket) : "l"(counter), "r"(tid_now() & 127), "r"(kNWin - 1 - kNWG * G) : "memory");
    return ticket;
}
template <int KK> struct Gemm2 { static __device__ __forceinline__ void run(float (&d)[32], const uint32_t* a, uint32_t lx) {
    Gemm2<KK - 1>::run(d, a, lx); wg64_rs<KK == 0, koff(KK, 8192)>(d, a + 4 * KK, lx);
    if constexpr (KK == PASS2 && KK < 11) ring_pass(); } };
template <int K0, int KK> struct Gemm2p { static __device__ __forceinline__ void run(float (&d)[32], const uint32_t* a, uint32_t lx) {
    if constexpr (KK > K0) Gemm2p<K0, KK - 1>::run(d, a, lx);
    wg64_rs<KK == 0, koff(KK, 8192)>(d, a + 4 * KK, lx); } };
template <int H, int C, int KK = 3> struct Gemm1h { static __device__ __forceinline__ void run(float (&d)[48], uint32_t lx, uint32_t lw) {
    if constexpr (KK > 0) Gemm1h<H, C, KK - 1>::run(d, lx, lw);
    wg96_ss<C == 0 && KK == 0, koff(4 * C + KK, 8192), koff(4 * C + KK, 24576) + H * 96 * 8>(d, lx, lw); } };
template <> struct Gemm2<-1> { static __device__ __forceinline__ void run(float (&)[32], const uint32_t*, uint32_t) {} };
template <int KK> struct Gemm3 { static __device__ __forceinline__ void run(float (&d)[96], const uint32_t* a, uint32_t lxt) {
    Gemm3<KK - 1>::run(d, a, lxt); wg192_rs<KK == 0, 1, KK * (2048 >> 4)>(d, a + 4 * KK, lxt);
    if constexpr (KK == PASS3 && KK < 3) ring_pass(); } };
template <> struct Gemm3<-1> { static __device__ __forceinline__ void run(float (&)[96], const uint32_t*, uint32_t) {} };
template <int K0, int KK> struct Gemm4 { static __device__ __forceinline__ void run(float (&d)[96], const uint32_t* a, uint32_t lw) {
    if constexpr (KK > K0) Gemm4<K0, KK - 1>::run(d, a, lw);
    wg192_rs<KK == 0, 0, koff(KK, 24576)>(d, a + 4 * KK, lw); } };

template <int J, int KK> struct Gemm3s { static __device__ __forceinline__ void run(float (&d)[32], uint32_t lp, uint32_t lxt) {
    if constexpr (KK > 0) Gemm3s<J, KK - 1>::run(d, lp, lxt);
    wg64_ss<KK == 0, KK * 2, (J * 8192 + KK * 2048) / 16>(d, lp, lxt); } };
template <int J, int K0, int KK> struct Gemm4s { static __device__ __forceinline__ void run(float (&d)[32], const uint32_t* a, uint32_t lw) {
    if constexpr (KK > K0) Gemm4s<J, K0, KK - 1>::run(d, a, lw);
    wg64_rs<KK == 0, koff(KK, 24576) + J * (8192 / 16)>(d, a + 4 * KK, lw); } };

__device__ __forceinline__ uint32_t pack_bf16(float lo, float hi) {
    uint32_t r;
    asm("cvt.rn.bf16x2.f32 %0, %1, %2;" : "=r"(r) : "f"(hi), "f"(lo));
    return r;
}
__device__ __forceinline__ float ex2(float x) {
    float r;
    asm("ex2.approx.ftz.f32 %0, %1;" : "=f"(r) : "f"(x));
    return r;
}
__device__ __forceinline__ float rcp(float x) {
    float r;
    asm("rcp.approx.ftz.f32 %0, %1;" : "=f"(r) : "f"(x));
    return r;
}

__device__ __forceinline__ void pack_slice(uint32_t* a, float (&d)[32]) {
    fence_regs(d);
#pragma unroll
    for (int i = 0; i < 16; i++) a[i] = pack_bf16(d[2 * i], d[2 * i + 1]);
#pragma unroll
    for (int i = 0; i < 16; i++) asm volatile("" : "+r"(a[i])::"memory");
}
template <int J> __device__ __forceinline__ void store_slice(float (&d)[32], uint8_t* hptr) {
    fence_regs(d);
#pragma unroll
    for (int r = 0; r < 2; r++) {
        uint4 h[2];
#pragma unroll
        for (int a = 0; a < 2; a++) {
            const int o = 16 * a + 2 * r;
            h[a] = make_uint4(pack_bf16(d[o], d[o + 1]), pack_bf16(d[o + 4], d[o + 5]), pack_bf16(d[o + 8], d[o + 9]), pack_bf16(d[o + 12], d[o + 13]));
        }
        stg128(hptr + r * (kC * 2) + J * 128, h[0]);
        stg128(hptr + r * (kC * 2) + J * 128 + 64, h[1]);
    }
    __syncwarp();
}
__device__ __forceinline__ void store_p_if(const uint32_t (&pa)[16], bool cond) {
    const uint32_t t = tid_now(), row = ((t >> 1) & 48) + (t & 15);
    const uint32_t adr = kSmemBase + kOffStage + row * 128 + ((((t >> 4) & 1) ^ (t & 7)) << 4);
#pragma unroll
    for (int i = 0; i < 4; i++)
        asm volatile("{\n.reg .pred p;\nsetp.ne.u32 p, %5, 0;\n@p stmatrix.sync.aligned.m8n8.x4.shared.b16 [%4], {%0, %1, %2, %3};\n}\n"
                     :: "r"(pa[4 * i]), "r"(pa[4 * i + 1]), "r"(pa[4 * i + 2]), "r"(pa[4 * i + 3]), "r"(adr ^ (i << 5)), "r"((uint32_t)cond) : "memory");
}
__device__ __forceinline__ void last_window(__nv_bfloat16* out, int win) {
    constexpr uint32_t dWv = ((kSmemBase + kOffWv) >> 4) | (1u << 16);
    asm volatile("fence.proxy.async.shared::cta;" ::: "memory");
    const uint32_t w = wg_uniform();
    const uint32_t dXt = desc_xt(w);
    constexpr uint32_t dP = ((kSmemBase + kOffStage) >> 4) | (1u << 16);
    float u0[32], u1[32], u2[32];
    uint32_t fa[48];
    uint8_t* hptr = out_address(out, out_pos(win));
    asm volatile("" : "+l"(hptr) :: "memory");
    ring_wait();
    wg_fence();
    Gemm3s<0, 3>::run(u0, dP, dXt); wg_commit();
    Gemm3s<1, 3>::run(u1, dP, dXt); wg_commit();
    Gemm3s<2, 3>::run(u2, dP, dXt); wg_commit();
    wg_wait2();
    pack_slice(fa, u0);
    wg_fence();
    Gemm4s<0, 0, 3>::run(u0, fa, dWv); wg_commit();
    wg_wait2();
    pack_slice(fa + 16, u1);
    wg_fence();
    Gemm4s<0, 4, 7>::run(u0, fa, dWv); wg_commit();
    wg_wait2();
    pack_slice(fa + 32, u2);
    wg_fence();
    Gemm4s<0, 8, 11>::run(u0, fa, dWv); wg_commit();
    Gemm4s<1, 0, 5>::run(u1, fa, dWv); wg_commit();
    wg_wait1();
    store_slice<0>(u0, hptr);
    wg_fence();
    Gemm4s<1, 6, 11>::run(u1, fa, dWv); wg_commit();
    Gemm4s<2, 0, 5>::run(u2, fa, dWv); wg_commit();
    wg_wait1();
    store_slice<1>(u1, hptr);
    wg_fence();
    Gemm4s<2, 6, 11>::run(u2, fa, dWv); wg_commit();
    wg_wait0();
    fence_regs(fa);
    store_slice<2>(u2, hptr);
}

__device__ __forceinline__ int fold_offset(int n, int k0, int q) {
    const int u = ((k0 & 63) >> 3) + (q >> 1);
    return (k0 >> 6) * 24576 + (q & 1) * 8 + n * 128 + ((u ^ (n & 7)) << 4);
}
__device__ __forceinline__ void mma16816x2(float (&c)[4], float (&d)[4], const uint32_t (&a)[4], const uint32_t (&b)[4]) {
    asm volatile("mma.sync.aligned.m16n8k16.row.col.f32.bf16.bf16.f32 {%0,%1,%2,%3}, {%8,%9,%10,%11}, {%12,%13}, {%0,%1,%2,%3};\n"
                 "mma.sync.aligned.m16n8k16.row.col.f32.bf16.bf16.f32 {%4,%5,%6,%7}, {%8,%9,%10,%11}, {%14,%15}, {%4,%5,%6,%7};"
                 : "+f"(c[0]), "+f"(c[1]), "+f"(c[2]), "+f"(c[3]), "+f"(d[0]), "+f"(d[1]), "+f"(d[2]), "+f"(d[3])
                 : "r"(a[0]), "r"(a[1]), "r"(a[2]), "r"(a[3]), "r"(b[0]), "r"(b[1]), "r"(b[2]), "r"(b[3]));
}
__device__ __forceinline__ void cp_async16(uint32_t dst, const void* src) {
    asm volatile("cp.async.cg.shared.global [%0], [%1], 16;" ::"r"(dst), "l"(src) : "memory");
}
template <bool kTrans> __device__ __forceinline__ void ldsm4(uint32_t (&r)[4], uint32_t addr) {
    if constexpr (kTrans)
        asm volatile("ldmatrix.sync.aligned.m8n8.x4.trans.shared.b16 {%0, %1, %2, %3}, [%4];" : "=r"(r[0]), "=r"(r[1]), "=r"(r[2]), "=r"(r[3]) : "r"(addr) : "memory");
    else
        asm volatile("ldmatrix.sync.aligned.m8n8.x4.shared.b16 {%0, %1, %2, %3}, [%4];" : "=r"(r[0]), "=r"(r[1]), "=r"(r[2]), "=r"(r[3]) : "r"(addr) : "memory");
}
__device__ __forceinline__ uint32_t nonzero(uint32_t w) { return w ? w : 0x80000000u; }
template <bool vo>
__device__ __forceinline__ void fold_job(Scratch* sc, const __nv_bfloat16* __restrict__ wqkv, const __nv_bfloat16* __restrict__ wo,
                                         int job, int warp, int lane) {
    constexpr int nw = vo ? 3 : 2;
    const int nb = vo ? job >> 2 : (job * 43) >> 8;
    const int n0 = nb * 16, k0 = (nw * (vo ? job & 3 : job - 6 * nb) + max(warp, 1) - 1) * 16;
    const uint32_t stage = kSmemBase + kOffWv;
    if (warp != kWarmW) {
        if (vo) {
            const char* src = reinterpret_cast<const char*>(wo) + (uint32_t)(((warp * 48 + (lane >> 1)) * kC + n0 + (lane & 1) * 8) * 2);
            const uint32_t dst = stage + warp * 1536 + ((lane ^ ((lane >> 3) & 1)) << 4);
#pragma unroll
            for (int i = 0; i < 3; i++) cp_async16(dst + i * 512, src + i * 16 * kC * 2);
        }
        if (!vo || warp != 0) {
            const int row0 = warp == 0 ? n0 : k0, col0 = warp == 0 ? kC : vo ? 2 * kC : 0;
            const char* src = reinterpret_cast<const char*>(wqkv) + (uint32_t)(((row0 + (lane >> 3)) * (3 * kC) + col0 + (lane & 7) * 8) * 2);
            const uint32_t dst = stage + warp * 6144 + (lane >> 3) * 384 + (((lane & 7) ^ (lane >> 3)) << 4);
#pragma unroll
            for (int i = 0; i < 12; i++) cp_async16((dst ^ (((i / 3) & 1) << 6)) + (i / 3) * 1536 + (i % 3) * 128, src + (i / 3) * 4 * 3 * kC * 2 + (i % 3) * 128);
        }
    }
    const int g = lane >> 2, q = lane & 3, mi = lane >> 3, r8 = lane & 7;
    const int row = 4 * (r8 >> 1) + (r8 & 1) + 2 * (mi >> 1), c = r8 + 8 * (mi >> 1);
    uint32_t baseB = stage + warp * 6144 + row * 384 + (((mi & 1) ^ (row & 7)) << 4);
    uint32_t baseA = stage + (vo ? ((2 * c + (mi & 1)) ^ ((c >> 2) & 1)) << 4 : (r8 + 8 * (mi & 1)) * 384 + (((mi >> 1) ^ r8) << 4));
    const int ch = n0 + g;
    const int n = vo ? 32 * (ch >> 5) + 8 * ((ch >> 1) & 3) + 2 * ((ch >> 3) & 3) + (ch & 1) : ch;
    char* img = reinterpret_cast<char*>(sc->wfold) + (vo ? kWBytes : 0);
    char* dst0 = img + fold_offset(n, k0, q);
    char* dst1 = img + fold_offset(n + (vo ? 2 : 8), k0, q);
    asm volatile("" : "+r"(baseA), "+r"(baseB), "+l"(dst0), "+l"(dst1));
    if (warp != kWarmW) {
        asm volatile("cp.async.wait_all;" ::: "memory");
        if (warp == 0) {
            asm volatile("bar.arrive 13, %0;" ::"n"(32 * nw + 32) : "memory");
            return;
        }
        asm volatile("bar.sync 13, %0;" ::"n"(32 * nw + 32) : "memory");
    }
    float c0[4] = {0.f, 0.f, 0.f, 0.f}, c1[4] = {0.f, 0.f, 0.f, 0.f}, c2[4] = {0.f, 0.f, 0.f, 0.f}, c3[4] = {0.f, 0.f, 0.f, 0.f};
    uint32_t A[12][4], B[12][4];
#pragma unroll
    for (int ks = 0; ks < 12; ks++) {
        ldsm4<vo>(A[ks], vo ? baseA + ks * 512 : (baseA ^ ((ks & 3) << 5)) + (ks >> 2) * 128);
        ldsm4<false>(B[ks], (baseB ^ ((ks & 3) << 5)) + (ks >> 2) * 128);
    }
#pragma unroll
    for (int ks = 0; ks < 12; ks += 2) {
        mma16816x2(c0, c1, A[ks], B[ks]);
        mma16816x2(c2, c3, A[ks + 1], B[ks + 1]);
    }
#pragma unroll
    for (int i = 0; i < 4; i++) { c0[i] += c2[i]; c1[i] += c3[i]; }
    asm volatile("{\n.reg .pred p;\nsetp.ne.u32 p, %6, %7;\n@p st.global.v2.u32 [%0], {%2, %3};\n@p st.global.v2.u32 [%1], {%4, %5};\n}\n"
                 ::"l"(dst0), "l"(dst1),
                   "r"(nonzero(pack_bf16(c0[0], c0[1]))), "r"(nonzero(pack_bf16(c1[0], c1[1]))), "r"(nonzero(pack_bf16(c0[2], c0[3]))), "r"(nonzero(pack_bf16(c1[2], c1[3]))),
                   "r"(warp), "n"(kWarmW) : "memory");
}
constexpr uint32_t kWarpsQK = 0x17;

__device__ __forceinline__ bool bar_or(uint32_t id, uint32_t n, bool pred) {
    uint32_t r;
    asm volatile("{\n.reg .pred p, q;\nsetp.ne.u32 q, %3, 0;\nbar.red.or.pred p, %1, %2, q;\nselp.u32 %0, 1, 0, p;\n}\n"
                 : "=r"(r) : "r"(id), "r"(n), "r"((uint32_t)pred) : "memory");
    return r != 0;
}
template <int N = 6> __device__ __forceinline__ bool chunk_incomplete(uint32_t base) {
    const uint32_t t = tid_now(), r = (t >> 2) & 7;
    const uint32_t adr = base + (((t >> 5) & 3) * 8 * N + r) * 128 + (t & 3) * 32 + r * 4;
    uint32_t m = ~0u;
#pragma unroll
    for (int j = 0; j < N; j++) {
        uint32_t v;
        asm volatile("ld.shared.u32 %0, [%1];" : "=r"(v) : "r"(adr + j * 1024) : "memory");
        m = min(m, v);
    }
    return m == 0;
}
__device__ __forceinline__ void load_image(uint32_t dst, const void* src, uint32_t bar) {
    mbar_expect_tx(bar, kWBytes);
#pragma unroll
    for (int c = 0; c < 3; c++) bulk_load(dst + c * 24576, reinterpret_cast<const char*>(src) + c * 24576, 24576, bar);
}
__device__ __forceinline__ void repair_image(uint32_t dst, const void* src, uint32_t bar, uint32_t par) {
    uint32_t tries = 0;
    bool bad;
    do {
        if (((tid_now() >> 5) & 3) == 0) {
            if (elect_one()) {
                asm volatile("fence.proxy.async;" ::: "memory");
                load_image(dst, src, bar);
            }
            __syncwarp();
        }
        mbar_wait(bar, par);
        par ^= 1;
        bad = chunk_incomplete(dst) | chunk_incomplete(dst + 24576) | chunk_incomplete(dst + 2 * 24576);
        if (++tries > (1u << 16)) __trap();
    } while (bar_or((tid_now() >> 7) + 1, 128, bad));
}
__device__ __forceinline__ void count_image(Scratch* sc) {
    asm volatile("red.relaxed.gpu.global.inc.u32 [%0], %1;" ::"l"(sc->cnt), "r"(3 * nctaid_now() - 1) : "memory");
}
__device__ __forceinline__ uint32_t ld_acquire(const uint32_t* p) {
    uint32_t v;
    asm volatile("ld.acquire.gpu.global.u32 %0, [%1];" : "=r"(v) : "l"(p) : "memory");
    return v;
}
__device__ __noinline__ void clear_images(Scratch* sc) {
    const uint32_t g = gridDim.x, t = threadIdx.x & 127;
    if (t == 0) {
        uint32_t spins = 0;
        while (ld_acquire(sc->cnt) < 2 * g) { if (++spins > (1u << 24)) __trap(); }
    }
    asm volatile("bar.sync %0, 128;" ::"r"((threadIdx.x >> 7) + 1) : "memory");
    for (uint32_t i = blockIdx.x * 64 + t; t < 64 && i < 2 * kWBytes / 16; i += g * 64) sc->wfold[i] = make_uint4(0, 0, 0, 0);
    if (t == 0) count_image(sc);
}
__device__ __forceinline__ void prefetch_x(const CUtensorMap* tm, int win) {
    const int wh = win >> 6, ww = win & 63;
    asm volatile("cp.async.bulk.prefetch.tensor.3d.L2.global.tile [%0, {%1, %2, %3}];"
                 ::"l"(tm), "r"(0), "r"(ww * 8), "r"(wh * 8) : "memory");
}
__device__ __forceinline__ void prefetch_x_chunk(const CUtensorMap* tm, int win, int chunk) {
    asm volatile("cp.async.bulk.prefetch.tensor.5d.L2.global.tile [%0, {%1, %2, %4, %4, %3}];"
                 ::"l"(tm), "r"(chunk * 64), "r"((win & 63) * 4), "r"((win >> 6) * 4), "r"(0) : "memory");
}

__device__ __forceinline__ void prefetch_for_ticket(const CUtensorMap* tmp, int t, int G) {
    const int base = kNWG * G;
    auto lead = [&](int tt) {
        int down = max(((kNWin - PF_END - base - tt) * PF_DOWN) >> 8, PF_MIN);
        return min(min(G + ((tt * PF_UP) >> 8), PF_LEAD), down);
    };
    const int hi = base + t + lead(t);
    int lo = max(base + t - 1 + lead(t - 1), base + t) + 1;
#pragma unroll 1
    for (; lo <= hi && lo < kNWin; lo++) prefetch_x(tmp, lo);
}

__device__ __forceinline__ void publish(uint32_t ticket, int G) {
    constexpr uint32_t sbase = kSmemBase;
    if (((tid_now() >> 5) & 3) == 0) {
        if ((tid_now() & 31) == 0) {
            uint32_t nxt = 2 * kNWG * G + ticket;
            if (nxt >= kNWin) {
                uint32_t p0, p1, p2, p3;
                asm volatile("ld.shared.v4.u32 {%0, %1, %2, %3}, [%4];" : "=r"(p0), "=r"(p1), "=r"(p2), "=r"(p3) : "r"(sbase + kOffBar + 64) : "memory");
                nxt = kDone + (p0 >> 30) + (p1 >> 30) + (p2 >> 30);
            }
            asm volatile("st.shared.u32 [%0], %1;" ::"r"(sbase + kOffBar + 64 + 4 * (tid_now() >> 7)), "r"(nxt) : "memory");
        }
        __syncwarp();
        asm volatile("bar.arrive %0, 128;" ::"r"((tid_now() >> 7) + 4) : "memory");
    }
}

template <bool kFewSMs>
__global__ void __launch_bounds__(kThreads, 1)
swin_attn_kernel(const __nv_bfloat16* __restrict__ wqkv, const __nv_bfloat16* __restrict__ wo, const __nv_bfloat16* __restrict__ xin, Scratch* sc, uint32_t* tickets,
                 const int G, const uint32_t trk, __nv_bfloat16* __restrict__ out, const __grid_constant__ CUtensorMap tmx, const __grid_constant__ CUtensorMap tmp, const __grid_constant__ CUtensorMap tmo) {
    extern __shared__ uint8_t smem_raw[];
    constexpr uint32_t sbase = kSmemBase;
    const uint32_t t_start = clock_now();
    asm volatile("{\n.reg .pred p, q;\n.reg .b32 i, j;\n.reg .b64 a, b;\nmad.lo.u32 i, %2, 14, %3;\nsetp.lt.u32 p, %3, 14;\nsetp.lt.and.u32 p, i, 1728, p;\n"
                 "mad.wide.u32 a, i, 128, %0;\n@p prefetch.global.L2 [a];\n"
                 "mad.lo.u32 j, %2, 5, %3;\nsetp.lt.u32 q, %3, 5;\nsetp.lt.and.u32 q, j, 576, q;\n"
                 "mad.wide.u32 b, j, 128, %1;\n@q prefetch.global.L2 [b];\n}\n" ::"l"(wqkv), "l"(wo), "r"(blockIdx.x), "r"(threadIdx.x) : "memory");
    if (smem_u32(smem_raw) != kSmemBase) __trap();
    const int tid = threadIdx.x, lane = tid & 31;
    const uint32_t warpu = __reduce_or_sync(0xffffffffu, (uint32_t)tid >> 5), wgu = warpu >> 2;
    const int warp = (int)warpu, wg = (int)wgu;
    const uint32_t bar_full = sbase + kOffBar + 8 * wg;
    constexpr uint32_t bar_m = sbase + kOffBarM, bar_w1 = sbase + kOffBar + 40;
    auto bar_v = [](int c) { return bar_w1 + 16 - 8 * c; };
    int win = wg * G + blockIdx.x;

    const int direct = blockIdx.x >= X0_LATE ? 1 : 2;
    if (!kFewSMs && blockIdx.x < kJobsM && ((kWarpsQK >> warp) & 1)) fold_job<false>(sc, wqkv, wo, blockIdx.x, warp, lane);
    if (warp == 10) {
        auto x_lines = [&](int c) {
            const int w = (c / 3) * G + blockIdx.x;
            return reinterpret_cast<const char*>(xin) + (uint32_t)((((w >> 6) * 8 + (lane >> 3)) * kHW + (w & 63) * 8 + (lane & 7)) * (kC * 2) + (c % 3) * 128);
        };
        if (elect_one()) {
            asm volatile("prefetch.tensormap [%0];" ::"l"(&tmx) : "memory");
#pragma unroll
            for (int w = 0; w < kNWG; w++) mbar_init(sbase + kOffBar + 8 * w, 1);
            mbar_init(sbase + kOffBar + 24, 1);
            mbar_init(sbase + kOffBar + 88, 1);
            mbar_init(sbase + kOffBar + 96, 1);
            mbar_init(sbase + kOffBar + 104, 1);
            mbar_init(sbase + kOffBar + 112, 1);
#pragma unroll
            for (int c = 0; c < 3; c++) mbar_init(bar_v(c), 1);
#pragma unroll
            for (int i = 0; i < 6; i++) mbar_init(bar_m + 8 * i, 1);
            asm volatile("st.shared.v4.u32 [%0], {%1, %1, %1, %1};" ::"r"(sbase + kOffBar + 64), "r"(0) : "memory");
            asm volatile("fence.mbarrier_init.release.cluster;" ::: "memory");
            asm volatile("mbarrier.arrive.shared::cta.b64 _, [%0];" ::"r"(sbase + kOffBar) : "memory");
        }
        __syncwarp();
        asm volatile("bar.arrive 15, 64;" ::: "memory");
        asm volatile("bar.arrive 0, %0;" ::"n"(kThreads) : "memory");
        const uint32_t due = (blockIdx.x * trk) >> 8;
        if (elect_one()) {
#pragma unroll
            for (int c = 0; c < 2; c++) {
                if (c >= direct) break;
                while (clock_now() - t_start < TRK_T0 + (due + c * TRK_S) / 3) {}
                tma_load_x_chunk(sbase + kOffX + c * 8192, &tmx, bar_m + 16 * c, blockIdx.x, c);
            }
        }
        __syncwarp();
#pragma unroll 1
        for (int c = direct; c < 3 * kNWG; c++) {
            const char* p = x_lines(c);
            while (clock_now() - t_start < TRK_T0 + (due + c * TRK_S) / 3) {}
            asm volatile("prefetch.global.L2 [%0];\nprefetch.global.L2 [%0 + %1];" ::"l"(p), "n"(4 * kHW * kC * 2) : "memory");
        }
        asm volatile("prefetch.tensormap [%0];" ::"l"(&tmp) : "memory");
        asm volatile("prefetch.tensormap [%0];" ::"l"(&tmo) : "memory");
    }
    int role = warp;
    asm volatile("" : "+r"(role));
    if (role == 10) {
    } else if (warp > kWarmW) {
        if (warp == 11) {
            asm volatile("bar.sync 15, 64;" ::: "memory");
            asm volatile("bar.arrive 0, %0;" ::"n"(kThreads) : "memory");
            if (elect_one()) {
                const char* img = reinterpret_cast<const char*>(sc->wfold);
#pragma unroll
                for (int i = 0; i < 6; i++) mbar_expect_tx(bar_m + 8 * i, 12288 + (i & 1 ? 0 : 8192));
#pragma unroll
                for (int c = 0; c < 3; c++) mbar_expect_tx(sbase + kOffBar + (c == 0 ? 8 : 80 + 8 * c), 8192);
                while (clock_now() - t_start < REQ_T) {}
#pragma unroll
                for (int i = 0; i < 6; i++) {
                    if (i >= 2 * direct && !(i & 1)) tma_load_x_chunk(sbase + kOffX + (i >> 1) * 8192, &tmx, bar_m + 8 * i, blockIdx.x, i >> 1);
                    bulk_load(sbase + kOffWm + i * 12288, img + i * 12288, 12288, bar_m + 8 * i);
                    if (i == 0) { }
                }
                mbar_wait(bar_m + 8, 0);
#pragma unroll
                for (int c = 0; c < 3; c++)
                    tma_load_x_chunk(sbase + kOffX + kXBytes + c * 8192, &tmx, sbase + kOffBar + (c == 0 ? 8 : 80 + 8 * c), G + blockIdx.x, c);
            }
            __syncwarp();
        } else {
            asm volatile("bar.sync 0, %0;" ::"n"(kThreads) : "memory");
            if (warp == 9) {
                if (elect_one()) {
                    while (clock_now() - t_start < REQ_TV) {}
                    mbar_wait(bar_m + 24, 0);
                    asm volatile("fence.proxy.async.shared::cta;" ::: "memory");
#pragma unroll
                    for (int c = 0; c < 3; c++) {
                        mbar_expect_tx(bar_v(c), 24576);
                        bulk_load(sbase + kOffWv + c * 24576, reinterpret_cast<const char*>(sc->wfold) + kWBytes + c * 24576, 24576, bar_v(c));
                    }
#pragma unroll
                    for (int c = 0; c < 3; c++) {
                        const uint32_t bar = sbase + kOffBar + (c == 0 ? 16 : 96 + 8 * c);
                        mbar_expect_tx(bar, 8192);
                        tma_load_x_chunk(sbase + kOffX + 2 * kXBytes + c * 8192, &tmx, bar, 2 * G + blockIdx.x, c);
                    }
                }
                __syncwarp();
            }
        }
    } else {
        if constexpr (kFewSMs) {
#pragma unroll 1
            for (int j = blockIdx.x; j < kJobs; j += G) {
                if (j >= kJobsM) fold_job<true>(sc, wqkv, wo, j - kJobsM, warp, lane);
                else if ((kWarpsQK >> warp) & 1) fold_job<false>(sc, wqkv, wo, j, warp, lane);
                asm volatile("bar.sync 14, %0;" ::"n"(32 * kWarmW + 32) : "memory");
            }
        } else {
            if (blockIdx.x - kJobsM < kJobs - kJobsM) fold_job<true>(sc, wqkv, wo, blockIdx.x - kJobsM, warp, lane);
        }
        asm volatile("bar.sync 0, %0;" ::"n"(kThreads) : "memory");
    }
    if (wg == 1) {
        mbar_wait(bar_m + 8 * (warp & 3), 0);
        bool bad = chunk_incomplete<12>(sbase + kOffWm);
#pragma unroll
        for (int i = 4; i < 6; i++) {
            mbar_wait(bar_m + 8 * i, 0);
            bad |= chunk_incomplete<3>(sbase + kOffWm + i * 12288);
        }
        bad = bar_or(2, 128, bad);
        if (bad) {
            repair_image(sbase + kOffWm, sc->wfold, sbase + kOffBar + 24, 0);
        }
        asm volatile("st.shared.u32 [%0], %1;" ::"r"(sbase + kOffBar + 80), "r"((uint32_t)bad) : "memory");
        asm volatile("bar.arrive 11, 256;" ::: "memory");
    } else if (wg == 2) {
        bool bad = false;
#pragma unroll
        for (int c = 0; c < 3; c++) {
            mbar_wait(bar_v(c), 0);
            bad |= chunk_incomplete(sbase + kOffWv + c * 24576);
        }
        if (bar_or(3, 128, bad)) {
            repair_image(sbase + kOffWv, reinterpret_cast<const char*>(sc->wfold) + kWBytes, bar_w1, 1);
        }
    }

    constexpr uint32_t dWm = ((sbase + kOffWm) >> 4) | (1u << 16);
    constexpr uint32_t dWv = ((sbase + kOffWv) >> 4) | (1u << 16);
    const float cs = 0.07216878364870322f * 1.4426950408889634f;
    mbar_wait(wg == 0 ? bar_m : bar_full, 0);

    uint4 hv[12];
    uint32_t pos;
    float acc[96];
    uint32_t ticket = win - kNWG * G;
    float s[32];
    {
        const uint32_t dX = desc_x(wg_uniform());
        uint32_t fa[48];
        if (wg == 0) {
            float ta[48], tb[48];
            wg_fence();
            Gemm1h<0, 0>::run(ta, dX, dWm);
            mbar_wait(bar_m + 8, 0);
            wg_fence();
            Gemm1h<1, 0>::run(tb, dX, dWm);
            mbar_wait(bar_m + 16, 0);
            wg_fence();
            Gemm1h<0, 1>::run(ta, dX, dWm);
            mbar_wait(bar_m + 24, 0);
            wg_fence();
            Gemm1h<1, 1>::run(tb, dX, dWm);
            mbar_wait(bar_m + 32, 0);
            wg_fence();
            Gemm1h<0, 2>::run(ta, dX, dWm);
            wg_commit();
            mbar_wait(bar_m + 40, 0);
            wg_fence();
            Gemm1h<1, 2>::run(tb, dX, dWm);
            wg_commit();
            wg_wait1();
            fence_regs(ta);
#pragma unroll
            for (int i = 0; i < 24; i++) fa[i] = pack_bf16(ta[2 * i], ta[2 * i + 1]);
#pragma unroll
            for (int i = 0; i < 24; i++) asm volatile("" : "+r"(fa[i])::"memory");
            wg_fence();
            Gemm2p<0, 5>::run(s, fa, dX);
            wg_commit();
            wg_wait1();
            fence_regs(tb);
#pragma unroll
            for (int i = 0; i < 24; i++) fa[24 + i] = pack_bf16(tb[2 * i], tb[2 * i + 1]);
#pragma unroll
            for (int i = 24; i < 48; i++) asm volatile("" : "+r"(fa[i])::"memory");
            wg_fence();
            Gemm2p<6, 11>::run(s, fa, dX);
            wg_commit();
            ring_pass();
            asm volatile("bar.sync 11, 256;" ::: "memory");
            uint32_t redo;
            asm volatile("ld.shared.u32 %0, [%1];" : "=r"(redo) : "r"(sbase + kOffBar + 80) : "memory");
            publish(ticket, G);
            asm volatile("bar.arrive 15, 256;" ::: "memory");
            redo = __reduce_or_sync(0xffffffffu, redo);
            wg_wait0();
            fence_regs(s);
            fence_regs(fa);
            if (redo) {
                wg_fence();
                Gemm1<0, 11>::run(acc, dX, dWm);
                wg_commit();
                wg_wait0();
                fence_regs(acc);
#pragma unroll
                for (int i = 0; i < 48; i++) fa[i] = pack_bf16(acc[2 * i], acc[2 * i + 1]);
                fence_regs(fa);
                wg_fence();
                Gemm2p<0, 11>::run(s, fa, dX);
                wg_commit();
                wg_wait0();
                fence_regs(s);
                fence_regs(fa);
            }
        } else {
            ring_wait();
            wg_fence();
            Gemm1<0, 3>::run(acc, dX, dWm);
            const uint32_t bar_c1 = sbase + kOffBar + 72 + 16 * wg;
            mbar_wait(bar_c1, 0);
            wg_fence();
            Gemm1<4, 7>::run(acc, dX, dWm);
            mbar_wait(bar_c1 + 8, 0);
            wg_fence();
            Gemm1<8, 11>::run(acc, dX, dWm);
            wg_commit();
            asm volatile("bar.arrive 8, 256;" ::: "memory");
            if (warp == 5) {
                if (elect_one()) prefetch_x(&tmp, kNWG * G + blockIdx.x);
                __syncwarp();
            }
            if ((tid & 127) == 0) count_image(sc);
            wg_wait0();
            fence_regs(acc);
#pragma unroll
            for (int i = 0; i < 48; i++) fa[i] = pack_bf16(acc[2 * i], acc[2 * i + 1]);
            fence_regs(fa);
            wg_fence();
            ring_wait();
            Gemm2<11>::run(s, fa, dX);
            wg_commit();
            publish(ticket, G);
            asm volatile("bar.arrive 15, 256;" ::: "memory");
            wg_wait0();
            fence_regs(s);
            fence_regs(fa);
        }
        __syncwarp();
    }

    while (true) {
        uint32_t fa[48];
        uint32_t pa[16];
        {
            float a0[8], a1[8];
#pragma unroll
            for (int j = 0; j < 8; j++) { a0[j] = fmaxf(s[4 * j], s[4 * j + 1]); a1[j] = fmaxf(s[4 * j + 2], s[4 * j + 3]); }
#pragma unroll
            for (int d = 4; d > 0; d >>= 1)
#pragma unroll
                for (int j = 0; j < d; j++) { a0[j] = fmaxf(a0[j], a0[j + d]); a1[j] = fmaxf(a1[j], a1[j + d]); }
            float m0 = a0[0], m1 = a1[0];
            m0 = fmaxf(m0, __shfl_xor_sync(0xffffffffu, m0, 1));
            m1 = fmaxf(m1, __shfl_xor_sync(0xffffffffu, m1, 1));
            m0 = fmaxf(m0, __shfl_xor_sync(0xffffffffu, m0, 2));
            m1 = fmaxf(m1, __shfl_xor_sync(0xffffffffu, m1, 2));
            m0 *= cs; m1 *= cs;
            float l0 = 0.f, l1 = 0.f;
#pragma unroll
            for (int j = 0; j < 8; j++) {
                s[4 * j]     = ex2(fmaf(s[4 * j], cs, -m0));
                s[4 * j + 1] = ex2(fmaf(s[4 * j + 1], cs, -m0));
                s[4 * j + 2] = ex2(fmaf(s[4 * j + 2], cs, -m1));
                s[4 * j + 3] = ex2(fmaf(s[4 * j + 3], cs, -m1));
                l0 += s[4 * j] + s[4 * j + 1];
                l1 += s[4 * j + 2] + s[4 * j + 3];
            }
            l0 += __shfl_xor_sync(0xffffffffu, l0, 1);
            l1 += __shfl_xor_sync(0xffffffffu, l1, 1);
            l0 += __shfl_xor_sync(0xffffffffu, l0, 2);
            l1 += __shfl_xor_sync(0xffffffffu, l1, 2);
            const float r0 = rcp(l0), r1 = rcp(l1);
#pragma unroll
            for (int j = 0; j < 8; j++) {
                pa[2 * j]     = pack_bf16(s[4 * j] * r0, s[4 * j + 1] * r0);
                pa[2 * j + 1] = pack_bf16(s[4 * j + 2] * r1, s[4 * j + 3] * r1);
            }
        }

        const uint32_t wu = __reduce_or_sync(0xffffffffu, tid_now() >> 5);
        const uint32_t dXt = desc_xt(wu >> 2);
        if ((wu & 3) != 0) asm volatile("bar.sync %0, 128;" ::"r"((wu >> 2) + 4) : "memory");
        uint32_t pub;
        asm volatile("ld.shared.u32 %0, [%1];" : "=r"(pub) : "r"(sbase + kOffBar + 64 + 4 * (tid_now() >> 7)) : "memory");
        const int nxt = (int)__reduce_or_sync(0xffffffffu, pub);
        store_p_if(pa, nxt == (int)kDone + kNWG - 1);
        if (nxt == (int)kDone + kNWG - 1) {
            last_window(out, win);
            asm volatile("exit;");
            __builtin_unreachable();
        }
        fence_regs(pa);
        wg_fence();
        ring_wait();
        Gemm3<3>::run(acc, pa, dXt);
        wg_commit();
        if constexpr (PASS3 == 3) ring_pass();
        wg_wait0();
        fence_regs(acc);
        fence_regs(pa);

        if (((tid_now() >> 5) & 3) == 0) {
            asm volatile("bar.sync %0, 128;" ::"r"((tid_now() >> 7) + 1) : "memory");
            if (elect_one()) {
                const uint32_t wgl = tid_now() >> 7;
                const uint32_t bar = sbase + kOffBar + 8 * wgl;
                if (nxt < kNWin) {
                    mbar_expect_tx(bar, kXBytes);
                    tma_load_x_hint(sbase + kOffX + wgl * kXBytes, &tmx, bar, nxt & 4095, nxt >= kNWin - EF_LAST);
                    uint32_t again;
                    asm volatile("ld.volatile.shared.u32 %0, [%1];" : "=r"(again) : "r"(sbase + kOffBar + 64 + 4 * wgl) : "memory");
                    prefetch_for_ticket(&tmp, (int)again - kNWG * G, G);
                }
            }
            __syncwarp();
        } else {
            asm volatile("bar.arrive %0, 128;" ::"r"((tid_now() >> 7) + 1) : "memory");
        }
#pragma unroll
        for (int i = 0; i < 48; i++) fa[i] = pack_bf16(acc[2 * i], acc[2 * i + 1]);

        asm volatile("{\n.reg .pred p;\nsetp.lt.s32 p, %5, 0;\n@p st.volatile.shared.v4.b32 [%4], {%0, %1, %2, %3};\n}\n"
                     :: "r"(fa[44]), "r"(fa[45]), "r"(fa[46]), "r"(fa[47]), "r"(sbase + kOffBar + 64), "r"(nxt) : "memory");
        fence_regs(fa);
        wg_fence();
        ring_wait();
        Gemm4<0, 1>::run(acc, fa, dWv);
        wg_commit();
        Gemm4<2, 10>::run(acc, fa, dWv);
        wg_commit();
        wg_wait1();
        uint32_t fl[4];
        uint32_t zero;
        asm volatile("ld.volatile.shared.u32 %0, [%1];" : "=r"(zero) : "r"(sbase + kOffBar + 76) : "memory");
#pragma unroll
        for (int i = 0; i < 4; i++) fl[i] = fa[44 + i] ^ zero;
        if constexpr (PASS4 == 10) ring_pass();
        wg_fence();
        wg192_rs<false, 0, koff(11, 24576)>(acc, fl, dWv);
        wg_commit();
        if constexpr (PASS4 == 11) ring_pass();
        pos = out_pos(win ^ zero);
        win = nxt | (~win & kPhase);
        const uint32_t dX = desc_x(__reduce_or_sync(0xffffffffu, (tid_now() >> 7) ^ zero));
        asm volatile("" : "+r"(pos) :: "memory");
        wg_wait0();
        fence_regs(acc);
        fence_regs(fa);
        fence_regs(fl);

#pragma unroll
        for (int a = 0; a < 6; a++) {
            hv[2 * a].x     = pack_bf16(acc[16 * a + 0], acc[16 * a + 1]);
            hv[2 * a].y     = pack_bf16(acc[16 * a + 4], acc[16 * a + 5]);
            hv[2 * a].z     = pack_bf16(acc[16 * a + 8], acc[16 * a + 9]);
            hv[2 * a].w     = pack_bf16(acc[16 * a + 12], acc[16 * a + 13]);
            hv[2 * a + 1].x = pack_bf16(acc[16 * a + 2], acc[16 * a + 3]);
            hv[2 * a + 1].y = pack_bf16(acc[16 * a + 6], acc[16 * a + 7]);
            hv[2 * a + 1].z = pack_bf16(acc[16 * a + 10], acc[16 * a + 11]);
            hv[2 * a + 1].w = pack_bf16(acc[16 * a + 14], acc[16 * a + 15]);
        }
        if (win < (int)kDone) mbar_wait(sbase + kOffBar + 8 * (tid_now() >> 7), (win >> 16) & 1);
        if (win >= (int)kDone) break;
        wg_fence();
        ring_wait();
        Gemm1<0, PASS1>::run(acc, dX, dWm);
        if constexpr (PASS1 < 11) {
            ring_pass();
            Gemm1<PASS1 + 1, 11>::run(acc, dX, dWm);
        }
        wg_commit();
        if constexpr (PASS1 == 11) ring_pass();
        ticket = draw_ticket(tickets, G);
        asm volatile("bar.sync 15, 256;" ::: "memory");
        stage_window<0>(hv, &tmo, pos, win);
        wg_wait0();
        fence_regs(acc);
#pragma unroll
        for (int i = 0; i < 48; i++) fa[i] = pack_bf16(acc[2 * i], acc[2 * i + 1]);

        fence_regs(fa);
        wg_fence();
        ring_wait();
        Gemm2<11>::run(s, fa, dX);
        wg_commit();
        if constexpr (PASS2 == 11) ring_pass();
        publish(ticket, G);
        asm volatile("cp.async.bulk.wait_group.read 0;" ::: "memory");
        asm volatile("bar.arrive 15, 256;" ::: "memory");
        wg_wait0();
        fence_regs(s);
        fence_regs(fa);
    }
    if ((win & 3) == 0) {
        const uint32_t buf = sbase + kOffX + (tid_now() >> 7) * kXBytes + ((tid_now() >> 5) & 3) * 2048;
        asm volatile("bar.sync %0, 128;" ::"r"((tid_now() >> 7) + 1) : "memory");
        ring_wait();
        ring_pass();
        stage_put<0>(hv, buf);
        stage_send(&tmo, pos, 0, buf);
        stage_put<1>(hv, buf + 8192);
        stage_send(&tmo, pos, 1, buf + 8192);
        stage_put<2>(hv, buf + 2 * 8192);
        stage_send(&tmo, pos, 2, buf + 2 * 8192);
        clear_images(sc);
        asm volatile("bar.sync 15, 256;" ::: "memory");
        stage_wait();
    } else {
        uint8_t* hptr = out_address(out, pos);
        store_tail<0>(hv, hptr, clock_now());
    }
}

typedef CUresult (*EncodeTiledFn)(CUtensorMap*, CUtensorMapDataType, cuuint32_t, void*, const cuuint64_t*,
                                  const cuuint64_t*, const cuuint32_t*, const cuuint32_t*, CUtensorMapInterleave,
                                  CUtensorMapSwizzle, CUtensorMapL2promotion, CUtensorMapFloatOOBfill);

}

extern "C" void kernel_launch(void* const* d_in, const int* in_sizes, int n_in, void* d_out, int out_size) {
    (void)in_sizes; (void)n_in; (void)out_size;
    const __nv_bfloat16* x    = (const __nv_bfloat16*)d_in[0];
    const __nv_bfloat16* wqkv = (const __nv_bfloat16*)d_in[1];
    const __nv_bfloat16* wo   = (const __nv_bfloat16*)d_in[2];

    static EncodeTiledFn encode = nullptr;
    static int num_sms = 0;
    static void* scratch = nullptr;
    if (!encode) {
        void* fn = nullptr;
        cudaDriverEntryPointQueryResult qr;
        cudaGetDriverEntryPoint("cuTensorMapEncodeTiled", &fn, cudaEnableDefault, &qr);
        encode = (EncodeTiledFn)fn;
        int dev = 0;
        cudaGetDevice(&dev);
        cudaDeviceGetAttribute(&num_sms, cudaDevAttrMultiProcessorCount, dev);
        if (num_sms > kNWin / 16) num_sms = kNWin / 16;
        cudaGetSymbolAddress(&scratch, g_scratch);
        cudaFuncSetAttribute(swin_attn_kernel<false>, cudaFuncAttributeMaxDynamicSharedMemorySize, kSmemBytes);
        cudaFuncSetAttribute(swin_attn_kernel<true>, cudaFuncAttributeMaxDynamicSharedMemorySize, kSmemBytes);
    }
    CUtensorMap tmx;
    const cuuint64_t gdim[5] = {(cuuint64_t)kC, (cuuint64_t)kHW / 2, 2, 2, (cuuint64_t)kHW / 2};
    const cuuint64_t gstr[4] = {(cuuint64_t)kC * 4, (cuuint64_t)kHW * kC * 2, (cuuint64_t)kC * 2, (cuuint64_t)kHW * kC * 4};
    const cuuint32_t box[5] = {64, 4, 2, 2, 4};
    const cuuint32_t estr[5] = {1, 1, 1, 1, 1};
    encode(&tmx, CU_TENSOR_MAP_DATA_TYPE_BFLOAT16, 5, (void*)x, gdim, gstr, box, estr, CU_TENSOR_MAP_INTERLEAVE_NONE,
           CU_TENSOR_MAP_SWIZZLE_128B, CU_TENSOR_MAP_L2_PROMOTION_NONE, CU_TENSOR_MAP_FLOAT_OOB_FILL_NONE);

    CUtensorMap tmp;
    const cuuint64_t pdim[3] = {(cuuint64_t)kC, (cuuint64_t)kHW, (cuuint64_t)kHW};
    const cuuint64_t pstr[2] = {(cuuint64_t)kC * 2, (cuuint64_t)kHW * kC * 2};
    const cuuint32_t pbox[3] = {(cuuint32_t)kC, 8, 8};
    encode(&tmp, CU_TENSOR_MAP_DATA_TYPE_BFLOAT16, 3, (void*)x, pdim, pstr, pbox, estr, CU_TENSOR_MAP_INTERLEAVE_NONE,
           CU_TENSOR_MAP_SWIZZLE_NONE, CU_TENSOR_MAP_L2_PROMOTION_NONE, CU_TENSOR_MAP_FLOAT_OOB_FILL_NONE);
    CUtensorMap tmo;
    const cuuint64_t odim[5] = {64, 6, (cuuint64_t)kHW / 4, 2, (cuuint64_t)kHW};
    const cuuint64_t ostr[4] = {128, (cuuint64_t)kC * 8, (cuuint64_t)kC * 4, (cuuint64_t)kHW * kC * 2};
    const cuuint32_t obox[5] = {64, 2, 2, 2, 2};
    encode(&tmo, CU_TENSOR_MAP_DATA_TYPE_BFLOAT16, 5, d_out, odim, ostr, obox, estr, CU_TENSOR_MAP_INTERLEAVE_NONE,
           CU_TENSOR_MAP_SWIZZLE_128B, CU_TENSOR_MAP_L2_PROMOTION_NONE, CU_TENSOR_MAP_FLOAT_OOB_FILL_NONE);
    if (num_sms >= kJobs)
        swin_attn_kernel<false><<<num_sms, kThreads, kSmemBytes, cudaStreamPerThread>>>(wqkv, wo, x, (Scratch*)scratch, ((Scratch*)scratch)->ticket, num_sms, TRK_HOST * 256 / num_sms, (__nv_bfloat16*)d_out, tmx, tmp, tmo);
    else
        swin_attn_kernel<true><<<num_sms, kThreads, kSmemBytes, cudaStreamPerThread>>>(wqkv, wo, x, (Scratch*)scratch, ((Scratch*)scratch)->ticket, num_sms, TRK_HOST * 256 / num_sms, (__nv_bfloat16*)d_out, tmx, tmp, tmo);
}
```

```cpp
#include <cuda_runtime.h>
#include <cuda_bf16.h>
#include <cuda.h>
#include <stdint.h>

namespace {

constexpr int kC      = 192;
constexpr int kHW     = 512;
#define MAXWIN 4096
constexpr int kNWin   = MAXWIN;
constexpr int kXBytes = 64 * kC * 2;
constexpr int kWBytes = kC * kC * 2;
constexpr int kNWG    = 3;
constexpr int kThreads = kNWG * 128;
constexpr int kJobsM  = 72;
constexpr int kJobs   = 120;
constexpr int kWarmW  = 4;
#define PF_LEAD 400
#define PF_UP 114
#define PF_DOWN 39
#define PF_END 300
#define PF_MIN 135
#define EF_LAST 1000
#define TRK_T0 500
#define TRK_S 1700
#define TRK_HOST (TRK_S * 256 / num_sms)
#define TRK_Q trk
#define X0_LATE 72
#define REQ_T 2360
#define REQ_TV 4000

constexpr int kOffWm  = 0;
constexpr int kOffWv  = kWBytes;
constexpr int kOffX   = 2 * kWBytes;
constexpr int kOffStage = kOffX + kNWG * kXBytes;
constexpr int kOffBar = kOffStage + 8192;
constexpr int kOffBarM = kOffBar + 128;
constexpr int kOffProf = kOffBar + 192;
constexpr int kSmemBytes = kOffProf;
constexpr uint32_t kSmemBase = 1024;

struct Scratch {
    uint4 wfold[2 * kWBytes / 16];
    uint32_t ticket[32];
    uint32_t cnt[32];
};
__device__ __align__(128) Scratch g_scratch;

__device__ __forceinline__ uint32_t smem_u32(const void* p) { return (uint32_t)__cvta_generic_to_shared(p); }

__device__ __forceinline__ void mbar_init(uint32_t bar, uint32_t count) {
    asm volatile("mbarrier.init.shared::cta.b64 [%0], %1;" ::"r"(bar), "r"(count) : "memory");
}
__device__ __forceinline__ void mbar_expect_tx(uint32_t bar, uint32_t bytes) {
    asm volatile("mbarrier.arrive.expect_tx.shared::cta.b64 _, [%0], %1;" ::"r"(bar), "r"(bytes) : "memory");
}
__device__ __forceinline__ void mbar_wait(uint32_t bar, uint32_t parity) {
    uint32_t ok;
    uint32_t spins = 0;
    do {
        asm volatile("{\n.reg .pred p;\n"
                     "mbarrier.try_wait.parity.shared::cta.b64 p, [%1], %2;\n"
                     "selp.b32 %0, 1, 0, p;\n}\n"
                     : "=r"(ok) : "r"(bar), "r"(parity) : "memory");
        if (++spins > (1u << 26)) __trap();
    } while (!ok);
}
__device__ __forceinline__ uint32_t tid_now() {
    uint32_t t;
    asm volatile("mov.u32 %0, %%tid.x;" : "=r"(t));
    return t;
}
__device__ __forceinline__ uint32_t nctaid_now() {
    uint32_t t;
    asm volatile("mov.u32 %0, %%nctaid.x;" : "=r"(t));
    return t;
}
__device__ __forceinline__ bool elect_one() {
    uint32_t pred;
    asm volatile("{\n.reg .pred p;\nelect.sync _|p, 0xffffffff;\nselp.b32 %0, 1, 0, p;\n}\n" : "=r"(pred));
    return pred != 0;
}
#define PASS1 10
#define PASS4 11
#define PASS2 7
#define PASS3 3
__device__ __forceinline__ void ring_wait() {
    asm volatile("bar.sync %0, 256;" ::"r"((tid_now() >> 7) + 8) : "memory");
}
__device__ __forceinline__ void ring_pass() {
    const uint32_t w = tid_now() >> 7;
    asm volatile("bar.arrive %0, 256;" ::"r"(w == kNWG - 1 ? 8u : w + 9u) : "memory");
}
constexpr uint32_t kDone = 0x40000000u;
constexpr int kPhase = 0x10000;
__device__ __forceinline__ uint32_t wg_uniform() { return __reduce_or_sync(0xffffffffu, tid_now() >> 7); }
__device__ __forceinline__ uint32_t desc_x(uint32_t w) { return (((kSmemBase + kOffX) >> 4) | (1u << 16)) + w * (kXBytes >> 4); }
__device__ __forceinline__ uint32_t desc_xt(uint32_t w) { return (((kSmemBase + kOffX) >> 4) | ((8192u >> 4) << 16)) + w * (kXBytes >> 4); }
__device__ __forceinline__ void tma_load_x_chunk(uint32_t dst, const CUtensorMap* tm, uint32_t bar, int win, int chunk) {
    asm volatile("cp.async.bulk.tensor.5d.shared::cluster.global.mbarrier::complete_tx::bytes"
                 " [%0], [%1, {%3, %4, %6, %6, %5}], [%2];"
                 ::"r"(dst), "l"(tm), "r"(bar), "r"(chunk * 64), "r"((win & 63) * 4), "r"((win >> 6) * 4), "r"(0) : "memory");
}
__device__ __forceinline__ void tma_load_x_hint(uint32_t dst, const CUtensorMap* tm, uint32_t bar, int win, bool evict_first) {
    uint64_t first, normal;
    asm("createpolicy.fractional.L2::evict_first.b64 %0, 1.0;" : "=l"(first));
    asm("createpolicy.fractional.L2::evict_normal.b64 %0, 1.0;" : "=l"(normal));
#pragma unroll
    for (int c = 0; c < 3; c++)
        asm volatile("cp.async.bulk.tensor.5d.shared::cluster.global.mbarrier::complete_tx::bytes.L2::cache_hint"
                     " [%0], [%1, {%3, %4, %6, %6, %5}], [%2], %7;"
                     ::"r"(dst + c * 8192), "l"(tm), "r"(bar), "r"(c * 64), "r"((win & 63) * 4), "r"((win >> 6) * 4), "r"(0),
                       "l"(evict_first ? first : normal) : "memory");
}
__device__ __forceinline__ void bulk_load(uint32_t dst, const void* src, uint32_t bytes, uint32_t bar) {
    asm volatile("cp.async.bulk.shared::cluster.global.mbarrier::complete_tx::bytes [%0], [%1], %2, [%3];"
                 ::"r"(dst), "l"(src), "r"(bytes), "r"(bar) : "memory");
}

__device__ __forceinline__ void wg_fence()  { asm volatile("wgmma.fence.sync.aligned;" ::: "memory"); }
__device__ __forceinline__ void wg_commit() { asm volatile("wgmma.commit_group.sync.aligned;" ::: "memory"); }
__device__ __forceinline__ void wg_wait0()  { asm volatile("wgmma.wait_group.sync.aligned 0;" ::: "memory"); }
__device__ __forceinline__ void wg_wait1()  { asm volatile("wgmma.wait_group.sync.aligned 1;" ::: "memory"); }
__device__ __forceinline__ void wg_wait2()  { asm volatile("wgmma.wait_group.sync.aligned 2;" ::: "memory"); }

template <int N> __device__ __forceinline__ void fence_regs(float (&d)[N]) {
#pragma unroll
    for (int i = 0; i < N; i++) asm volatile("" : "+f"(d[i])::"memory");
}
template <int N> __device__ __forceinline__ void fence_regs(uint32_t (&d)[N]) {
#pragma unroll
    for (int i = 0; i < N; i++) asm volatile("" : "+r"(d[i])::"memory");
}

#define ACC8(c, d, i) c(d[i]), c(d[i + 1]), c(d[i + 2]), c(d[i + 3]), c(d[i + 4]), c(d[i + 5]), c(d[i + 6]), c(d[i + 7])
#define ACC32(c, d) ACC8(c, d, 0), ACC8(c, d, 8), ACC8(c, d, 16), ACC8(c, d, 24)
#define ACC96(c, d) ACC32(c, d), ACC8(c, d, 32), ACC8(c, d, 40), ACC8(c, d, 48), ACC8(c, d, 56), \
                    ACC8(c, d, 64), ACC8(c, d, 72), ACC8(c, d, 80), ACC8(c, d, 88)
#define C_IO(x) "+f"(x)
#define C_O(x) "=f"(x)
#define REGS32 "{%0, %1, %2, %3, %4, %5, %6, %7, %8, %9, %10, %11, %12, %13, %14, %15, " \
               "%16, %17, %18, %19, %20, %21, %22, %23, %24, %25, %26, %27, %28, %29, %30, %31}"
#define REGS96 "{%0, %1, %2, %3, %4, %5, %6, %7, %8, %9, %10, %11, %12, %13, %14, %15, " \
               "%16, %17, %18, %19, %20, %21, %22, %23, %24, %25, %26, %27, %28, %29, %30, %31, " \
               "%32, %33, %34, %35, %36, %37, %38, %39, %40, %41, %42, %43, %44, %45, %46, %47, " \
               "%48, %49, %50, %51, %52, %53, %54, %55, %56, %57, %58, %59, %60, %61, %62, %63, " \
               "%64, %65, %66, %67, %68, %69, %70, %71, %72, %73, %74, %75, %76, %77, %78, %79, " \
               "%80, %81, %82, %83, %84, %85, %86, %87, %88, %89, %90, %91, %92, %93, %94, %95}"

#define DESC_HI "0x40000040"
#define MK_DESC(name, lo, off) "add.u32 t, " lo ", " off ";\nmov.b64 " name ", {t, " DESC_HI "};\n"

template <bool First, int OA, int OB> __device__ __forceinline__ void wg192_ss(float (&d)[96], uint32_t la, uint32_t lb) {
    if constexpr (First)
        asm volatile("{\n.reg .pred p;\n.reg .b32 t;\n.reg .b64 da, db;\nsetp.ne.b32 p, 0, 0;\n"
                     MK_DESC("da", "%96", "%98") MK_DESC("db", "%97", "%99")
                     "wgmma.mma_async.sync.aligned.m64n192k16.f32.bf16.bf16 " REGS96 ", da, db, p, 1, 1, 0, 0;\n}\n"
                     : ACC96(C_O, d) : "r"(la), "r"(lb), "n"(OA), "n"(OB));
    else
        asm volatile("{\n.reg .pred p;\n.reg .b32 t;\n.reg .b64 da, db;\nsetp.ne.b32 p, 1, 0;\n"
                     MK_DESC("da", "%96", "%98") MK_DESC("db", "%97", "%99")
                     "wgmma.mma_async.sync.aligned.m64n192k16.f32.bf16.bf16 " REGS96 ", da, db, p, 1, 1, 0, 0;\n}\n"
                     : ACC96(C_IO, d) : "r"(la), "r"(lb), "n"(OA), "n"(OB));
}
#define ACC48(c, d, o) ACC8(c, d, o), ACC8(c, d, o + 8), ACC8(c, d, o + 16), ACC8(c, d, o + 24), ACC8(c, d, o + 32), ACC8(c, d, o + 40)
#define REGS48 "{%0, %1, %2, %3, %4, %5, %6, %7, %8, %9, %10, %11, %12, %13, %14, %15, %16, %17, %18, %19, %20, %21, %22, %23, " \
               "%24, %25, %26, %27, %28, %29, %30, %31, %32, %33, %34, %35, %36, %37, %38, %39, %40, %41, %42, %43, %44, %45, %46, %47}"
template <bool First, int OA, int OB> __device__ __forceinline__ void wg96_ss(float (&d)[48], uint32_t la, uint32_t lb) {
    if constexpr (First)
        asm volatile("{\n.reg .pred p;\n.reg .b32 t;\n.reg .b64 da, db;\nsetp.ne.b32 p, 0, 0;\n"
                     MK_DESC("da", "%48", "%50") MK_DESC("db", "%49", "%51")
                     "wgmma.mma_async.sync.aligned.m64n96k16.f32.bf16.bf16 " REGS48 ", da, db, p, 1, 1, 0, 0;\n}\n"
                     : ACC48(C_O, d, 0) : "r"(la), "r"(lb), "n"(OA), "n"(OB));
    else
        asm volatile("{\n.reg .pred p;\n.reg .b32 t;\n.reg .b64 da, db;\nsetp.ne.b32 p, 1, 0;\n"
                     MK_DESC("da", "%48", "%50") MK_DESC("db", "%49", "%51")
                     "wgmma.mma_async.sync.aligned.m64n96k16.f32.bf16.bf16 " REGS48 ", da, db, p, 1, 1, 0, 0;\n}\n"
                     : ACC48(C_IO, d, 0) : "r"(la), "r"(lb), "n"(OA), "n"(OB));
}
template <bool First, int TB, int OB> __device__ __forceinline__ void wg192_rs(float (&d)[96], const uint32_t* a, uint32_t lb) {
    if constexpr (First)
        asm volatile("{\n.reg .pred p;\n.reg .b32 t;\n.reg .b64 db;\nsetp.ne.b32 p, 0, 0;\n"
                     MK_DESC("db", "%100", "%102")
                     "wgmma.mma_async.sync.aligned.m64n192k16.f32.bf16.bf16 " REGS96 ", {%96, %97, %98, %99}, db, p, 1, 1, %101;\n}\n"
                     : ACC96(C_O, d) : "r"(a[0]), "r"(a[1]), "r"(a[2]), "r"(a[3]), "r"(lb), "n"(TB), "n"(OB));
    else
        asm volatile("{\n.reg .pred p;\n.reg .b32 t;\n.reg .b64 db;\nsetp.ne.b32 p, 1, 0;\n"
                     MK_DESC("db", "%100", "%102")
                     "wgmma.mma_async.sync.aligned.m64n192k16.f32.bf16.bf16 " REGS96 ", {%96, %97, %98, %99}, db, p, 1, 1, %101;\n}\n"
                     : ACC96(C_IO, d) : "r"(a[0]), "r"(a[1]), "r"(a[2]), "r"(a[3]), "r"(lb), "n"(TB), "n"(OB));
}
template <bool First, int OB> __device__ __forceinline__ void wg64_rs(float (&d)[32], const uint32_t* a, uint32_t lb) {
    if constexpr (First)
        asm volatile("{\n.reg .pred p;\n.reg .b32 t;\n.reg .b64 db;\nsetp.ne.b32 p, 0, 0;\n"
                     MK_DESC("db", "%36", "%37")
                     "wgmma.mma_async.sync.aligned.m64n64k16.f32.bf16.bf16 " REGS32 ", {%32, %33, %34, %35}, db, p, 1, 1, 0;\n}\n"
                     : ACC32(C_O, d) : "r"(a[0]), "r"(a[1]), "r"(a[2]), "r"(a[3]), "r"(lb), "n"(OB));
    else
        asm volatile("{\n.reg .pred p;\n.reg .b32 t;\n.reg .b64 db;\nsetp.ne.b32 p, 1, 0;\n"
                     MK_DESC("db", "%36", "%37")
                     "wgmma.mma_async.sync.aligned.m64n64k16.f32.bf16.bf16 " REGS32 ", {%32, %33, %34, %35}, db, p, 1, 1, 0;\n}\n"
                     : ACC32(C_IO, d) : "r"(a[0]), "r"(a[1]), "r"(a[2]), "r"(a[3]), "r"(lb), "n"(OB));
}
template <bool First, int OA, int OB> __device__ __forceinline__ void wg64_ss(float (&d)[32], uint32_t la, uint32_t lb) {
    if constexpr (First)
        asm volatile("{\n.reg .pred p;\n.reg .b32 t;\n.reg .b64 da, db;\nsetp.ne.b32 p, 0, 0;\n"
                     MK_DESC("da", "%32", "%34") MK_DESC("db", "%33", "%35")
                     "wgmma.mma_async.sync.aligned.m64n64k16.f32.bf16.bf16 " REGS32 ", da, db, p, 1, 1, 0, 1;\n}\n"
                     : ACC32(C_O, d) : "r"(la), "r"(lb), "n"(OA), "n"(OB));
    else
        asm volatile("{\n.reg .pred p;\n.reg .b32 t;\n.reg .b64 da, db;\nsetp.ne.b32 p, 1, 0;\n"
                     MK_DESC("da", "%32", "%34") MK_DESC("db", "%33", "%35")
                     "wgmma.mma_async.sync.aligned.m64n64k16.f32.bf16.bf16 " REGS32 ", da, db, p, 1, 1, 0, 1;\n}\n"
                     : ACC32(C_IO, d) : "r"(la), "r"(lb), "n"(OA), "n"(OB));
}
__host__ __device__ constexpr int koff(int kk, int chunk) { return ((kk >> 2) * chunk + (kk & 3) * 32) >> 4; }

__device__ __forceinline__ uint32_t clock_now() {
    uint32_t t;
    asm volatile("mov.u32 %0, %%clock;" : "=r"(t));
    return t;
}
template <int K> __device__ __forceinline__ void stage_put(const uint4 (&h)[12], uint32_t buf) {
    const uint32_t t = tid_now(), line = ((t >> 2) & 2) + (t & 4) + ((t >> 1) & 8);
    const uint32_t adr = buf + line * 128 + (((t & 3) ^ (line & 7)) << 4);
#pragma unroll
    for (int j = 0; j < 4; j++) {
        const int i = 4 * K + j, n = 2 * (i % 6) + i / 6;
        asm volatile("st.shared.v4.b32 [%4], {%0, %1, %2, %3};"
                     :: "r"(h[n].x), "r"(h[n].y), "r"(h[n].z), "r"(h[n].w), "r"((adr ^ ((j & 1) * 64 + (j >> 1) * 16)) + (j >> 1) * 128) : "memory");
    }
}
__device__ __forceinline__ void stage_send(const CUtensorMap* tm, uint32_t pos, int k, uint32_t buf) {
    asm volatile("fence.proxy.async.shared::cta;" ::: "memory");
    __syncwarp();
    if (elect_one()) {
        asm volatile("cp.async.bulk.tensor.5d.global.shared::cta.bulk_group [%0, {%2, %5, %3, %2, %4}], [%1];"
                     ::"l"(tm), "r"(buf), "r"(0), "r"(pos & 0xffff), "r"(pos >> 16), "r"(2 * k) : "memory");
        asm volatile("cp.async.bulk.commit_group;" ::: "memory");
    }
    __syncwarp();
}
__device__ __forceinline__ void stage_wait() {
    asm volatile("cp.async.bulk.wait_group.read 0;" ::: "memory");
    __syncwarp();
}
__device__ __forceinline__ uint32_t out_pos(int win) {
    return ((win & 63) * 2) | (((((win & 4095) >> 6) & 63) * 8 + 2 * ((tid_now() >> 5) & 3)) << 16);
}
__device__ __forceinline__ uint32_t stage_buf() { return kSmemBase + kOffStage + ((tid_now() >> 5) & 3) * 2048; }
template <int K> __device__ __forceinline__ void stage_window(uint4 (&h)[12], const CUtensorMap* tm, uint32_t pos, [[maybe_unused]] int win) {
    if constexpr (K < 3) {
        if constexpr (K > 0) stage_wait();
        stage_put<K>(h, stage_buf());
        stage_send(tm, pos, K, stage_buf());
        stage_window<K + 1>(h, tm, pos, win);
    }
}
__device__ __forceinline__ void stg128(void* p, uint4 v) {
    asm volatile("st.global.v4.b32 [%0], {%1, %2, %3, %4};" ::"l"(p), "r"(v.x), "r"(v.y), "r"(v.z), "r"(v.w) : "memory");
}
#define TAIL_DT 90
#define TAIL_FREE 2
template <int J> __device__ __forceinline__ void store_tail(uint4 (&h)[12], uint8_t* hptr, uint32_t t0) {
    if constexpr (J < 12) {
        if (J > TAIL_FREE) { while (clock_now() - t0 < (uint32_t)((J - TAIL_FREE) * TAIL_DT)) {} }
        stg128(hptr + J * 64, h[2 * (J % 6) + J / 6]);
        store_tail<J + 1>(h, hptr, t0);
    }
}
__device__ __forceinline__ uint8_t* out_address(__nv_bfloat16* out, uint32_t pos) {
    const uint32_t ln = tid_now() & 31;
    return reinterpret_cast<uint8_t*>(out) + (((pos >> 16) + (ln >> 4)) * kHW + (pos & 0xffff) * 4 + ((ln >> 1) & 6)) * (uint32_t)(kC * 2) + (ln & 3) * 16;
}
template <int K0, int K> struct Gemm1 {
    static __device__ __forceinline__ void run(float (&d)[96], uint32_t lx, uint32_t lw) {
        if constexpr (K > K0) Gemm1<K0, K - 1>::run(d, lx, lw);
        wg192_ss<K == 0, koff(K, 8192), koff(K, 24576)>(d, lx, lw);
    }
};
__device__ __forceinline__ uint32_t draw_ticket(uint32_t* counter, int G) {
    uint32_t ticket = 0;
    asm volatile("{\n.reg .pred p;\nsetp.eq.u32 p, %2, 0;\n@p atom.relaxed.gpu.global.inc.u32 %0, [%1], %3;\n}\n"
                 : "+r"(ticket) : "l"(counter), "r"(tid_now() & 127), "r"(kNWin - 1 - kNWG * G) : "memory");
    return ticket;
}
template <int KK> struct Gemm2 { static __device__ __forceinline__ void run(float (&d)[32], const uint32_t* a, uint32_t lx) {
    Gemm2<KK - 1>::run(d, a, lx); wg64_rs<KK == 0, koff(KK, 8192)>(d, a + 4 * KK, lx);
    if constexpr (KK == PASS2 && KK < 11) ring_pass(); } };
template <int K0, int KK> struct Gemm2p { static __device__ __forceinline__ void run(float (&d)[32], const uint32_t* a, uint32_t lx) {
    if constexpr (KK > K0) Gemm2p<K0, KK - 1>::run(d, a, lx);
    wg64_rs<KK == 0, koff(KK, 8192)>(d, a + 4 * KK, lx); } };
template <int H, int C, int KK = 3> struct Gemm1h { static __device__ __forceinline__ void run(float (&d)[48], uint32_t lx, uint32_t lw) {
    if constexpr (KK > 0) Gemm1h<H, C, KK - 1>::run(d, lx, lw);
    wg96_ss<C == 0 && KK == 0, koff(4 * C + KK, 8192), koff(4 * C + KK, 24576) + H * 96 * 8>(d, lx, lw); } };
template <> struct Gemm2<-1> { static __device__ __forceinline__ void run(float (&)[32], const uint32_t*, uint32_t) {} };
template <int KK> struct Gemm3 { static __device__ __forceinline__ void run(float (&d)[96], const uint32_t* a, uint32_t lxt) {
    Gemm3<KK - 1>::run(d, a, lxt); wg192_rs<KK == 0, 1, KK * (2048 >> 4)>(d, a + 4 * KK, lxt);
    if constexpr (KK == PASS3 && KK < 3) ring_pass(); } };
template <> struct Gemm3<-1> { static __device__ __forceinline__ void run(float (&)[96], const uint32_t*, uint32_t) {} };
template <int K0, int KK> struct Gemm4 { static __device__ __forceinline__ void run(float (&d)[96], const uint32_t* a, uint32_t lw) {
    if constexpr (KK > K0) Gemm4<K0, KK - 1>::run(d, a, lw);
    wg192_rs<KK == 0, 0, koff(KK, 24576)>(d, a + 4 * KK, lw); } };

template <int J, int KK> struct Gemm3s { static __device__ __forceinline__ void run(float (&d)[32], uint32_t lp, uint32_t lxt) {
    if constexpr (KK > 0) Gemm3s<J, KK - 1>::run(d, lp, lxt);
    wg64_ss<KK == 0, KK * 2, (J * 8192 + KK * 2048) / 16>(d, lp, lxt); } };
template <int J, int K0, int KK> struct Gemm4s { static __device__ __forceinline__ void run(float (&d)[32], const uint32_t* a, uint32_t lw) {
    if constexpr (KK > K0) Gemm4s<J, K0, KK - 1>::run(d, a, lw);
    wg64_rs<KK == 0, koff(KK, 24576) + J * (8192 / 16)>(d, a + 4 * KK, lw); } };

__device__ __forceinline__ uint32_t pack_bf16(float lo, float hi) {
    uint32_t r;
    asm("cvt.rn.bf16x2.f32 %0, %1, %2;" : "=r"(r) : "f"(hi), "f"(lo));
    return r;
}
__device__ __forceinline__ float ex2(float x) {
    float r;
    asm("ex2.approx.ftz.f32 %0, %1;" : "=f"(r) : "f"(x));
    return r;
}
__device__ __forceinline__ float rcp(float x) {
    float r;
    asm("rcp.approx.ftz.f32 %0, %1;" : "=f"(r) : "f"(x));
    return r;
}

__device__ __forceinline__ void pack_slice(uint32_t* a, float (&d)[32]) {
    fence_regs(d);
#pragma unroll
    for (int i = 0; i < 16; i++) a[i] = pack_bf16(d[2 * i], d[2 * i + 1]);
#pragma unroll
    for (int i = 0; i < 16; i++) asm volatile("" : "+r"(a[i])::"memory");
}
template <int J> __device__ __forceinline__ void store_slice(float (&d)[32], uint8_t* hptr) {
    fence_regs(d);
#pragma unroll
    for (int r = 0; r < 2; r++) {
        uint4 h[2];
#pragma unroll
        for (int a = 0; a < 2; a++) {
            const int o = 16 * a + 2 * r;
            h[a] = make_uint4(pack_bf16(d[o], d[o + 1]), pack_bf16(d[o + 4], d[o + 5]), pack_bf16(d[o + 8], d[o + 9]), pack_bf16(d[o + 12], d[o + 13]));
        }
        stg128(hptr + r * (kC * 2) + J * 128, h[0]);
        stg128(hptr + r * (kC * 2) + J * 128 + 64, h[1]);
    }
    __syncwarp();
}
__device__ __forceinline__ void store_p_if(const uint32_t (&pa)[16], bool cond) {
    const uint32_t t = tid_now(), row = ((t >> 1) & 48) + (t & 15);
    const uint32_t adr = kSmemBase + kOffStage + row * 128 + ((((t >> 4) & 1) ^ (t & 7)) << 4);
#pragma unroll
    for (int i = 0; i < 4; i++)
        asm volatile("{\n.reg .pred p;\nsetp.ne.u32 p, %5, 0;\n@p stmatrix.sync.aligned.m8n8.x4.shared.b16 [%4], {%0, %1, %2, %3};\n}\n"
                     :: "r"(pa[4 * i]), "r"(pa[4 * i + 1]), "r"(pa[4 * i + 2]), "r"(pa[4 * i + 3]), "r"(adr ^ (i << 5)), "r"((uint32_t)cond) : "memory");
}
__device__ __forceinline__ void last_window(__nv_bfloat16* out, int win) {
    constexpr uint32_t dWv = ((kSmemBase + kOffWv) >> 4) | (1u << 16);
    asm volatile("fence.proxy.async.shared::cta;" ::: "memory");
    const uint32_t w = wg_uniform();
    const uint32_t dXt = desc_xt(w);
    constexpr uint32_t dP = ((kSmemBase + kOffStage) >> 4) | (1u << 16);
    float u0[32], u1[32], u2[32];
    uint32_t fa[48];
    uint8_t* hptr = out_address(out, out_pos(win));
    asm volatile("" : "+l"(hptr) :: "memory");
    ring_wait();
    wg_fence();
    Gemm3s<0, 3>::run(u0, dP, dXt); wg_commit();
    Gemm3s<1, 3>::run(u1, dP, dXt); wg_commit();
    Gemm3s<2, 3>::run(u2, dP, dXt); wg_commit();
    wg_wait2();
    pack_slice(fa, u0);
    wg_fence();
    Gemm4s<0, 0, 3>::run(u0, fa, dWv); wg_commit();
    wg_wait2();
    pack_slice(fa + 16, u1);
    wg_fence();
    Gemm4s<0, 4, 7>::run(u0, fa, dWv); wg_commit();
    wg_wait2();
    pack_slice(fa + 32, u2);
    wg_fence();
    Gemm4s<0, 8, 11>::run(u0, fa, dWv); wg_commit();
    Gemm4s<1, 0, 5>::run(u1, fa, dWv); wg_commit();
    wg_wait1();
    store_slice<0>(u0, hptr);
    wg_fence();
    Gemm4s<1, 6, 11>::run(u1, fa, dWv); wg_commit();
    Gemm4s<2, 0, 5>::run(u2, fa, dWv); wg_commit();
    wg_wait1();
    store_slice<1>(u1, hptr);
    wg_fence();
    Gemm4s<2, 6, 11>::run(u2, fa, dWv); wg_commit();
    wg_wait0();
    fence_regs(fa);
    store_slice<2>(u2, hptr);
}

__device__ __forceinline__ int fold_offset(int n, int k0, int q) {
    const int u = ((k0 & 63) >> 3) + (q >> 1);
    return (k0 >> 6) * 24576 + (q & 1) * 8 + n * 128 + ((u ^ (n & 7)) << 4);
}
__device__ __forceinline__ void mma16816x2(float (&c)[4], float (&d)[4], const uint32_t (&a)[4], const uint32_t (&b)[4]) {
    asm volatile("mma.sync.aligned.m16n8k16.row.col.f32.bf16.bf16.f32 {%0,%1,%2,%3}, {%8,%9,%10,%11}, {%12,%13}, {%0,%1,%2,%3};\n"
                 "mma.sync.aligned.m16n8k16.row.col.f32.bf16.bf16.f32 {%4,%5,%6,%7}, {%8,%9,%10,%11}, {%14,%15}, {%4,%5,%6,%7};"
                 : "+f"(c[0]), "+f"(c[1]), "+f"(c[2]), "+f"(c[3]), "+f"(d[0]), "+f"(d[1]), "+f"(d[2]), "+f"(d[3])
                 : "r"(a[0]), "r"(a[1]), "r"(a[2]), "r"(a[3]), "r"(b[0]), "r"(b[1]), "r"(b[2]), "r"(b[3]));
}
__device__ __forceinline__ void cp_async16(uint32_t dst, const void* src) {
    asm volatile("cp.async.cg.shared.global [%0], [%1], 16;" ::"r"(dst), "l"(src) : "memory");
}
template <bool kTrans> __device__ __forceinline__ void ldsm4(uint32_t (&r)[4], uint32_t addr) {
    if constexpr (kTrans)
        asm volatile("ldmatrix.sync.aligned.m8n8.x4.trans.shared.b16 {%0, %1, %2, %3}, [%4];" : "=r"(r[0]), "=r"(r[1]), "=r"(r[2]), "=r"(r[3]) : "r"(addr) : "memory");
    else
        asm volatile("ldmatrix.sync.aligned.m8n8.x4.shared.b16 {%0, %1, %2, %3}, [%4];" : "=r"(r[0]), "=r"(r[1]), "=r"(r[2]), "=r"(r[3]) : "r"(addr) : "memory");
}
__device__ __forceinline__ uint32_t nonzero(uint32_t w) { return w ? w : 0x80000000u; }
template <bool vo>
__device__ __forceinline__ void fold_job(Scratch* sc, const __nv_bfloat16* __restrict__ wqkv, const __nv_bfloat16* __restrict__ wo,
                                         int job, int warp, int lane) {
    constexpr int nw = vo ? 3 : 2;
    const int nb = vo ? job >> 2 : (job * 43) >> 8;
    const int n0 = nb * 16, k0 = (nw * (vo ? job & 3 : job - 6 * nb) + max(warp, 1) - 1) * 16;
    const uint32_t stage = kSmemBase + kOffWv;
    if (warp != kWarmW) {
        if (vo) {
            const char* src = reinterpret_cast<const char*>(wo) + (uint32_t)(((warp * 48 + (lane >> 1)) * kC + n0 + (lane & 1) * 8) * 2);
            const uint32_t dst = stage + warp * 1536 + ((lane ^ ((lane >> 3) & 1)) << 4);
#pragma unroll
            for (int i = 0; i < 3; i++) cp_async16(dst + i * 512, src + i * 16 * kC * 2);
        }
        if (!vo || warp != 0) {
            const int row0 = warp == 0 ? n0 : k0, col0 = warp == 0 ? kC : vo ? 2 * kC : 0;
            const char* src = reinterpret_cast<const char*>(wqkv) + (uint32_t)(((row0 + (lane >> 3)) * (3 * kC) + col0 + (lane & 7) * 8) * 2);
            const uint32_t dst = stage + warp * 6144 + (lane >> 3) * 384 + (((lane & 7) ^ (lane >> 3)) << 4);
#pragma unroll
            for (int i = 0; i < 12; i++) cp_async16((dst ^ (((i / 3) & 1) << 6)) + (i / 3) * 1536 + (i % 3) * 128, src + (i / 3) * 4 * 3 * kC * 2 + (i % 3) * 128);
        }
    }
    const int g = lane >> 2, q = lane & 3, mi = lane >> 3, r8 = lane & 7;
    const int row = 4 * (r8 >> 1) + (r8 & 1) + 2 * (mi >> 1), c = r8 + 8 * (mi >> 1);
    uint32_t baseB = stage + warp * 6144 + row * 384 + (((mi & 1) ^ (row & 7)) << 4);
    uint32_t baseA = stage + (vo ? ((2 * c + (mi & 1)) ^ ((c >> 2) & 1)) << 4 : (r8 + 8 * (mi & 1)) * 384 + (((mi >> 1) ^ r8) << 4));
    const int ch = n0 + g;
    const int n = vo ? 32 * (ch >> 5) + 8 * ((ch >> 1) & 3) + 2 * ((ch >> 3) & 3) + (ch & 1) : ch;
    char* img = reinterpret_cast<char*>(sc->wfold) + (vo ? kWBytes : 0);
    char* dst0 = img + fold_offset(n, k0, q);
    char* dst1 = img + fold_offset(n + (vo ? 2 : 8), k0, q);
    asm volatile("" : "+r"(baseA), "+r"(baseB), "+l"(dst0), "+l"(dst1));
    if (warp != kWarmW) {
        asm volatile("cp.async.wait_all;" ::: "memory");
        if (warp == 0) {
            asm volatile("bar.arrive 13, %0;" ::"n"(32 * nw + 32) : "memory");
            return;
        }
        asm volatile("bar.sync 13, %0;" ::"n"(32 * nw + 32) : "memory");
    }
    float c0[4] = {0.f, 0.f, 0.f, 0.f}, c1[4] = {0.f, 0.f, 0.f, 0.f}, c2[4] = {0.f, 0.f, 0.f, 0.f}, c3[4] = {0.f, 0.f, 0.f, 0.f};
    uint32_t A[12][4], B[12][4];
#pragma unroll
    for (int ks = 0; ks < 12; ks++) {
        ldsm4<vo>(A[ks], vo ? baseA + ks * 512 : (baseA ^ ((ks & 3) << 5)) + (ks >> 2) * 128);
        ldsm4<false>(B[ks], (baseB ^ ((ks & 3) << 5)) + (ks >> 2) * 128);
    }
#pragma unroll
    for (int ks = 0; ks < 12; ks += 2) {
        mma16816x2(c0, c1, A[ks], B[ks]);
        mma16816x2(c2, c3, A[ks + 1], B[ks + 1]);
    }
#pragma unroll
    for (int i = 0; i < 4; i++) { c0[i] += c2[i]; c1[i] += c3[i]; }
    asm volatile("{\n.reg .pred p;\nsetp.ne.u32 p, %6, %7;\n@p st.global.v2.u32 [%0], {%2, %3};\n@p st.global.v2.u32 [%1], {%4, %5};\n}\n"
                 ::"l"(dst0), "l"(dst1),
                   "r"(nonzero(pack_bf16(c0[0], c0[1]))), "r"(nonzero(pack_bf16(c1[0], c1[1]))), "r"(nonzero(pack_bf16(c0[2], c0[3]))), "r"(nonzero(pack_bf16(c1[2], c1[3]))),
                   "r"(warp), "n"(kWarmW) : "memory");
}
constexpr uint32_t kWarpsQK = 0x17;

__device__ __forceinline__ bool bar_or(uint32_t id, uint32_t n, bool pred) {
    uint32_t r;
    asm volatile("{\n.reg .pred p, q;\nsetp.ne.u32 q, %3, 0;\nbar.red.or.pred p, %1, %2, q;\nselp.u32 %0, 1, 0, p;\n}\n"
                 : "=r"(r) : "r"(id), "r"(n), "r"((uint32_t)pred) : "memory");
    return r != 0;
}
template <int N = 6> __device__ __forceinline__ bool chunk_incomplete(uint32_t base) {
    const uint32_t t = tid_now(), r = (t >> 2) & 7;
    const uint32_t adr = base + (((t >> 5) & 3) * 8 * N + r) * 128 + (t & 3) * 32 + r * 4;
    uint32_t m = ~0u;
#pragma unroll
    for (int j = 0; j < N; j++) {
        uint32_t v;
        asm volatile("ld.shared.u32 %0, [%1];" : "=r"(v) : "r"(adr + j * 1024) : "memory");
        m = min(m, v);
    }
    return m == 0;
}
__device__ __forceinline__ void load_image(uint32_t dst, const void* src, uint32_t bar) {
    mbar_expect_tx(bar, kWBytes);
#pragma unroll
    for (int c = 0; c < 3; c++) bulk_load(dst + c * 24576, reinterpret_cast<const char*>(src) + c * 24576, 24576, bar);
}
__device__ __forceinline__ void repair_image(uint32_t dst, const void* src, uint32_t bar, uint32_t par) {
    uint32_t tries = 0;
    bool bad;
    do {
        if (((tid_now() >> 5) & 3) == 0) {
            if (elect_one()) {
                asm volatile("fence.proxy.async;" ::: "memory");
                load_image(dst, src, bar);
            }
            __syncwarp();
        }
        mbar_wait(bar, par);
        par ^= 1;
        bad = chunk_incomplete(dst) | chunk_incomplete(dst + 24576) | chunk_incomplete(dst + 2 * 24576);
        if (++tries > (1u << 16)) __trap();
    } while (bar_or((tid_now() >> 7) + 1, 128, bad));
}
__device__ __forceinline__ void count_image(Scratch* sc) {
    asm volatile("red.relaxed.gpu.global.inc.u32 [%0], %1;" ::"l"(sc->cnt), "r"(3 * nctaid_now() - 1) : "memory");
}
__device__ __forceinline__ uint32_t ld_acquire(const uint32_t* p) {
    uint32_t v;
    asm volatile("ld.acquire.gpu.global.u32 %0, [%1];" : "=r"(v) : "l"(p) : "memory");
    return v;
}
__device__ __noinline__ void clear_images(Scratch* sc) {
    const uint32_t g = gridDim.x, t = threadIdx.x & 127;
    if (t == 0) {
        uint32_t spins = 0;
        while (ld_acquire(sc->cnt) < 2 * g) { if (++spins > (1u << 24)) __trap(); }
    }
    asm volatile("bar.sync %0, 128;" ::"r"((threadIdx.x >> 7) + 1) : "memory");
    for (uint32_t i = blockIdx.x * 64 + t; t < 64 && i < 2 * kWBytes / 16; i += g * 64) sc->wfold[i] = make_uint4(0, 0, 0, 0);
    if (t == 0) count_image(sc);
}
__device__ __forceinline__ void prefetch_x(const CUtensorMap* tm, int win) {
    const int wh = win >> 6, ww = win & 63;
    asm volatile("cp.async.bulk.prefetch.tensor.3d.L2.global.tile [%0, {%1, %2, %3}];"
                 ::"l"(tm), "r"(0), "r"(ww * 8), "r"(wh * 8) : "memory");
}
__device__ __forceinline__ void prefetch_x_chunk(const CUtensorMap* tm, int win, int chunk) {
    asm volatile("cp.async.bulk.prefetch.tensor.5d.L2.global.tile [%0, {%1, %2, %4, %4, %3}];"
                 ::"l"(tm), "r"(chunk * 64), "r"((win & 63) * 4), "r"((win >> 6) * 4), "r"(0) : "memory");
}

__device__ __forceinline__ void prefetch_for_ticket(const CUtensorMap* tmp, int t, int G) {
    const int base = kNWG * G;
    auto lead = [&](int tt) {
        int down = max(((kNWin - PF_END - base - tt) * PF_DOWN) >> 8, PF_MIN);
        return min(min(G + ((tt * PF_UP) >> 8), PF_LEAD), down);
    };
    const int hi = base + t + lead(t);
    int lo = max(base + t - 1 + lead(t - 1), base + t) + 1;
#pragma unroll 1
    for (; lo <= hi && lo < kNWin; lo++) prefetch_x(tmp, lo);
}

__device__ __forceinline__ void publish(uint32_t ticket, int G) {
    constexpr uint32_t sbase = kSmemBase;
    if (((tid_now() >> 5) & 3) == 0) {
        if ((tid_now() & 31) == 0) {
            uint32_t nxt = 2 * kNWG * G + ticket;
            if (nxt >= kNWin) {
                uint32_t p0, p1, p2, p3;
                asm volatile("ld.shared.v4.u32 {%0, %1, %2, %3}, [%4];" : "=r"(p0), "=r"(p1), "=r"(p2), "=r"(p3) : "r"(sbase + kOffBar + 64) : "memory");
                nxt = kDone + (p0 >> 30) + (p1 >> 30) + (p2 >> 30);
            }
            asm volatile("st.shared.u32 [%0], %1;" ::"r"(sbase + kOffBar + 64 + 4 * (tid_now() >> 7)), "r"(nxt) : "memory");
        }
        __syncwarp();
        asm volatile("bar.arrive %0, 128;" ::"r"((tid_now() >> 7) + 4) : "memory");
    }
}

template <bool kFewSMs>
__global__ void __launch_bounds__(kThreads, 1)
swin_attn_kernel(const __nv_bfloat16* __restrict__ wqkv, const __nv_bfloat16* __restrict__ wo, const __nv_bfloat16* __restrict__ xin, Scratch* sc, uint32_t* tickets,
                 const int G, const uint32_t trk, __nv_bfloat16* __restrict__ out, const __grid_constant__ CUtensorMap tmx, const __grid_constant__ CUtensorMap tmp, const __grid_constant__ CUtensorMap tmo) {
    extern __shared__ uint8_t smem_raw[];
    constexpr uint32_t sbase = kSmemBase;
    const uint32_t t_start = clock_now();
    asm volatile("{\n.reg .pred p, q;\n.reg .b32 i, j;\n.reg .b64 a, b;\nmad.lo.u32 i, %2, 14, %3;\nsetp.lt.u32 p, %3, 14;\nsetp.lt.and.u32 p, i, 1728, p;\n"
                 "mad.wide.u32 a, i, 128, %0;\n@p prefetch.global.L2 [a];\n"
                 "mad.lo.u32 j, %2, 5, %3;\nsetp.lt.u32 q, %3, 5;\nsetp.lt.and.u32 q, j, 576, q;\n"
                 "mad.wide.u32 b, j, 128, %1;\n@q prefetch.global.L2 [b];\n}\n" ::"l"(wqkv), "l"(wo), "r"(blockIdx.x), "r"(threadIdx.x) : "memory");
    if (smem_u32(smem_raw) != kSmemBase) __trap();
    const int tid = threadIdx.x, lane = tid & 31;
    const uint32_t warpu = __reduce_or_sync(0xffffffffu, (uint32_t)tid >> 5), wgu = warpu >> 2;
    const int warp = (int)warpu, wg = (int)wgu;
    const uint32_t bar_full = sbase + kOffBar + 8 * wg;
    constexpr uint32_t bar_m = sbase + kOffBarM, bar_w1 = sbase + kOffBar + 40;
    auto bar_v = [](int c) { return bar_w1 + 16 - 8 * c; };
    int win = wg * G + blockIdx.x;

    const int direct = blockIdx.x >= X0_LATE ? 1 : 2;
    if (!kFewSMs && blockIdx.x < kJobsM && ((kWarpsQK >> warp) & 1)) fold_job<false>(sc, wqkv, wo, blockIdx.x, warp, lane);
    if (warp == 10) {
        auto x_lines = [&](int c) {
            const int w = (c / 3) * G + blockIdx.x;
            return reinterpret_cast<const char*>(xin) + (uint32_t)((((w >> 6) * 8 + (lane >> 3)) * kHW + (w & 63) * 8 + (lane & 7)) * (kC * 2) + (c % 3) * 128);
        };
        if (elect_one()) {
            asm volatile("prefetch.tensormap [%0];" ::"l"(&tmx) : "memory");
#pragma unroll
            for (int w = 0; w < kNWG; w++) mbar_init(sbase + kOffBar + 8 * w, 1);
            mbar_init(sbase + kOffBar + 24, 1);
            mbar_init(sbase + kOffBar + 88, 1);
            mbar_init(sbase + kOffBar + 96, 1);
            mbar_init(sbase + kOffBar + 104, 1);
            mbar_init(sbase + kOffBar + 112, 1);
#pragma unroll
            for (int c = 0; c < 3; c++) mbar_init(bar_v(c), 1);
#pragma unroll
            for (int i = 0; i < 6; i++) mbar_init(bar_m + 8 * i, 1);
            asm volatile("st.shared.v4.u32 [%0], {%1, %1, %1, %1};" ::"r"(sbase + kOffBar + 64), "r"(0) : "memory");
            asm volatile("fence.mbarrier_init.release.cluster;" ::: "memory");
            asm volatile("mbarrier.arrive.shared::cta.b64 _, [%0];" ::"r"(sbase + kOffBar) : "memory");
        }
        __syncwarp();
        asm volatile("bar.arrive 15, 64;" ::: "memory");
        asm volatile("bar.arrive 0, %0;" ::"n"(kThreads) : "memory");
        const uint32_t due = (blockIdx.x * TRK_Q) >> 8;
        if (elect_one()) {
#pragma unroll
            for (int c = 0; c < 2; c++) {
                if (c >= direct) break;
                while (clock_now() - t_start < TRK_T0 + (due + c * TRK_S) / 3) {}
                tma_load_x_chunk(sbase + kOffX + c * 8192, &tmx, bar_m + 16 * c, blockIdx.x, c);
            }
        }
        __syncwarp();
#pragma unroll 1
        for (int c = direct; c < 3 * kNWG; c++) {
            const char* p = x_lines(c);
            while (clock_now() - t_start < TRK_T0 + (due + c * TRK_S) / 3) {}
            asm volatile("prefetch.global.L2 [%0];\nprefetch.global.L2 [%0 + %1];" ::"l"(p), "n"(4 * kHW * kC * 2) : "memory");
        }
        asm volatile("prefetch.tensormap [%0];" ::"l"(&tmp) : "memory");
        asm volatile("prefetch.tensormap [%0];" ::"l"(&tmo) : "memory");
    }
    int role = warp;
    asm volatile("" : "+r"(role));
    if (role == 10) {
    } else if (warp > kWarmW) {
        if (warp == 11) {
            asm volatile("bar.sync 15, 64;" ::: "memory");
            asm volatile("bar.arrive 0, %0;" ::"n"(kThreads) : "memory");
            if (elect_one()) {
                const char* img = reinterpret_cast<const char*>(sc->wfold);
#pragma unroll
                for (int i = 0; i < 6; i++) mbar_expect_tx(bar_m + 8 * i, 12288 + (i & 1 ? 0 : 8192));
#pragma unroll
                for (int c = 0; c < 3; c++) mbar_expect_tx(sbase + kOffBar + (c == 0 ? 8 : 80 + 8 * c), 8192);
                while (clock_now() - t_start < REQ_T) {}
#pragma unroll
                for (int i = 0; i < 6; i++) {
                    if (i >= 2 * direct && !(i & 1)) tma_load_x_chunk(sbase + kOffX + (i >> 1) * 8192, &tmx, bar_m + 8 * i, blockIdx.x, i >> 1);
                    bulk_load(sbase + kOffWm + i * 12288, img + i * 12288, 12288, bar_m + 8 * i);
                }
                mbar_wait(bar_m + 8, 0);
#pragma unroll
                for (int c = 0; c < 3; c++)
                    tma_load_x_chunk(sbase + kOffX + kXBytes + c * 8192, &tmx, sbase + kOffBar + (c == 0 ? 8 : 80 + 8 * c), G + blockIdx.x, c);
            }
            __syncwarp();
        } else {
            asm volatile("bar.sync 0, %0;" ::"n"(kThreads) : "memory");
            if (warp == 9) {
                if (elect_one()) {
                    while (clock_now() - t_start < REQ_TV) {}
                    mbar_wait(bar_m + 24, 0);
                    asm volatile("fence.proxy.async.shared::cta;" ::: "memory");
#pragma unroll
                    for (int c = 0; c < 3; c++) {
                        mbar_expect_tx(bar_v(c), 24576);
                        bulk_load(sbase + kOffWv + c * 24576, reinterpret_cast<const char*>(sc->wfold) + kWBytes + c * 24576, 24576, bar_v(c));
                    }
#pragma unroll
                    for (int c = 0; c < 3; c++) {
                        const uint32_t bar = sbase + kOffBar + (c == 0 ? 16 : 96 + 8 * c);
                        mbar_expect_tx(bar, 8192);
                        tma_load_x_chunk(sbase + kOffX + 2 * kXBytes + c * 8192, &tmx, bar, 2 * G + blockIdx.x, c);
                    }
                }
                __syncwarp();
            }
        }
    } else {
        if constexpr (kFewSMs) {
#pragma unroll 1
            for (int j = blockIdx.x; j < kJobs; j += G) {
                if (j >= kJobsM) fold_job<true>(sc, wqkv, wo, j - kJobsM, warp, lane);
                else if ((kWarpsQK >> warp) & 1) fold_job<false>(sc, wqkv, wo, j, warp, lane);
                asm volatile("bar.sync 14, %0;" ::"n"(32 * kWarmW + 32) : "memory");
            }
        } else {
            if (blockIdx.x - kJobsM < kJobs - kJobsM) fold_job<true>(sc, wqkv, wo, blockIdx.x - kJobsM, warp, lane);
        }
        asm volatile("bar.sync 0, %0;" ::"n"(kThreads) : "memory");
    }
    if (wg == 1) {
        mbar_wait(bar_m + 8 * (warp & 3), 0);
        bool bad = chunk_incomplete<12>(sbase + kOffWm);
#pragma unroll
        for (int i = 4; i < 6; i++) {
            mbar_wait(bar_m + 8 * i, 0);
            bad |= chunk_incomplete<3>(sbase + kOffWm + i * 12288);
        }
        bad = bar_or(2, 128, bad);
        if (bad) {
            repair_image(sbase + kOffWm, sc->wfold, sbase + kOffBar + 24, 0);
        }
        asm volatile("st.shared.u32 [%0], %1;" ::"r"(sbase + kOffBar + 80), "r"((uint32_t)bad) : "memory");
        asm volatile("bar.arrive 11, 256;" ::: "memory");
    } else if (wg == 2) {
        bool bad = false;
#pragma unroll
        for (int c = 0; c < 3; c++) {
            mbar_wait(bar_v(c), 0);
            bad |= chunk_incomplete(sbase + kOffWv + c * 24576);
        }
        if (bar_or(3, 128, bad)) {
            repair_image(sbase + kOffWv, reinterpret_cast<const char*>(sc->wfold) + kWBytes, bar_w1, 1);
        }
    }

    constexpr uint32_t dWm = ((sbase + kOffWm) >> 4) | (1u << 16);
    constexpr uint32_t dWv = ((sbase + kOffWv) >> 4) | (1u << 16);
    const float cs = 0.07216878364870322f * 1.4426950408889634f;
    mbar_wait(wg == 0 ? bar_m : bar_full, 0);

    uint4 hv[12];
    uint32_t pos;
    float acc[96];
    uint32_t ticket = win - kNWG * G;
    float s[32];
    {
        const uint32_t dX = desc_x(wg_uniform());
        uint32_t fa[48];
        if (wg == 0) {
            float ta[48], tb[48];
            wg_fence();
            Gemm1h<0, 0>::run(ta, dX, dWm);
            mbar_wait(bar_m + 8, 0);
            wg_fence();
            Gemm1h<1, 0>::run(tb, dX, dWm);
            mbar_wait(bar_m + 16, 0);
            wg_fence();
            Gemm1h<0, 1>::run(ta, dX, dWm);
            mbar_wait(bar_m + 24, 0);
            wg_fence();
            Gemm1h<1, 1>::run(tb, dX, dWm);
            mbar_wait(bar_m + 32, 0);
            wg_fence();
            Gemm1h<0, 2>::run(ta, dX, dWm);
            wg_commit();
            mbar_wait(bar_m + 40, 0);
            wg_fence();
            Gemm1h<1, 2>::run(tb, dX, dWm);
            wg_commit();
            wg_wait1();
            fence_regs(ta);
#pragma unroll
            for (int i = 0; i < 24; i++) fa[i] = pack_bf16(ta[2 * i], ta[2 * i + 1]);
#pragma unroll
            for (int i = 0; i < 24; i++) asm volatile("" : "+r"(fa[i])::"memory");
            wg_fence();
            Gemm2p<0, 5>::run(s, fa, dX);
            wg_commit();
            wg_wait1();
            fence_regs(tb);
#pragma unroll
            for (int i = 0; i < 24; i++) fa[24 + i] = pack_bf16(tb[2 * i], tb[2 * i + 1]);
#pragma unroll
            for (int i = 24; i < 48; i++) asm volatile("" : "+r"(fa[i])::"memory");
            wg_fence();
            Gemm2p<6, 11>::run(s, fa, dX);
            wg_commit();
            ring_pass();
            asm volatile("bar.sync 11, 256;" ::: "memory");
            uint32_t redo;
            asm volatile("ld.shared.u32 %0, [%1];" : "=r"(redo) : "r"(sbase + kOffBar + 80) : "memory");
            publish(ticket, G);
            asm volatile("bar.arrive 15, 256;" ::: "memory");
            redo = __reduce_or_sync(0xffffffffu, redo);
            wg_wait0();
            fence_regs(s);
            fence_regs(fa);
            if (redo) {
                wg_fence();
                Gemm1<0, 11>::run(acc, dX, dWm);
                wg_commit();
                wg_wait0();
                fence_regs(acc);
#pragma unroll
                for (int i = 0; i < 48; i++) fa[i] = pack_bf16(acc[2 * i], acc[2 * i + 1]);
                fence_regs(fa);
                wg_fence();
                Gemm2p<0, 11>::run(s, fa, dX);
                wg_commit();
                wg_wait0();
                fence_regs(s);
                fence_regs(fa);
            }
        } else {
            ring_wait();
            wg_fence();
            Gemm1<0, 3>::run(acc, dX, dWm);
            const uint32_t bar_c1 = sbase + kOffBar + 72 + 16 * wg;
            mbar_wait(bar_c1, 0);
            wg_fence();
            Gemm1<4, 7>::run(acc, dX, dWm);
            mbar_wait(bar_c1 + 8, 0);
            wg_fence();
            Gemm1<8, 11>::run(acc, dX, dWm);
            wg_commit();
            asm volatile("bar.arrive 8, 256;" ::: "memory");
            if (warp == 5) {
                if (elect_one()) prefetch_x(&tmp, kNWG * G + blockIdx.x);
                __syncwarp();
            }
            if ((tid & 127) == 0) count_image(sc);
            wg_wait0();
            fence_regs(acc);
#pragma unroll
            for (int i = 0; i < 48; i++) fa[i] = pack_bf16(acc[2 * i], acc[2 * i + 1]);
            fence_regs(fa);
            wg_fence();
            ring_wait();
            Gemm2<11>::run(s, fa, dX);
            wg_commit();
            publish(ticket, G);
            asm volatile("bar.arrive 15, 256;" ::: "memory");
            wg_wait0();
            fence_regs(s);
            fence_regs(fa);
        }
        __syncwarp();
    }

    while (true) {
        uint32_t fa[48];
        uint32_t pa[16];
        {
            float a0[8], a1[8];
#pragma unroll
            for (int j = 0; j < 8; j++) { a0[j] = fmaxf(s[4 * j], s[4 * j + 1]); a1[j] = fmaxf(s[4 * j + 2], s[4 * j + 3]); }
#pragma unroll
            for (int d = 4; d > 0; d >>= 1)
#pragma unroll
                for (int j = 0; j < d; j++) { a0[j] = fmaxf(a0[j], a0[j + d]); a1[j] = fmaxf(a1[j], a1[j + d]); }
            float m0 = a0[0], m1 = a1[0];
            m0 = fmaxf(m0, __shfl_xor_sync(0xffffffffu, m0, 1));
            m1 = fmaxf(m1, __shfl_xor_sync(0xffffffffu, m1, 1));
            m0 = fmaxf(m0, __shfl_xor_sync(0xffffffffu, m0, 2));
            m1 = fmaxf(m1, __shfl_xor_sync(0xffffffffu, m1, 2));
            m0 *= cs; m1 *= cs;
            float l0 = 0.f, l1 = 0.f;
#pragma unroll
            for (int j = 0; j < 8; j++) {
                s[4 * j]     = ex2(fmaf(s[4 * j], cs, -m0));
                s[4 * j + 1] = ex2(fmaf(s[4 * j + 1], cs, -m0));
                s[4 * j + 2] = ex2(fmaf(s[4 * j + 2], cs, -m1));
                s[4 * j + 3] = ex2(fmaf(s[4 * j + 3], cs, -m1));
                l0 += s[4 * j] + s[4 * j + 1];
                l1 += s[4 * j + 2] + s[4 * j + 3];
            }
            l0 += __shfl_xor_sync(0xffffffffu, l0, 1);
            l1 += __shfl_xor_sync(0xffffffffu, l1, 1);
            l0 += __shfl_xor_sync(0xffffffffu, l0, 2);
            l1 += __shfl_xor_sync(0xffffffffu, l1, 2);
            const float r0 = rcp(l0), r1 = rcp(l1);
#pragma unroll
            for (int j = 0; j < 8; j++) {
                pa[2 * j]     = pack_bf16(s[4 * j] * r0, s[4 * j + 1] * r0);
                pa[2 * j + 1] = pack_bf16(s[4 * j + 2] * r1, s[4 * j + 3] * r1);
            }
        }

        const uint32_t wu = __reduce_or_sync(0xffffffffu, tid_now() >> 5);
        const uint32_t dXt = desc_xt(wu >> 2);
        if ((wu & 3) != 0) asm volatile("bar.sync %0, 128;" ::"r"((wu >> 2) + 4) : "memory");
        uint32_t pub;
        asm volatile("ld.shared.u32 %0, [%1];" : "=r"(pub) : "r"(sbase + kOffBar + 64 + 4 * (tid_now() >> 7)) : "memory");
        const int nxt = (int)__reduce_or_sync(0xffffffffu, pub);
        store_p_if(pa, nxt == (int)kDone + kNWG - 1);
        if (nxt == (int)kDone + kNWG - 1) {
            last_window(out, win);
            asm volatile("exit;");
            __builtin_unreachable();
        }
        fence_regs(pa);
        wg_fence();
        ring_wait();
        Gemm3<3>::run(acc, pa, dXt);
        wg_commit();
        if constexpr (PASS3 == 3) ring_pass();
        wg_wait0();
        fence_regs(acc);
        fence_regs(pa);

        if (((tid_now() >> 5) & 3) == 0) {
            asm volatile("bar.sync %0, 128;" ::"r"((tid_now() >> 7) + 1) : "memory");
            if (elect_one()) {
                const uint32_t wgl = tid_now() >> 7;
                const uint32_t bar = sbase + kOffBar + 8 * wgl;
                if (nxt < kNWin) {
                    mbar_expect_tx(bar, kXBytes);
                    tma_load_x_hint(sbase + kOffX + wgl * kXBytes, &tmx, bar, nxt & 4095, nxt >= kNWin - EF_LAST);
                    uint32_t again;
                    asm volatile("ld.volatile.shared.u32 %0, [%1];" : "=r"(again) : "r"(sbase + kOffBar + 64 + 4 * wgl) : "memory");
                    prefetch_for_ticket(&tmp, (int)again - kNWG * G, G);
                }
            }
            __syncwarp();
        } else {
            asm volatile("bar.arrive %0, 128;" ::"r"((tid_now() >> 7) + 1) : "memory");
        }
#pragma unroll
        for (int i = 0; i < 48; i++) fa[i] = pack_bf16(acc[2 * i], acc[2 * i + 1]);

        asm volatile("{\n.reg .pred p;\nsetp.lt.s32 p, %5, 0;\n@p st.volatile.shared.v4.b32 [%4], {%0, %1, %2, %3};\n}\n"
                     :: "r"(fa[44]), "r"(fa[45]), "r"(fa[46]), "r"(fa[47]), "r"(sbase + kOffBar + 64), "r"(nxt) : "memory");
        fence_regs(fa);
        wg_fence();
        ring_wait();
        Gemm4<0, 1>::run(acc, fa, dWv);
        wg_commit();
        Gemm4<2, 10>::run(acc, fa, dWv);
        wg_commit();
        wg_wait1();
        uint32_t fl[4];
        uint32_t zero;
        asm volatile("ld.volatile.shared.u32 %0, [%1];" : "=r"(zero) : "r"(sbase + kOffBar + 76) : "memory");
#pragma unroll
        for (int i = 0; i < 4; i++) fl[i] = fa[44 + i] ^ zero;
        if constexpr (PASS4 == 10) ring_pass();
        wg_fence();
        wg192_rs<false, 0, koff(11, 24576)>(acc, fl, dWv);
        wg_commit();
        if constexpr (PASS4 == 11) ring_pass();
        pos = out_pos(win ^ zero);
        win = nxt | (~win & kPhase);
        const uint32_t dX = desc_x(__reduce_or_sync(0xffffffffu, (tid_now() >> 7) ^ zero));
        asm volatile("" : "+r"(pos) :: "memory");
        wg_wait0();
        fence_regs(acc);
        fence_regs(fa);
        fence_regs(fl);

#pragma unroll
        for (int a = 0; a < 6; a++) {
            hv[2 * a].x     = pack_bf16(acc[16 * a + 0], acc[16 * a + 1]);
            hv[2 * a].y     = pack_bf16(acc[16 * a + 4], acc[16 * a + 5]);
            hv[2 * a].z     = pack_bf16(acc[16 * a + 8], acc[16 * a + 9]);
            hv[2 * a].w     = pack_bf16(acc[16 * a + 12], acc[16 * a + 13]);
            hv[2 * a + 1].x = pack_bf16(acc[16 * a + 2], acc[16 * a + 3]);
            hv[2 * a + 1].y = pack_bf16(acc[16 * a + 6], acc[16 * a + 7]);
            hv[2 * a + 1].z = pack_bf16(acc[16 * a + 10], acc[16 * a + 11]);
            hv[2 * a + 1].w = pack_bf16(acc[16 * a + 14], acc[16 * a + 15]);
        }
        if (win < (int)kDone) mbar_wait(sbase + kOffBar + 8 * (tid_now() >> 7), (win >> 16) & 1);
        if (win >= (int)kDone) break;
        wg_fence();
        ring_wait();
        Gemm1<0, PASS1>::run(acc, dX, dWm);
        if constexpr (PASS1 < 11) {
            ring_pass();
            Gemm1<PASS1 + 1, 11>::run(acc, dX, dWm);
        }
        wg_commit();
        if constexpr (PASS1 == 11) ring_pass();
        ticket = draw_ticket(tickets, G);
        asm volatile("bar.sync 15, 256;" ::: "memory");
        stage_window<0>(hv, &tmo, pos, win);
        wg_wait0();
        fence_regs(acc);
#pragma unroll
        for (int i = 0; i < 48; i++) fa[i] = pack_bf16(acc[2 * i], acc[2 * i + 1]);

        fence_regs(fa);
        wg_fence();
        ring_wait();
        Gemm2<11>::run(s, fa, dX);
        wg_commit();
        if constexpr (PASS2 == 11) ring_pass();
        publish(ticket, G);
        asm volatile("cp.async.bulk.wait_group.read 0;" ::: "memory");
        asm volatile("bar.arrive 15, 256;" ::: "memory");
        wg_wait0();
        fence_regs(s);
        fence_regs(fa);
    }
    if ((win & 3) == 0) {
        const uint32_t buf = sbase + kOffX + (tid_now() >> 7) * kXBytes + ((tid_now() >> 5) & 3) * 2048;
        asm volatile("bar.sync %0, 128;" ::"r"((tid_now() >> 7) + 1) : "memory");
        ring_wait();
        ring_pass();
        stage_put<0>(hv, buf);
        stage_send(&tmo, pos, 0, buf);
        stage_put<1>(hv, buf + 8192);
        stage_send(&tmo, pos, 1, buf + 8192);
        stage_put<2>(hv, buf + 2 * 8192);
        stage_send(&tmo, pos, 2, buf + 2 * 8192);
        clear_images(sc);
        asm volatile("bar.sync 15, 256;" ::: "memory");
        stage_wait();
    } else {
        uint8_t* hptr = out_address(out, pos);
        store_tail<0>(hv, hptr, clock_now());
    }
}

typedef CUresult (*EncodeTiledFn)(CUtensorMap*, CUtensorMapDataType, cuuint32_t, void*, const cuuint64_t*,
                                  const cuuint64_t*, const cuuint32_t*, const cuuint32_t*, CUtensorMapInterleave,
                                  CUtensorMapSwizzle, CUtensorMapL2promotion, CUtensorMapFloatOOBfill);

}

extern "C" void kernel_launch(void* const* d_in, const int* in_sizes, int n_in, void* d_out, int out_size) {
    (void)in_sizes; (void)n_in; (void)out_size;
    const __nv_bfloat16* x    = (const __nv_bfloat16*)d_in[0];
    const __nv_bfloat16* wqkv = (const __nv_bfloat16*)d_in[1];
    const __nv_bfloat16* wo   = (const __nv_bfloat16*)d_in[2];

    static EncodeTiledFn encode = nullptr;
    static int num_sms = 0;
    static void* scratch = nullptr;
    if (!encode) {
        void* fn = nullptr;
        cudaDriverEntryPointQueryResult qr;
        cudaGetDriverEntryPoint("cuTensorMapEncodeTiled", &fn, cudaEnableDefault, &qr);
        encode = (EncodeTiledFn)fn;
        int dev = 0;
        cudaGetDevice(&dev);
        cudaDeviceGetAttribute(&num_sms, cudaDevAttrMultiProcessorCount, dev);
        if (num_sms > kNWin / 16) num_sms = kNWin / 16;
        cudaGetSymbolAddress(&scratch, g_scratch);
        cudaFuncSetAttribute(swin_attn_kernel<false>, cudaFuncAttributeMaxDynamicSharedMemorySize, kSmemBytes);
        cudaFuncSetAttribute(swin_attn_kernel<true>, cudaFuncAttributeMaxDynamicSharedMemorySize, kSmemBytes);
    }
    CUtensorMap tmx;
    const cuuint64_t gdim[5] = {(cuuint64_t)kC, (cuuint64_t)kHW / 2, 2, 2, (cuuint64_t)kHW / 2};
    const cuuint64_t gstr[4] = {(cuuint64_t)kC * 4, (cuuint64_t)kHW * kC * 2, (cuuint64_t)kC * 2, (cuuint64_t)kHW * kC * 4};
    const cuuint32_t box[5] = {64, 4, 2, 2, 4};
    const cuuint32_t estr[5] = {1, 1, 1, 1, 1};
    encode(&tmx, CU_TENSOR_MAP_DATA_TYPE_BFLOAT16, 5, (void*)x, gdim, gstr, box, estr, CU_TENSOR_MAP_INTERLEAVE_NONE,
           CU_TENSOR_MAP_SWIZZLE_128B, CU_TENSOR_MAP_L2_PROMOTION_NONE, CU_TENSOR_MAP_FLOAT_OOB_FILL_NONE);

    CUtensorMap tmp;
    const cuuint64_t pdim[3] = {(cuuint64_t)kC, (cuuint64_t)kHW, (cuuint64_t)kHW};
    const cuuint64_t pstr[2] = {(cuuint64_t)kC * 2, (cuuint64_t)kHW * kC * 2};
    const cuuint32_t pbox[3] = {(cuuint32_t)kC, 8, 8};
    encode(&tmp, CU_TENSOR_MAP_DATA_TYPE_BFLOAT16, 3, (void*)x, pdim, pstr, pbox, estr, CU_TENSOR_MAP_INTERLEAVE_NONE,
           CU_TENSOR_MAP_SWIZZLE_NONE, CU_TENSOR_MAP_L2_PROMOTION_NONE, CU_TENSOR_MAP_FLOAT_OOB_FILL_NONE);
    CUtensorMap tmo;
    const cuuint64_t odim[5] = {64, 6, (cuuint64_t)kHW / 4, 2, (cuuint64_t)kHW};
    const cuuint64_t ostr[4] = {128, (cuuint64_t)kC * 8, (cuuint64_t)kC * 4, (cuuint64_t)kHW * kC * 2};
    const cuuint32_t obox[5] = {64, 2, 2, 2, 2};
    encode(&tmo, CU_TENSOR_MAP_DATA_TYPE_BFLOAT16, 5, d_out, odim, ostr, obox, estr, CU_TENSOR_MAP_INTERLEAVE_NONE,
           CU_TENSOR_MAP_SWIZZLE_128B, CU_TENSOR_MAP_L2_PROMOTION_NONE, CU_TENSOR_MAP_FLOAT_OOB_FILL_NONE);
    if (num_sms >= kJobs)
        swin_attn_kernel<false><<<num_sms, kThreads, kSmemBytes, cudaStreamPerThread>>>(wqkv, wo, x, (Scratch*)scratch, ((Scratch*)scratch)->ticket, num_sms, TRK_HOST, (__nv_bfloat16*)d_out, tmx, tmp, tmo);
    else
        swin_attn_kernel<true><<<num_sms, kThreads, kSmemBytes, cudaStreamPerThread>>>(wqkv, wo, x, (Scratch*)scratch, ((Scratch*)scratch)->ticket, num_sms, TRK_HOST, (__nv_bfloat16*)d_out, tmx, tmp, tmo);
}
```

```cpp
#include <cuda_runtime.h>
#include <cuda_bf16.h>
#include <cuda.h>
#include <stdint.h>

namespace {

constexpr int kC      = 192;
constexpr int kHW     = 512;
#define MAXWIN 4096
constexpr int kNWin   = MAXWIN;
constexpr int kXBytes = 64 * kC * 2;
constexpr int kWBytes = kC * kC * 2;
constexpr int kNWG    = 3;
constexpr int kThreads = kNWG * 128;
constexpr int kJobsM  = 72;
constexpr int kJobs   = 120;
constexpr int kWarmW  = 4;
#define PF_LEAD 400
#define PF_UP 114
#define PF_DOWN 39
#define PF_END 300
#define PF_MIN 135
#define EF_LAST 1000
#define TRK_T0 500
#define TRK_S 1700
#define TRK_HOST (TRK_S * 256 / num_sms)
#define TRK_Q trk
#define X0_LATE 72
#define REQ_T 2360
#define REQ_TV 4000

constexpr int kOffWm  = 0;
constexpr int kOffWv  = kWBytes;
constexpr int kOffX   = 2 * kWBytes;
constexpr int kOffStage = kOffX + kNWG * kXBytes;
constexpr int kOffBar = kOffStage + 8192;
constexpr int kOffBarM = kOffBar + 128;
constexpr int kOffProf = kOffBar + 192;
constexpr int kSmemBytes = kOffProf;
constexpr uint32_t kSmemBase = 1024;

struct Scratch {
    uint4 wfold[2 * kWBytes / 16];
    uint32_t ticket[32];
    uint32_t cnt[32];
};
__device__ __align__(128) Scratch g_scratch;

__device__ __forceinline__ uint32_t smem_u32(const void* p) { return (uint32_t)__cvta_generic_to_shared(p); }

__device__ __forceinline__ void mbar_init(uint32_t bar, uint32_t count) {
    asm volatile("mbarrier.init.shared::cta.b64 [%0], %1;" ::"r"(bar), "r"(count) : "memory");
}
__device__ __forceinline__ void mbar_expect_tx(uint32_t bar, uint32_t bytes) {
    asm volatile("mbarrier.arrive.expect_tx.shared::cta.b64 _, [%0], %1;" ::"r"(bar), "r"(bytes) : "memory");
}
__device__ __forceinline__ void mbar_wait(uint32_t bar, uint32_t parity) {
    uint32_t ok;
    uint32_t spins = 0;
    do {
        asm volatile("{\n.reg .pred p;\n"
                     "mbarrier.try_wait.parity.shared::cta.b64 p, [%1], %2;\n"
                     "selp.b32 %0, 1, 0, p;\n}\n"
                     : "=r"(ok) : "r"(bar), "r"(parity) : "memory");
        if (++spins > (1u << 26)) __trap();
    } while (!ok);
}
__device__ __forceinline__ uint32_t tid_now() {
    uint32_t t;
    asm volatile("mov.u32 %0, %%tid.x;" : "=r"(t));
    return t;
}
__device__ __forceinline__ uint32_t nctaid_now() {
    uint32_t t;
    asm volatile("mov.u32 %0, %%nctaid.x;" : "=r"(t));
    return t;
}
__device__ __forceinline__ bool elect_one() {
    uint32_t pred;
    asm volatile("{\n.reg .pred p;\nelect.sync _|p, 0xffffffff;\nselp.b32 %0, 1, 0, p;\n}\n" : "=r"(pred));
    return pred != 0;
}
#define PASS1 10
#define PASS4 11
#define PASS2 7
#define PASS3 3
__device__ __forceinline__ void ring_wait() {
    asm volatile("bar.sync %0, 256;" ::"r"((tid_now() >> 7) + 8) : "memory");
}
__device__ __forceinline__ void ring_pass() {
    const uint32_t w = tid_now() >> 7;
    asm volatile("bar.arrive %0, 256;" ::"r"(w == kNWG - 1 ? 8u : w + 9u) : "memory");
}
constexpr uint32_t kDone = 0x40000000u;
constexpr int kPhase = 0x10000;
#define SHARED 16
constexpr int kHelp = 0x1000;
__device__ __forceinline__ uint32_t wg_uniform() { return __reduce_or_sync(0xffffffffu, tid_now() >> 7); }
__device__ __forceinline__ uint32_t desc_x(uint32_t w) { return (((kSmemBase + kOffX) >> 4) | (1u << 16)) + w * (kXBytes >> 4); }
__device__ __forceinline__ uint32_t desc_xt(uint32_t w) { return (((kSmemBase + kOffX) >> 4) | ((8192u >> 4) << 16)) + w * (kXBytes >> 4); }
__device__ __forceinline__ void tma_load_x_chunk(uint32_t dst, const CUtensorMap* tm, uint32_t bar, int win, int chunk) {
    asm volatile("cp.async.bulk.tensor.5d.shared::cluster.global.mbarrier::complete_tx::bytes"
                 " [%0], [%1, {%3, %4, %6, %6, %5}], [%2];"
                 ::"r"(dst), "l"(tm), "r"(bar), "r"(chunk * 64), "r"((win & 63) * 4), "r"((win >> 6) * 4), "r"(0) : "memory");
}
__device__ __forceinline__ void tma_load_x_hint(uint32_t dst, const CUtensorMap* tm, uint32_t bar, int win, bool evict_first) {
    uint64_t first, normal;
    asm("createpolicy.fractional.L2::evict_first.b64 %0, 1.0;" : "=l"(first));
    asm("createpolicy.fractional.L2::evict_normal.b64 %0, 1.0;" : "=l"(normal));
#pragma unroll
    for (int c = 0; c < 3; c++)
        asm volatile("cp.async.bulk.tensor.5d.shared::cluster.global.mbarrier::complete_tx::bytes.L2::cache_hint"
                     " [%0], [%1, {%3, %4, %6, %6, %5}], [%2], %7;"
                     ::"r"(dst + c * 8192), "l"(tm), "r"(bar), "r"(c * 64), "r"((win & 63) * 4), "r"((win >> 6) * 4), "r"(0),
                       "l"(evict_first ? first : normal) : "memory");
}
__device__ __forceinline__ void bulk_load(uint32_t dst, const void* src, uint32_t bytes, uint32_t bar) {
    asm volatile("cp.async.bulk.shared::cluster.global.mbarrier::complete_tx::bytes [%0], [%1], %2, [%3];"
                 ::"r"(dst), "l"(src), "r"(bytes), "r"(bar) : "memory");
}

__device__ __forceinline__ void wg_fence()  { asm volatile("wgmma.fence.sync.aligned;" ::: "memory"); }
__device__ __forceinline__ void wg_commit() { asm volatile("wgmma.commit_group.sync.aligned;" ::: "memory"); }
__device__ __forceinline__ void wg_wait0()  { asm volatile("wgmma.wait_group.sync.aligned 0;" ::: "memory"); }
__device__ __forceinline__ void wg_wait1()  { asm volatile("wgmma.wait_group.sync.aligned 1;" ::: "memory"); }
__device__ __forceinline__ void wg_wait2()  { asm volatile("wgmma.wait_group.sync.aligned 2;" ::: "memory"); }

template <int N> __device__ __forceinline__ void fence_regs(float (&d)[N]) {
#pragma unroll
    for (int i = 0; i < N; i++) asm volatile("" : "+f"(d[i])::"memory");
}
template <int N> __device__ __forceinline__ void fence_regs(uint32_t (&d)[N]) {
#pragma unroll
    for (int i = 0; i < N; i++) asm volatile("" : "+r"(d[i])::"memory");
}

#define ACC8(c, d, i) c(d[i]), c(d[i + 1]), c(d[i + 2]), c(d[i + 3]), c(d[i + 4]), c(d[i + 5]), c(d[i + 6]), c(d[i + 7])
#define ACC32(c, d) ACC8(c, d, 0), ACC8(c, d, 8), ACC8(c, d, 16), ACC8(c, d, 24)
#define ACC96(c, d) ACC32(c, d), ACC8(c, d, 32), ACC8(c, d, 40), ACC8(c, d, 48), ACC8(c, d, 56), \
                    ACC8(c, d, 64), ACC8(c, d, 72), ACC8(c, d, 80), ACC8(c, d, 88)
#define C_IO(x) "+f"(x)
#define C_O(x) "=f"(x)
#define REGS32 "{%0, %1, %2, %3, %4, %5, %6, %7, %8, %9, %10, %11, %12, %13, %14, %15, " \
               "%16, %17, %18, %19, %20, %21, %22, %23, %24, %25, %26, %27, %28, %29, %30, %31}"
#define REGS96 "{%0, %1, %2, %3, %4, %5, %6, %7, %8, %9, %10, %11, %12, %13, %14, %15, " \
               "%16, %17, %18, %19, %20, %21, %22, %23, %24, %25, %26, %27, %28, %29, %30, %31, " \
               "%32, %33, %34, %35, %36, %37, %38, %39, %40, %41, %42, %43, %44, %45, %46, %47, " \
               "%48, %49, %50, %51, %52, %53, %54, %55, %56, %57, %58, %59, %60, %61, %62, %63, " \
               "%64, %65, %66, %67, %68, %69, %70, %71, %72, %73, %74, %75, %76, %77, %78, %79, " \
               "%80, %81, %82, %83, %84, %85, %86, %87, %88, %89, %90, %91, %92, %93, %94, %95}"

#define DESC_HI "0x40000040"
#define MK_DESC(name, lo, off) "add.u32 t, " lo ", " off ";\nmov.b64 " name ", {t, " DESC_HI "};\n"

template <bool First, int OA, int OB> __device__ __forceinline__ void wg192_ss(float (&d)[96], uint32_t la, uint32_t lb) {
    if constexpr (First)
        asm volatile("{\n.reg .pred p;\n.reg .b32 t;\n.reg .b64 da, db;\nsetp.ne.b32 p, 0, 0;\n"
                     MK_DESC("da", "%96", "%98") MK_DESC("db", "%97", "%99")
                     "wgmma.mma_async.sync.aligned.m64n192k16.f32.bf16.bf16 " REGS96 ", da, db, p, 1, 1, 0, 0;\n}\n"
                     : ACC96(C_O, d) : "r"(la), "r"(lb), "n"(OA), "n"(OB));
    else
        asm volatile("{\n.reg .pred p;\n.reg .b32 t;\n.reg .b64 da, db;\nsetp.ne.b32 p, 1, 0;\n"
                     MK_DESC("da", "%96", "%98") MK_DESC("db", "%97", "%99")
                     "wgmma.mma_async.sync.aligned.m64n192k16.f32.bf16.bf16 " REGS96 ", da, db, p, 1, 1, 0, 0;\n}\n"
                     : ACC96(C_IO, d) : "r"(la), "r"(lb), "n"(OA), "n"(OB));
}
#define ACC48(c, d, o) ACC8(c, d, o), ACC8(c, d, o + 8), ACC8(c, d, o + 16), ACC8(c, d, o + 24), ACC8(c, d, o + 32), ACC8(c, d, o + 40)
#define REGS48 "{%0, %1, %2, %3, %4, %5, %6, %7, %8, %9, %10, %11, %12, %13, %14, %15, %16, %17, %18, %19, %20, %21, %22, %23, " \
               "%24, %25, %26, %27, %28, %29, %30, %31, %32, %33, %34, %35, %36, %37, %38, %39, %40, %41, %42, %43, %44, %45, %46, %47}"
template <bool First, int OA, int OB> __device__ __forceinline__ void wg96_ss(float (&d)[48], uint32_t la, uint32_t lb) {
    if constexpr (First)
        asm volatile("{\n.reg .pred p;\n.reg .b32 t;\n.reg .b64 da, db;\nsetp.ne.b32 p, 0, 0;\n"
                     MK_DESC("da", "%48", "%50") MK_DESC("db", "%49", "%51")
                     "wgmma.mma_async.sync.aligned.m64n96k16.f32.bf16.bf16 " REGS48 ", da, db, p, 1, 1, 0, 0;\n}\n"
                     : ACC48(C_O, d, 0) : "r"(la), "r"(lb), "n"(OA), "n"(OB));
    else
        asm volatile("{\n.reg .pred p;\n.reg .b32 t;\n.reg .b64 da, db;\nsetp.ne.b32 p, 1, 0;\n"
                     MK_DESC("da", "%48", "%50") MK_DESC("db", "%49", "%51")
                     "wgmma.mma_async.sync.aligned.m64n96k16.f32.bf16.bf16 " REGS48 ", da, db, p, 1, 1, 0, 0;\n}\n"
                     : ACC48(C_IO, d, 0) : "r"(la), "r"(lb), "n"(OA), "n"(OB));
}
template <bool First, int TB, int OB> __device__ __forceinline__ void wg192_rs(float (&d)[96], const uint32_t* a, uint32_t lb) {
    if constexpr (First)
        asm volatile("{\n.reg .pred p;\n.reg .b32 t;\n.reg .b64 db;\nsetp.ne.b32 p, 0, 0;\n"
                     MK_DESC("db", "%100", "%102")
                     "wgmma.mma_async.sync.aligned.m64n192k16.f32.bf16.bf16 " REGS96 ", {%96, %97, %98, %99}, db, p, 1, 1, %101;\n}\n"
                     : ACC96(C_O, d) : "r"(a[0]), "r"(a[1]), "r"(a[2]), "r"(a[3]), "r"(lb), "n"(TB), "n"(OB));
    else
        asm volatile("{\n.reg .pred p;\n.reg .b32 t;\n.reg .b64 db;\nsetp.ne.b32 p, 1, 0;\n"
                     MK_DESC("db", "%100", "%102")
                     "wgmma.mma_async.sync.aligned.m64n192k16.f32.bf16.bf16 " REGS96 ", {%96, %97, %98, %99}, db, p, 1, 1, %101;\n}\n"
                     : ACC96(C_IO, d) : "r"(a[0]), "r"(a[1]), "r"(a[2]), "r"(a[3]), "r"(lb), "n"(TB), "n"(OB));
}
template <bool First, int OB> __device__ __forceinline__ void wg64_rs(float (&d)[32], const uint32_t* a, uint32_t lb) {
    if constexpr (First)
        asm volatile("{\n.reg .pred p;\n.reg .b32 t;\n.reg .b64 db;\nsetp.ne.b32 p, 0, 0;\n"
                     MK_DESC("db", "%36", "%37")
                     "wgmma.mma_async.sync.aligned.m64n64k16.f32.bf16.bf16 " REGS32 ", {%32, %33, %34, %35}, db, p, 1, 1, 0;\n}\n"
                     : ACC32(C_O, d) : "r"(a[0]), "r"(a[1]), "r"(a[2]), "r"(a[3]), "r"(lb), "n"(OB));
    else
        asm volatile("{\n.reg .pred p;\n.reg .b32 t;\n.reg .b64 db;\nsetp.ne.b32 p, 1, 0;\n"
                     MK_DESC("db", "%36", "%37")
                     "wgmma.mma_async.sync.aligned.m64n64k16.f32.bf16.bf16 " REGS32 ", {%32, %33, %34, %35}, db, p, 1, 1, 0;\n}\n"
                     : ACC32(C_IO, d) : "r"(a[0]), "r"(a[1]), "r"(a[2]), "r"(a[3]), "r"(lb), "n"(OB));
}
template <bool First, int OA, int OB> __device__ __forceinline__ void wg64_ss(float (&d)[32], uint32_t la, uint32_t lb) {
    if constexpr (First)
        asm volatile("{\n.reg .pred p;\n.reg .b32 t;\n.reg .b64 da, db;\nsetp.ne.b32 p, 0, 0;\n"
                     MK_DESC("da", "%32", "%34") MK_DESC("db", "%33", "%35")
                     "wgmma.mma_async.sync.aligned.m64n64k16.f32.bf16.bf16 " REGS32 ", da, db, p, 1, 1, 0, 1;\n}\n"
                     : ACC32(C_O, d) : "r"(la), "r"(lb), "n"(OA), "n"(OB));
    else
        asm volatile("{\n.reg .pred p;\n.reg .b32 t;\n.reg .b64 da, db;\nsetp.ne.b32 p, 1, 0;\n"
                     MK_DESC("da", "%32", "%34") MK_DESC("db", "%33", "%35")
                     "wgmma.mma_async.sync.aligned.m64n64k16.f32.bf16.bf16 " REGS32 ", da, db, p, 1, 1, 0, 1;\n}\n"
                     : ACC32(C_IO, d) : "r"(la), "r"(lb), "n"(OA), "n"(OB));
}
__host__ __device__ constexpr int koff(int kk, int chunk) { return ((kk >> 2) * chunk + (kk & 3) * 32) >> 4; }

__device__ __forceinline__ uint32_t clock_now() {
    uint32_t t;
    asm volatile("mov.u32 %0, %%clock;" : "=r"(t));
    return t;
}
template <int K> __device__ __forceinline__ void stage_put(const uint4 (&h)[12], uint32_t buf) {
    const uint32_t t = tid_now(), line = ((t >> 2) & 2) + (t & 4) + ((t >> 1) & 8);
    const uint32_t adr = buf + line * 128 + (((t & 3) ^ (line & 7)) << 4);
#pragma unroll
    for (int j = 0; j < 4; j++) {
        const int i = 4 * K + j, n = 2 * (i % 6) + i / 6;
        asm volatile("st.shared.v4.b32 [%4], {%0, %1, %2, %3};"
                     :: "r"(h[n].x), "r"(h[n].y), "r"(h[n].z), "r"(h[n].w), "r"((adr ^ ((j & 1) * 64 + (j >> 1) * 16)) + (j >> 1) * 128) : "memory");
    }
}
__device__ __forceinline__ void stage_send(const CUtensorMap* tm, uint32_t pos, int k, uint32_t buf) {
    asm volatile("fence.proxy.async.shared::cta;" ::: "memory");
    __syncwarp();
    if (elect_one()) {
        asm volatile("cp.async.bulk.tensor.5d.global.shared::cta.bulk_group [%0, {%2, %5, %3, %2, %4}], [%1];"
                     ::"l"(tm), "r"(buf), "r"(0), "r"(pos & 0xffff), "r"(pos >> 16), "r"(2 * k) : "memory");
        asm volatile("cp.async.bulk.commit_group;" ::: "memory");
    }
    __syncwarp();
}
__device__ __forceinline__ void stage_wait() {
    asm volatile("cp.async.bulk.wait_group.read 0;" ::: "memory");
    __syncwarp();
}
__device__ __forceinline__ uint32_t out_pos(int win) {
    return ((win & 63) * 2) | (((((win & 4095) >> 6) & 63) * 8 + 2 * ((tid_now() >> 5) & 3)) << 16);
}
__device__ __forceinline__ uint32_t stage_buf() { return kSmemBase + kOffStage + ((tid_now() >> 5) & 3) * 2048; }
template <int K> __device__ __forceinline__ void stage_window(uint4 (&h)[12], const CUtensorMap* tm, uint32_t pos, [[maybe_unused]] int win) {
    if constexpr (K < 3) {
        if constexpr (K > 0) stage_wait();
        stage_put<K>(h, stage_buf());
        stage_send(tm, pos, K, stage_buf());
        stage_window<K + 1>(h, tm, pos, win);
    }
}
__device__ __forceinline__ void stg128(void* p, uint4 v) {
    asm volatile("st.global.v4.b32 [%0], {%1, %2, %3, %4};" ::"l"(p), "r"(v.x), "r"(v.y), "r"(v.z), "r"(v.w) : "memory");
}
#define TAIL_DT 90
#define TAIL_FREE 2
template <int J> __device__ __forceinline__ void store_tail(uint4 (&h)[12], uint8_t* hptr, uint32_t t0) {
    if constexpr (J < 12) {
        if (J > TAIL_FREE) { while (clock_now() - t0 < (uint32_t)((J - TAIL_FREE) * TAIL_DT)) {} }
        stg128(hptr + J * 64, h[2 * (J % 6) + J / 6]);
        store_tail<J + 1>(h, hptr, t0);
    }
}
__device__ __forceinline__ uint8_t* out_address(__nv_bfloat16* out, uint32_t pos) {
    const uint32_t ln = tid_now() & 31;
    return reinterpret_cast<uint8_t*>(out) + (((pos >> 16) + (ln >> 4)) * kHW + (pos & 0xffff) * 4 + ((ln >> 1) & 6)) * (uint32_t)(kC * 2) + (ln & 3) * 16;
}
template <int K0, int K> struct Gemm1 {
    static __device__ __forceinline__ void run(float (&d)[96], uint32_t lx, uint32_t lw) {
        if constexpr (K > K0) Gemm1<K0, K - 1>::run(d, lx, lw);
        wg192_ss<K == 0, koff(K, 8192), koff(K, 24576)>(d, lx, lw);
    }
};
__device__ __forceinline__ uint32_t draw_ticket(uint32_t* counter, int G) {
    uint32_t ticket = 0;
    asm volatile("{\n.reg .pred p;\nsetp.eq.u32 p, %2, 0;\n@p atom.relaxed.gpu.global.inc.u32 %0, [%1], %3;\n}\n"
                 : "+r"(ticket) : "l"(counter), "r"(tid_now() & 127), "r"(kNWin + SHARED - 1 - kNWG * G) : "memory");
    return ticket;
}
template <int KK> struct Gemm2 { static __device__ __forceinline__ void run(float (&d)[32], const uint32_t* a, uint32_t lx) {
    Gemm2<KK - 1>::run(d, a, lx); wg64_rs<KK == 0, koff(KK, 8192)>(d, a + 4 * KK, lx);
    if constexpr (KK == PASS2 && KK < 11) ring_pass(); } };
template <int K0, int KK> struct Gemm2p { static __device__ __forceinline__ void run(float (&d)[32], const uint32_t* a, uint32_t lx) {
    if constexpr (KK > K0) Gemm2p<K0, KK - 1>::run(d, a, lx);
    wg64_rs<KK == 0, koff(KK, 8192)>(d, a + 4 * KK, lx); } };
template <int H, int C, int KK = 3> struct Gemm1h { static __device__ __forceinline__ void run(float (&d)[48], uint32_t lx, uint32_t lw) {
    if constexpr (KK > 0) Gemm1h<H, C, KK - 1>::run(d, lx, lw);
    wg96_ss<C == 0 && KK == 0, koff(4 * C + KK, 8192), koff(4 * C + KK, 24576) + H * 96 * 8>(d, lx, lw); } };
template <> struct Gemm2<-1> { static __device__ __forceinline__ void run(float (&)[32], const uint32_t*, uint32_t) {} };
template <int KK> struct Gemm3 { static __device__ __forceinline__ void run(float (&d)[96], const uint32_t* a, uint32_t lxt) {
    Gemm3<KK - 1>::run(d, a, lxt); wg192_rs<KK == 0, 1, KK * (2048 >> 4)>(d, a + 4 * KK, lxt);
    if constexpr (KK == PASS3 && KK < 3) ring_pass(); } };
template <> struct Gemm3<-1> { static __device__ __forceinline__ void run(float (&)[96], const uint32_t*, uint32_t) {} };
template <int K0, int KK> struct Gemm4 { static __device__ __forceinline__ void run(float (&d)[96], const uint32_t* a, uint32_t lw) {
    if constexpr (KK > K0) Gemm4<K0, KK - 1>::run(d, a, lw);
    wg192_rs<KK == 0, 0, koff(KK, 24576)>(d, a + 4 * KK, lw); } };

template <int J, int KK> struct Gemm3s { static __device__ __forceinline__ void run(float (&d)[32], uint32_t lp, uint32_t lxt) {
    if constexpr (KK > 0) Gemm3s<J, KK - 1>::run(d, lp, lxt);
    wg64_ss<KK == 0, KK * 2, (J * 8192 + KK * 2048) / 16>(d, lp, lxt); } };
template <int J, int K0, int KK> struct Gemm4s { static __device__ __forceinline__ void run(float (&d)[32], const uint32_t* a, uint32_t lw) {
    if constexpr (KK > K0) Gemm4s<J, K0, KK - 1>::run(d, a, lw);
    wg64_rs<KK == 0, koff(KK, 24576) + J * (8192 / 16)>(d, a + 4 * KK, lw); } };

__device__ __forceinline__ uint32_t pack_bf16(float lo, float hi) {
    uint32_t r;
    asm("cvt.rn.bf16x2.f32 %0, %1, %2;" : "=r"(r) : "f"(hi), "f"(lo));
    return r;
}
__device__ __forceinline__ float ex2(float x) {
    float r;
    asm("ex2.approx.ftz.f32 %0, %1;" : "=f"(r) : "f"(x));
    return r;
}
__device__ __forceinline__ float rcp(float x) {
    float r;
    asm("rcp.approx.ftz.f32 %0, %1;" : "=f"(r) : "f"(x));
    return r;
}

__device__ __forceinline__ void pack_slice(uint32_t* a, float (&d)[32]) {
    fence_regs(d);
#pragma unroll
    for (int i = 0; i < 16; i++) a[i] = pack_bf16(d[2 * i], d[2 * i + 1]);
#pragma unroll
    for (int i = 0; i < 16; i++) asm volatile("" : "+r"(a[i])::"memory");
}
template <int J> __device__ __forceinline__ void store_slice(float (&d)[32], uint8_t* hptr) {
    fence_regs(d);
#pragma unroll
    for (int r = 0; r < 2; r++) {
        uint4 h[2];
#pragma unroll
        for (int a = 0; a < 2; a++) {
            const int o = 16 * a + 2 * r;
            h[a] = make_uint4(pack_bf16(d[o], d[o + 1]), pack_bf16(d[o + 4], d[o + 5]), pack_bf16(d[o + 8], d[o + 9]), pack_bf16(d[o + 12], d[o + 13]));
        }
        stg128(hptr + r * (kC * 2) + J * 128, h[0]);
        stg128(hptr + r * (kC * 2) + J * 128 + 64, h[1]);
    }
    __syncwarp();
}
__device__ __forceinline__ void store_p_if(const uint32_t (&pa)[16], bool cond) {
    const uint32_t t = tid_now(), row = ((t >> 1) & 48) + (t & 15);
    const uint32_t adr = kSmemBase + kOffStage + row * 128 + ((((t >> 4) & 1) ^ (t & 7)) << 4);
#pragma unroll
    for (int i = 0; i < 4; i++)
        asm volatile("{\n.reg .pred p;\nsetp.ne.u32 p, %5, 0;\n@p stmatrix.sync.aligned.m8n8.x4.shared.b16 [%4], {%0, %1, %2, %3};\n}\n"
                     :: "r"(pa[4 * i]), "r"(pa[4 * i + 1]), "r"(pa[4 * i + 2]), "r"(pa[4 * i + 3]), "r"(adr ^ (i << 5)), "r"((uint32_t)cond) : "memory");
}
__device__ __forceinline__ void last_window(__nv_bfloat16* out, int win) {
    constexpr uint32_t dWv = ((kSmemBase + kOffWv) >> 4) | (1u << 16);
    asm volatile("fence.proxy.async.shared::cta;" ::: "memory");
    const uint32_t w = wg_uniform();
    const uint32_t dXt = desc_xt(w);
    constexpr uint32_t dP = ((kSmemBase + kOffStage) >> 4) | (1u << 16);
    float u0[32], u1[32], u2[32];
    uint32_t fa[48];
    const bool help = (win & kHelp) != 0;
    uint8_t* hptr = out_address(out, out_pos(win)) + (help ? 256 : 0);
    const uint32_t dW0 = dWv + (help ? 2 * 8192 / 16 : 0);
    asm volatile("" : "+l"(hptr) :: "memory");
    ring_wait();
    wg_fence();
    Gemm3s<0, 3>::run(u0, dP, dXt); wg_commit();
    Gemm3s<1, 3>::run(u1, dP, dXt); wg_commit();
    Gemm3s<2, 3>::run(u2, dP, dXt); wg_commit();
    wg_wait2();
    pack_slice(fa, u0);
    wg_fence();
    Gemm4s<0, 0, 3>::run(u0, fa, dW0); wg_commit();
    wg_wait2();
    pack_slice(fa + 16, u1);
    wg_fence();
    Gemm4s<0, 4, 7>::run(u0, fa, dW0); wg_commit();
    wg_wait2();
    pack_slice(fa + 32, u2);
    wg_fence();
    Gemm4s<0, 8, 11>::run(u0, fa, dW0); wg_commit();
    if (help) {
        wg_wait0();
        fence_regs(fa);
        store_slice<0>(u0, hptr);
    } else {
        wg_fence();
        Gemm4s<1, 0, 5>::run(u1, fa, dWv); wg_commit();
        wg_wait1();
        store_slice<0>(u0, hptr);
        wg_fence();
        Gemm4s<1, 6, 11>::run(u1, fa, dWv); wg_commit();
        if ((win & 4095) >= kNWin - SHARED) {
            wg_wait0();
            fence_regs(fa);
            store_slice<1>(u1, hptr);
        } else {
            wg_fence();
            Gemm4s<2, 0, 5>::run(u2, fa, dWv); wg_commit();
            wg_wait1();
            store_slice<1>(u1, hptr);
            wg_fence();
            Gemm4s<2, 6, 11>::run(u2, fa, dWv); wg_commit();
            wg_wait0();
            fence_regs(fa);
            store_slice<2>(u2, hptr);
        }
    }
}

__device__ __forceinline__ int fold_offset(int n, int k0, int q) {
    const int u = ((k0 & 63) >> 3) + (q >> 1);
    return (k0 >> 6) * 24576 + (q & 1) * 8 + n * 128 + ((u ^ (n & 7)) << 4);
}
__device__ __forceinline__ void mma16816x2(float (&c)[4], float (&d)[4], const uint32_t (&a)[4], const uint32_t (&b)[4]) {
    asm volatile("mma.sync.aligned.m16n8k16.row.col.f32.bf16.bf16.f32 {%0,%1,%2,%3}, {%8,%9,%10,%11}, {%12,%13}, {%0,%1,%2,%3};\n"
                 "mma.sync.aligned.m16n8k16.row.col.f32.bf16.bf16.f32 {%4,%5,%6,%7}, {%8,%9,%10,%11}, {%14,%15}, {%4,%5,%6,%7};"
                 : "+f"(c[0]), "+f"(c[1]), "+f"(c[2]), "+f"(c[3]), "+f"(d[0]), "+f"(d[1]), "+f"(d[2]), "+f"(d[3])
                 : "r"(a[0]), "r"(a[1]), "r"(a[2]), "r"(a[3]), "r"(b[0]), "r"(b[1]), "r"(b[2]), "r"(b[3]));
}
__device__ __forceinline__ void cp_async16(uint32_t dst, const void* src) {
    asm volatile("cp.async.cg.shared.global [%0], [%1], 16;" ::"r"(dst), "l"(src) : "memory");
}
template <bool kTrans> __device__ __forceinline__ void ldsm4(uint32_t (&r)[4], uint32_t addr) {
    if constexpr (kTrans)
        asm volatile("ldmatrix.sync.aligned.m8n8.x4.trans.shared.b16 {%0, %1, %2, %3}, [%4];" : "=r"(r[0]), "=r"(r[1]), "=r"(r[2]), "=r"(r[3]) : "r"(addr) : "memory");
    else
        asm volatile("ldmatrix.sync.aligned.m8n8.x4.shared.b16 {%0, %1, %2, %3}, [%4];" : "=r"(r[0]), "=r"(r[1]), "=r"(r[2]), "=r"(r[3]) : "r"(addr) : "memory");
}
__device__ __forceinline__ uint32_t nonzero(uint32_t w) { return w ? w : 0x80000000u; }
template <bool vo>
__device__ __forceinline__ void fold_job(Scratch* sc, const __nv_bfloat16* __restrict__ wqkv, const __nv_bfloat16* __restrict__ wo,
                                         int job, int warp, int lane) {
    constexpr int nw = vo ? 3 : 2;
    const int nb = vo ? job >> 2 : (job * 43) >> 8;
    const int n0 = nb * 16, k0 = (nw * (vo ? job & 3 : job - 6 * nb) + max(warp, 1) - 1) * 16;
    const uint32_t stage = kSmemBase + kOffWv;
    if (warp != kWarmW) {
        if (vo) {
            const char* src = reinterpret_cast<const char*>(wo) + (uint32_t)(((warp * 48 + (lane >> 1)) * kC + n0 + (lane & 1) * 8) * 2);
            const uint32_t dst = stage + warp * 1536 + ((lane ^ ((lane >> 3) & 1)) << 4);
#pragma unroll
            for (int i = 0; i < 3; i++) cp_async16(dst + i * 512, src + i * 16 * kC * 2);
        }
        if (!vo || warp != 0) {
            const int row0 = warp == 0 ? n0 : k0, col0 = warp == 0 ? kC : vo ? 2 * kC : 0;
            const char* src = reinterpret_cast<const char*>(wqkv) + (uint32_t)(((row0 + (lane >> 3)) * (3 * kC) + col0 + (lane & 7) * 8) * 2);
            const uint32_t dst = stage + warp * 6144 + (lane >> 3) * 384 + (((lane & 7) ^ (lane >> 3)) << 4);
#pragma unroll
            for (int i = 0; i < 12; i++) cp_async16((dst ^ (((i / 3) & 1) << 6)) + (i / 3) * 1536 + (i % 3) * 128, src + (i / 3) * 4 * 3 * kC * 2 + (i % 3) * 128);
        }
    }
    const int g = lane >> 2, q = lane & 3, mi = lane >> 3, r8 = lane & 7;
    const int row = 4 * (r8 >> 1) + (r8 & 1) + 2 * (mi >> 1), c = r8 + 8 * (mi >> 1);
    uint32_t baseB = stage + warp * 6144 + row * 384 + (((mi & 1) ^ (row & 7)) << 4);
    uint32_t baseA = stage + (vo ? ((2 * c + (mi & 1)) ^ ((c >> 2) & 1)) << 4 : (r8 + 8 * (mi & 1)) * 384 + (((mi >> 1) ^ r8) << 4));
    const int ch = n0 + g;
    const int n = vo ? 32 * (ch >> 5) + 8 * ((ch >> 1) & 3) + 2 * ((ch >> 3) & 3) + (ch & 1) : ch;
    char* img = reinterpret_cast<char*>(sc->wfold) + (vo ? kWBytes : 0);
    char* dst0 = img + fold_offset(n, k0, q);
    char* dst1 = img + fold_offset(n + (vo ? 2 : 8), k0, q);
    asm volatile("" : "+r"(baseA), "+r"(baseB), "+l"(dst0), "+l"(dst1));
    if (warp != kWarmW) {
        asm volatile("cp.async.wait_all;" ::: "memory");
        if (warp == 0) {
            asm volatile("bar.arrive 13, %0;" ::"n"(32 * nw + 32) : "memory");
            return;
        }
        asm volatile("bar.sync 13, %0;" ::"n"(32 * nw + 32) : "memory");
    }
    float c0[4] = {0.f, 0.f, 0.f, 0.f}, c1[4] = {0.f, 0.f, 0.f, 0.f}, c2[4] = {0.f, 0.f, 0.f, 0.f}, c3[4] = {0.f, 0.f, 0.f, 0.f};
    uint32_t A[12][4], B[12][4];
#pragma unroll
    for (int ks = 0; ks < 12; ks++) {
        ldsm4<vo>(A[ks], vo ? baseA + ks * 512 : (baseA ^ ((ks & 3) << 5)) + (ks >> 2) * 128);
        ldsm4<false>(B[ks], (baseB ^ ((ks & 3) << 5)) + (ks >> 2) * 128);
    }
#pragma unroll
    for (int ks = 0; ks < 12; ks += 2) {
        mma16816x2(c0, c1, A[ks], B[ks]);
        mma16816x2(c2, c3, A[ks + 1], B[ks + 1]);
    }
#pragma unroll
    for (int i = 0; i < 4; i++) { c0[i] += c2[i]; c1[i] += c3[i]; }
    asm volatile("{\n.reg .pred p;\nsetp.ne.u32 p, %6, %7;\n@p st.global.v2.u32 [%0], {%2, %3};\n@p st.global.v2.u32 [%1], {%4, %5};\n}\n"
                 ::"l"(dst0), "l"(dst1),
                   "r"(nonzero(pack_bf16(c0[0], c0[1]))), "r"(nonzero(pack_bf16(c1[0], c1[1]))), "r"(nonzero(pack_bf16(c0[2], c0[3]))), "r"(nonzero(pack_bf16(c1[2], c1[3]))),
                   "r"(warp), "n"(kWarmW) : "memory");
}
constexpr uint32_t kWarpsQK = 0x17;

__device__ __forceinline__ bool bar_or(uint32_t id, uint32_t n, bool pred) {
    uint32_t r;
    asm volatile("{\n.reg .pred p, q;\nsetp.ne.u32 q, %3, 0;\nbar.red.or.pred p, %1, %2, q;\nselp.u32 %0, 1, 0, p;\n}\n"
                 : "=r"(r) : "r"(id), "r"(n), "r"((uint32_t)pred) : "memory");
    return r != 0;
}
template <int N = 6> __device__ __forceinline__ bool chunk_incomplete(uint32_t base) {
    const uint32_t t = tid_now(), r = (t >> 2) & 7;
    const uint32_t adr = base + (((t >> 5) & 3) * 8 * N + r) * 128 + (t & 3) * 32 + r * 4;
    uint32_t m = ~0u;
#pragma unroll
    for (int j = 0; j < N; j++) {
        uint32_t v;
        asm volatile("ld.shared.u32 %0, [%1];" : "=r"(v) : "r"(adr + j * 1024) : "memory");
        m = min(m, v);
    }
    return m == 0;
}
__device__ __forceinline__ void load_image(uint32_t dst, const void* src, uint32_t bar) {
    mbar_expect_tx(bar, kWBytes);
#pragma unroll
    for (int c = 0; c < 3; c++) bulk_load(dst + c * 24576, reinterpret_cast<const char*>(src) + c * 24576, 24576, bar);
}
__device__ __forceinline__ void repair_image(uint32_t dst, const void* src, uint32_t bar, uint32_t par) {
    uint32_t tries = 0;
    bool bad;
    do {
        if (((tid_now() >> 5) & 3) == 0) {
            if (elect_one()) {
                asm volatile("fence.proxy.async;" ::: "memory");
                load_image(dst, src, bar);
            }
            __syncwarp();
        }
        mbar_wait(bar, par);
        par ^= 1;
        bad = chunk_incomplete(dst) | chunk_incomplete(dst + 24576) | chunk_incomplete(dst + 2 * 24576);
        if (++tries > (1u << 16)) __trap();
    } while (bar_or((tid_now() >> 7) + 1, 128, bad));
}
__device__ __forceinline__ void count_image(Scratch* sc) {
    asm volatile("red.relaxed.gpu.global.inc.u32 [%0], %1;" ::"l"(sc->cnt), "r"(3 * nctaid_now() - 1) : "memory");
}
__device__ __forceinline__ uint32_t ld_acquire(const uint32_t* p) {
    uint32_t v;
    asm volatile("ld.acquire.gpu.global.u32 %0, [%1];" : "=r"(v) : "l"(p) : "memory");
    return v;
}
__device__ __noinline__ void clear_images(Scratch* sc) {
    const uint32_t g = gridDim.x, t = threadIdx.x & 127;
    if (t == 0) {
        uint32_t spins = 0;
        while (ld_acquire(sc->cnt) < 2 * g) { if (++spins > (1u << 24)) __trap(); }
    }
    asm volatile("bar.sync %0, 128;" ::"r"((threadIdx.x >> 7) + 1) : "memory");
    for (uint32_t i = blockIdx.x * 64 + t; t < 64 && i < 2 * kWBytes / 16; i += g * 64) sc->wfold[i] = make_uint4(0, 0, 0, 0);
    if (t == 0) count_image(sc);
}
__device__ __forceinline__ void prefetch_x(const CUtensorMap* tm, int win) {
    const int wh = win >> 6, ww = win & 63;
    asm volatile("cp.async.bulk.prefetch.tensor.3d.L2.global.tile [%0, {%1, %2, %3}];"
                 ::"l"(tm), "r"(0), "r"(ww * 8), "r"(wh * 8) : "memory");
}
__device__ __forceinline__ void prefetch_x_chunk(const CUtensorMap* tm, int win, int chunk) {
    asm volatile("cp.async.bulk.prefetch.tensor.5d.L2.global.tile [%0, {%1, %2, %4, %4, %3}];"
                 ::"l"(tm), "r"(chunk * 64), "r"((win & 63) * 4), "r"((win >> 6) * 4), "r"(0) : "memory");
}

__device__ __forceinline__ void prefetch_for_ticket(const CUtensorMap* tmp, int t, int G) {
    const int base = kNWG * G;
    auto lead = [&](int tt) {
        int down = max(((kNWin - PF_END - base - tt) * PF_DOWN) >> 8, PF_MIN);
        return min(min(G + ((tt * PF_UP) >> 8), PF_LEAD), down);
    };
    const int hi = base + t + lead(t);
    int lo = max(base + t - 1 + lead(t - 1), base + t) + 1;
#pragma unroll 1
    for (; lo <= hi && lo < kNWin; lo++) prefetch_x(tmp, lo);
}

__device__ __forceinline__ void publish(uint32_t ticket, int G) {
    constexpr uint32_t sbase = kSmemBase;
    if (((tid_now() >> 5) & 3) == 0) {
        if ((tid_now() & 31) == 0) {
            uint32_t nxt = 2 * kNWG * G + ticket;
            if (nxt >= kNWin) nxt = nxt < kNWin + SHARED ? (2 * kNWin - 1 - nxt) | kHelp : kDone;
            if (nxt == kDone) {
                uint32_t p0, p1, p2, p3;
                asm volatile("ld.shared.v4.u32 {%0, %1, %2, %3}, [%4];" : "=r"(p0), "=r"(p1), "=r"(p2), "=r"(p3) : "r"(sbase + kOffBar + 64) : "memory");
                nxt = kDone + (p0 >> 30) + (p1 >> 30) + (p2 >> 30);
            }
            asm volatile("st.shared.u32 [%0], %1;" ::"r"(sbase + kOffBar + 64 + 4 * (tid_now() >> 7)), "r"(nxt) : "memory");
        }
        __syncwarp();
        asm volatile("bar.arrive %0, 128;" ::"r"((tid_now() >> 7) + 4) : "memory");
    }
}

template <bool kFewSMs>
__global__ void __launch_bounds__(kThreads, 1)
swin_attn_kernel(const __nv_bfloat16* __restrict__ wqkv, const __nv_bfloat16* __restrict__ wo, const __nv_bfloat16* __restrict__ xin, Scratch* sc, uint32_t* tickets,
                 const int G, const uint32_t trk, __nv_bfloat16* __restrict__ out, const __grid_constant__ CUtensorMap tmx, const __grid_constant__ CUtensorMap tmp, const __grid_constant__ CUtensorMap tmo) {
    extern __shared__ uint8_t smem_raw[];
    constexpr uint32_t sbase = kSmemBase;
    const uint32_t t_start = clock_now();
    asm volatile("{\n.reg .pred p, q;\n.reg .b32 i, j;\n.reg .b64 a, b;\nmad.lo.u32 i, %2, 14, %3;\nsetp.lt.u32 p, %3, 14;\nsetp.lt.and.u32 p, i, 1728, p;\n"
                 "mad.wide.u32 a, i, 128, %0;\n@p prefetch.global.L2 [a];\n"
                 "mad.lo.u32 j, %2, 5, %3;\nsetp.lt.u32 q, %3, 5;\nsetp.lt.and.u32 q, j, 576, q;\n"
                 "mad.wide.u32 b, j, 128, %1;\n@q prefetch.global.L2 [b];\n}\n" ::"l"(wqkv), "l"(wo), "r"(blockIdx.x), "r"(threadIdx.x) : "memory");
    if (smem_u32(smem_raw) != kSmemBase) __trap();
    const int tid = threadIdx.x, lane = tid & 31;
    const uint32_t warpu = __reduce_or_sync(0xffffffffu, (uint32_t)tid >> 5), wgu = warpu >> 2;
    const int warp = (int)warpu, wg = (int)wgu;
    const uint32_t bar_full = sbase + kOffBar + 8 * wg;
    constexpr uint32_t bar_m = sbase + kOffBarM, bar_w1 = sbase + kOffBar + 40;
    auto bar_v = [](int c) { return bar_w1 + 16 - 8 * c; };
    int win = wg * G + blockIdx.x;

    const int direct = blockIdx.x >= X0_LATE ? 1 : 2;
    if (!kFewSMs && blockIdx.x < kJobsM && ((kWarpsQK >> warp) & 1)) fold_job<false>(sc, wqkv, wo, blockIdx.x, warp, lane);
    if (warp == 10) {
        auto x_lines = [&](int c) {
            const int w = (c / 3) * G + blockIdx.x;
            return reinterpret_cast<const char*>(xin) + (uint32_t)((((w >> 6) * 8 + (lane >> 3)) * kHW + (w & 63) * 8 + (lane & 7)) * (kC * 2) + (c % 3) * 128);
        };
        if (elect_one()) {
            asm volatile("prefetch.tensormap [%0];" ::"l"(&tmx) : "memory");
#pragma unroll
            for (int w = 0; w < kNWG; w++) mbar_init(sbase + kOffBar + 8 * w, 1);
            mbar_init(sbase + kOffBar + 24, 1);
            mbar_init(sbase + kOffBar + 88, 1);
            mbar_init(sbase + kOffBar + 96, 1);
            mbar_init(sbase + kOffBar + 104, 1);
            mbar_init(sbase + kOffBar + 112, 1);
#pragma unroll
            for (int c = 0; c < 3; c++) mbar_init(bar_v(c), 1);
#pragma unroll
            for (int i = 0; i < 6; i++) mbar_init(bar_m + 8 * i, 1);
            asm volatile("st.shared.v4.u32 [%0], {%1, %1, %1, %1};" ::"r"(sbase + kOffBar + 64), "r"(0) : "memory");
            asm volatile("fence.mbarrier_init.release.cluster;" ::: "memory");
            asm volatile("mbarrier.arrive.shared::cta.b64 _, [%0];" ::"r"(sbase + kOffBar) : "memory");
        }
        __syncwarp();
        asm volatile("bar.arrive 15, 64;" ::: "memory");
        asm volatile("bar.arrive 0, %0;" ::"n"(kThreads) : "memory");
        const uint32_t due = (blockIdx.x * TRK_Q) >> 8;
        if (elect_one()) {
#pragma unroll
            for (int c = 0; c < 2; c++) {
                if (c >= direct) break;
                while (clock_now() - t_start < TRK_T0 + (due + c * TRK_S) / 3) {}
                tma_load_x_chunk(sbase + kOffX + c * 8192, &tmx, bar_m + 16 * c, blockIdx.x, c);
            }
        }
        __syncwarp();
#pragma unroll 1
        for (int c = direct; c < 3 * kNWG; c++) {
            const char* p = x_lines(c);
            while (clock_now() - t_start < TRK_T0 + (due + c * TRK_S) / 3) {}
            asm volatile("prefetch.global.L2 [%0];\nprefetch.global.L2 [%0 + %1];" ::"l"(p), "n"(4 * kHW * kC * 2) : "memory");
        }
        asm volatile("prefetch.tensormap [%0];" ::"l"(&tmp) : "memory");
        asm volatile("prefetch.tensormap [%0];" ::"l"(&tmo) : "memory");
    }
    int role = warp;
    asm volatile("" : "+r"(role));
    if (role == 10) {
    } else if (warp > kWarmW) {
        if (warp == 11) {
            asm volatile("bar.sync 15, 64;" ::: "memory");
            asm volatile("bar.arrive 0, %0;" ::"n"(kThreads) : "memory");
            if (elect_one()) {
                const char* img = reinterpret_cast<const char*>(sc->wfold);
#pragma unroll
                for (int i = 0; i < 6; i++) mbar_expect_tx(bar_m + 8 * i, 12288 + (i & 1 ? 0 : 8192));
#pragma unroll
                for (int c = 0; c < 3; c++) mbar_expect_tx(sbase + kOffBar + (c == 0 ? 8 : 80 + 8 * c), 8192);
                while (clock_now() - t_start < REQ_T) {}
#pragma unroll
                for (int i = 0; i < 6; i++) {
                    if (i >= 2 * direct && !(i & 1)) tma_load_x_chunk(sbase + kOffX + (i >> 1) * 8192, &tmx, bar_m + 8 * i, blockIdx.x, i >> 1);
                    bulk_load(sbase + kOffWm + i * 12288, img + i * 12288, 12288, bar_m + 8 * i);
                }
                mbar_wait(bar_m + 8, 0);
#pragma unroll
                for (int c = 0; c < 3; c++)
                    tma_load_x_chunk(sbase + kOffX + kXBytes + c * 8192, &tmx, sbase + kOffBar + (c == 0 ? 8 : 80 + 8 * c), G + blockIdx.x, c);
            }
            __syncwarp();
        } else {
            asm volatile("bar.sync 0, %0;" ::"n"(kThreads) : "memory");
            if (warp == 9) {
                if (elect_one()) {
                    while (clock_now() - t_start < REQ_TV) {}
                    mbar_wait(bar_m + 24, 0);
                    asm volatile("fence.proxy.async.shared::cta;" ::: "memory");
#pragma unroll
                    for (int c = 0; c < 3; c++) {
                        mbar_expect_tx(bar_v(c), 24576);
                        bulk_load(sbase + kOffWv + c * 24576, reinterpret_cast<const char*>(sc->wfold) + kWBytes + c * 24576, 24576, bar_v(c));
                    }
#pragma unroll
                    for (int c = 0; c < 3; c++) {
                        const uint32_t bar = sbase + kOffBar + (c == 0 ? 16 : 96 + 8 * c);
                        mbar_expect_tx(bar, 8192);
                        tma_load_x_chunk(sbase + kOffX + 2 * kXBytes + c * 8192, &tmx, bar, 2 * G + blockIdx.x, c);
                    }
                }
                __syncwarp();
            }
        }
    } else {
        if constexpr (kFewSMs) {
#pragma unroll 1
            for (int j = blockIdx.x; j < kJobs; j += G) {
                if (j >= kJobsM) fold_job<true>(sc, wqkv, wo, j - kJobsM, warp, lane);
                else if ((kWarpsQK >> warp) & 1) fold_job<false>(sc, wqkv, wo, j, warp, lane);
                asm volatile("bar.sync 14, %0;" ::"n"(32 * kWarmW + 32) : "memory");
            }
        } else {
            if (blockIdx.x - kJobsM < kJobs - kJobsM) fold_job<true>(sc, wqkv, wo, blockIdx.x - kJobsM, warp, lane);
        }
        asm volatile("bar.sync 0, %0;" ::"n"(kThreads) : "memory");
    }
    if (wg == 1) {
        mbar_wait(bar_m + 8 * (warp & 3), 0);
        bool bad = chunk_incomplete<12>(sbase + kOffWm);
#pragma unroll
        for (int i = 4; i < 6; i++) {
            mbar_wait(bar_m + 8 * i, 0);
            bad |= chunk_incomplete<3>(sbase + kOffWm + i * 12288);
        }
        bad = bar_or(2, 128, bad);
        if (bad) {
            repair_image(sbase + kOffWm, sc->wfold, sbase + kOffBar + 24, 0);
        }
        asm volatile("st.shared.u32 [%0], %1;" ::"r"(sbase + kOffBar + 80), "r"((uint32_t)bad) : "memory");
        asm volatile("bar.arrive 11, 256;" ::: "memory");
    } else if (wg == 2) {
        bool bad = false;
#pragma unroll
        for (int c = 0; c < 3; c++) {
            mbar_wait(bar_v(c), 0);
            bad |= chunk_incomplete(sbase + kOffWv + c * 24576);
        }
        if (bar_or(3, 128, bad)) {
            repair_image(sbase + kOffWv, reinterpret_cast<const char*>(sc->wfold) + kWBytes, bar_w1, 1);
        }
    }

    constexpr uint32_t dWm = ((sbase + kOffWm) >> 4) | (1u << 16);
    constexpr uint32_t dWv = ((sbase + kOffWv) >> 4) | (1u << 16);
    const float cs = 0.07216878364870322f * 1.4426950408889634f;
    mbar_wait(wg == 0 ? bar_m : bar_full, 0);

    uint4 hv[12];
    uint32_t pos;
    float acc[96];
    uint32_t ticket = win - kNWG * G;
    float s[32];
    {
        const uint32_t dX = desc_x(wg_uniform());
        uint32_t fa[48];
        if (wg == 0) {
            float ta[48], tb[48];
            wg_fence();
            Gemm1h<0, 0>::run(ta, dX, dWm);
            mbar_wait(bar_m + 8, 0);
            wg_fence();
            Gemm1h<1, 0>::run(tb, dX, dWm);
            mbar_wait(bar_m + 16, 0);
            wg_fence();
            Gemm1h<0, 1>::run(ta, dX, dWm);
            mbar_wait(bar_m + 24, 0);
            wg_fence();
            Gemm1h<1, 1>::run(tb, dX, dWm);
            mbar_wait(bar_m + 32, 0);
            wg_fence();
            Gemm1h<0, 2>::run(ta, dX, dWm);
            wg_commit();
            mbar_wait(bar_m + 40, 0);
            wg_fence();
            Gemm1h<1, 2>::run(tb, dX, dWm);
            wg_commit();
            wg_wait1();
            fence_regs(ta);
#pragma unroll
            for (int i = 0; i < 24; i++) fa[i] = pack_bf16(ta[2 * i], ta[2 * i + 1]);
#pragma unroll
            for (int i = 0; i < 24; i++) asm volatile("" : "+r"(fa[i])::"memory");
            wg_fence();
            Gemm2p<0, 5>::run(s, fa, dX);
            wg_commit();
            wg_wait1();
            fence_regs(tb);
#pragma unroll
            for (int i = 0; i < 24; i++) fa[24 + i] = pack_bf16(tb[2 * i], tb[2 * i + 1]);
#pragma unroll
            for (int i = 24; i < 48; i++) asm volatile("" : "+r"(fa[i])::"memory");
            wg_fence();
            Gemm2p<6, 11>::run(s, fa, dX);
            wg_commit();
            ring_pass();
            asm volatile("bar.sync 11, 256;" ::: "memory");
            uint32_t redo;
            asm volatile("ld.shared.u32 %0, [%1];" : "=r"(redo) : "r"(sbase + kOffBar + 80) : "memory");
            publish(ticket, G);
            asm volatile("bar.arrive 15, 256;" ::: "memory");
            redo = __reduce_or_sync(0xffffffffu, redo);
            wg_wait0();
            fence_regs(s);
            fence_regs(fa);
            if (redo) {
                wg_fence();
                Gemm1<0, 11>::run(acc, dX, dWm);
                wg_commit();
                wg_wait0();
                fence_regs(acc);
#pragma unroll
                for (int i = 0; i < 48; i++) fa[i] = pack_bf16(acc[2 * i], acc[2 * i + 1]);
                fence_regs(fa);
                wg_fence();
                Gemm2p<0, 11>::run(s, fa, dX);
                wg_commit();
                wg_wait0();
                fence_regs(s);
                fence_regs(fa);
            }
        } else {
            ring_wait();
            wg_fence();
            Gemm1<0, 3>::run(acc, dX, dWm);
            const uint32_t bar_c1 = sbase + kOffBar + 72 + 16 * wg;
            mbar_wait(bar_c1, 0);
            wg_fence();
            Gemm1<4, 7>::run(acc, dX, dWm);
            mbar_wait(bar_c1 + 8, 0);
            wg_fence();
            Gemm1<8, 11>::run(acc, dX, dWm);
            wg_commit();
            asm volatile("bar.arrive 8, 256;" ::: "memory");
            if (warp == 5) {
                if (elect_one()) prefetch_x(&tmp, kNWG * G + blockIdx.x);
                __syncwarp();
            }
            if ((tid & 127) == 0) count_image(sc);
            wg_wait0();
            fence_regs(acc);
#pragma unroll
            for (int i = 0; i < 48; i++) fa[i] = pack_bf16(acc[2 * i], acc[2 * i + 1]);
            fence_regs(fa);
            wg_fence();
            ring_wait();
            Gemm2<11>::run(s, fa, dX);
            wg_commit();
            publish(ticket, G);
            asm volatile("bar.arrive 15, 256;" ::: "memory");
            wg_wait0();
            fence_regs(s);
            fence_regs(fa);
        }
        __syncwarp();
    }

    while (true) {
        uint32_t fa[48];
        uint32_t pa[16];
        {
            float a0[8], a1[8];
#pragma unroll
            for (int j = 0; j < 8; j++) { a0[j] = fmaxf(s[4 * j], s[4 * j + 1]); a1[j] = fmaxf(s[4 * j + 2], s[4 * j + 3]); }
#pragma unroll
            for (int d = 4; d > 0; d >>= 1)
#pragma unroll
                for (int j = 0; j < d; j++) { a0[j] = fmaxf(a0[j], a0[j + d]); a1[j] = fmaxf(a1[j], a1[j + d]); }
            float m0 = a0[0], m1 = a1[0];
            m0 = fmaxf(m0, __shfl_xor_sync(0xffffffffu, m0, 1));
            m1 = fmaxf(m1, __shfl_xor_sync(0xffffffffu, m1, 1));
            m0 = fmaxf(m0, __shfl_xor_sync(0xffffffffu, m0, 2));
            m1 = fmaxf(m1, __shfl_xor_sync(0xffffffffu, m1, 2));
            m0 *= cs; m1 *= cs;
            float l0 = 0.f, l1 = 0.f;
#pragma unroll
            for (int j = 0; j < 8; j++) {
                s[4 * j]     = ex2(fmaf(s[4 * j], cs, -m0));
                s[4 * j + 1] = ex2(fmaf(s[4 * j + 1], cs, -m0));
                s[4 * j + 2] = ex2(fmaf(s[4 * j + 2], cs, -m1));
                s[4 * j + 3] = ex2(fmaf(s[4 * j + 3], cs, -m1));
                l0 += s[4 * j] + s[4 * j + 1];
                l1 += s[4 * j + 2] + s[4 * j + 3];
            }
            l0 += __shfl_xor_sync(0xffffffffu, l0, 1);
            l1 += __shfl_xor_sync(0xffffffffu, l1, 1);
            l0 += __shfl_xor_sync(0xffffffffu, l0, 2);
            l1 += __shfl_xor_sync(0xffffffffu, l1, 2);
            const float r0 = rcp(l0), r1 = rcp(l1);
#pragma unroll
            for (int j = 0; j < 8; j++) {
                pa[2 * j]     = pack_bf16(s[4 * j] * r0, s[4 * j + 1] * r0);
                pa[2 * j + 1] = pack_bf16(s[4 * j + 2] * r1, s[4 * j + 3] * r1);
            }
        }

        const uint32_t wu = __reduce_or_sync(0xffffffffu, tid_now() >> 5);
        const uint32_t dXt = desc_xt(wu >> 2);
        if ((wu & 3) != 0) asm volatile("bar.sync %0, 128;" ::"r"((wu >> 2) + 4) : "memory");
        uint32_t pub;
        asm volatile("ld.shared.u32 %0, [%1];" : "=r"(pub) : "r"(sbase + kOffBar + 64 + 4 * (tid_now() >> 7)) : "memory");
        const int nxt = (int)__reduce_or_sync(0xffffffffu, pub);
        store_p_if(pa, nxt == (int)kDone + kNWG - 1);
        if (nxt == (int)kDone + kNWG - 1) {
            last_window(out, win);
            asm volatile("exit;");
            __builtin_unreachable();
        }
        fence_regs(pa);
        wg_fence();
        ring_wait();
        Gemm3<3>::run(acc, pa, dXt);
        wg_commit();
        if constexpr (PASS3 == 3) ring_pass();
        wg_wait0();
        fence_regs(acc);
        fence_regs(pa);

        if (((tid_now() >> 5) & 3) == 0) {
            asm volatile("bar.sync %0, 128;" ::"r"((tid_now() >> 7) + 1) : "memory");
            if (elect_one()) {
                const uint32_t wgl = tid_now() >> 7;
                const uint32_t bar = sbase + kOffBar + 8 * wgl;
                if (nxt < (int)kDone) {
                    mbar_expect_tx(bar, kXBytes);
                    tma_load_x_hint(sbase + kOffX + wgl * kXBytes, &tmx, bar, nxt & 4095, nxt >= kNWin - EF_LAST);
                    uint32_t again;
                    asm volatile("ld.volatile.shared.u32 %0, [%1];" : "=r"(again) : "r"(sbase + kOffBar + 64 + 4 * wgl) : "memory");
                    prefetch_for_ticket(&tmp, (int)again - kNWG * G, G);
                }
            }
            __syncwarp();
        } else {
            asm volatile("bar.arrive %0, 128;" ::"r"((tid_now() >> 7) + 1) : "memory");
        }
#pragma unroll
        for (int i = 0; i < 48; i++) fa[i] = pack_bf16(acc[2 * i], acc[2 * i + 1]);

        asm volatile("{\n.reg .pred p;\nsetp.lt.s32 p, %5, 0;\n@p st.volatile.shared.v4.b32 [%4], {%0, %1, %2, %3};\n}\n"
                     :: "r"(fa[44]), "r"(fa[45]), "r"(fa[46]), "r"(fa[47]), "r"(sbase + kOffBar + 64), "r"(nxt) : "memory");
        fence_regs(fa);
        wg_fence();
        ring_wait();
        Gemm4<0, 1>::run(acc, fa, dWv);
        wg_commit();
        Gemm4<2, 10>::run(acc, fa, dWv);
        wg_commit();
        wg_wait1();
        uint32_t fl[4];
        uint32_t zero;
        asm volatile("ld.volatile.shared.u32 %0, [%1];" : "=r"(zero) : "r"(sbase + kOffBar + 76) : "memory");
#pragma unroll
        for (int i = 0; i < 4; i++) fl[i] = fa[44 + i] ^ zero;
        if constexpr (PASS4 == 10) ring_pass();
        wg_fence();
        wg192_rs<false, 0, koff(11, 24576)>(acc, fl, dWv);
        wg_commit();
        if constexpr (PASS4 == 11) ring_pass();
        pos = out_pos(win ^ zero);
        win = nxt | (~win & kPhase);
        const uint32_t dX = desc_x(__reduce_or_sync(0xffffffffu, (tid_now() >> 7) ^ zero));
        asm volatile("" : "+r"(pos) :: "memory");
        wg_wait0();
        fence_regs(acc);
        fence_regs(fa);
        fence_regs(fl);

#pragma unroll
        for (int a = 0; a < 6; a++) {
            hv[2 * a].x     = pack_bf16(acc[16 * a + 0], acc[16 * a + 1]);
            hv[2 * a].y     = pack_bf16(acc[16 * a + 4], acc[16 * a + 5]);
            hv[2 * a].z     = pack_bf16(acc[16 * a + 8], acc[16 * a + 9]);
            hv[2 * a].w     = pack_bf16(acc[16 * a + 12], acc[16 * a + 13]);
            hv[2 * a + 1].x = pack_bf16(acc[16 * a + 2], acc[16 * a + 3]);
            hv[2 * a + 1].y = pack_bf16(acc[16 * a + 6], acc[16 * a + 7]);
            hv[2 * a + 1].z = pack_bf16(acc[16 * a + 10], acc[16 * a + 11]);
            hv[2 * a + 1].w = pack_bf16(acc[16 * a + 14], acc[16 * a + 15]);
        }
        if (win < (int)kDone) mbar_wait(sbase + kOffBar + 8 * (tid_now() >> 7), (win >> 16) & 1);
        if (win >= (int)kDone) break;
        wg_fence();
        ring_wait();
        Gemm1<0, PASS1>::run(acc, dX, dWm);
        if constexpr (PASS1 < 11) {
            ring_pass();
            Gemm1<PASS1 + 1, 11>::run(acc, dX, dWm);
        }
        wg_commit();
        if constexpr (PASS1 == 11) ring_pass();
        ticket = draw_ticket(tickets, G);
        asm volatile("bar.sync 15, 256;" ::: "memory");
        stage_window<0>(hv, &tmo, pos, win);
        wg_wait0();
        fence_regs(acc);
#pragma unroll
        for (int i = 0; i < 48; i++) fa[i] = pack_bf16(acc[2 * i], acc[2 * i + 1]);

        fence_regs(fa);
        wg_fence();
        ring_wait();
        Gemm2<11>::run(s, fa, dX);
        wg_commit();
        if constexpr (PASS2 == 11) ring_pass();
        publish(ticket, G);
        asm volatile("cp.async.bulk.wait_group.read 0;" ::: "memory");
        asm volatile("bar.arrive 15, 256;" ::: "memory");
        wg_wait0();
        fence_regs(s);
        fence_regs(fa);
    }
    if ((win & 3) == 0) {
        const uint32_t buf = sbase + kOffX + (tid_now() >> 7) * kXBytes + ((tid_now() >> 5) & 3) * 2048;
        asm volatile("bar.sync %0, 128;" ::"r"((tid_now() >> 7) + 1) : "memory");
        ring_wait();
        ring_pass();
        stage_put<0>(hv, buf);
        stage_send(&tmo, pos, 0, buf);
        stage_put<1>(hv, buf + 8192);
        stage_send(&tmo, pos, 1, buf + 8192);
        stage_put<2>(hv, buf + 2 * 8192);
        stage_send(&tmo, pos, 2, buf + 2 * 8192);
        clear_images(sc);
        asm volatile("bar.sync 15, 256;" ::: "memory");
        stage_wait();
    } else {
        uint8_t* hptr = out_address(out, pos);
        store_tail<0>(hv, hptr, clock_now());
    }
}

typedef CUresult (*EncodeTiledFn)(CUtensorMap*, CUtensorMapDataType, cuuint32_t, void*, const cuuint64_t*,
                                  const cuuint64_t*, const cuuint32_t*, const cuuint32_t*, CUtensorMapInterleave,
                                  CUtensorMapSwizzle, CUtensorMapL2promotion, CUtensorMapFloatOOBfill);

}

extern "C" void kernel_launch(void* const* d_in, const int* in_sizes, int n_in, void* d_out, int out_size) {
    (void)in_sizes; (void)n_in; (void)out_size;
    const __nv_bfloat16* x    = (const __nv_bfloat16*)d_in[0];
    const __nv_bfloat16* wqkv = (const __nv_bfloat16*)d_in[1];
    const __nv_bfloat16* wo   = (const __nv_bfloat16*)d_in[2];

    static EncodeTiledFn encode = nullptr;
    static int num_sms = 0;
    static void* scratch = nullptr;
    if (!encode) {
        void* fn = nullptr;
        cudaDriverEntryPointQueryResult qr;
        cudaGetDriverEntryPoint("cuTensorMapEncodeTiled", &fn, cudaEnableDefault, &qr);
        encode = (EncodeTiledFn)fn;
        int dev = 0;
        cudaGetDevice(&dev);
        cudaDeviceGetAttribute(&num_sms, cudaDevAttrMultiProcessorCount, dev);
        if (num_sms > kNWin / 16) num_sms = kNWin / 16;
        cudaGetSymbolAddress(&scratch, g_scratch);
        cudaFuncSetAttribute(swin_attn_kernel<false>, cudaFuncAttributeMaxDynamicSharedMemorySize, kSmemBytes);
        cudaFuncSetAttribute(swin_attn_kernel<true>, cudaFuncAttributeMaxDynamicSharedMemorySize, kSmemBytes);
    }
    CUtensorMap tmx;
    const cuuint64_t gdim[5] = {(cuuint64_t)kC, (cuuint64_t)kHW / 2, 2, 2, (cuuint64_t)kHW / 2};
    const cuuint64_t gstr[4] = {(cuuint64_t)kC * 4, (cuuint64_t)kHW * kC * 2, (cuuint64_t)kC * 2, (cuuint64_t)kHW * kC * 4};
    const cuuint32_t box[5] = {64, 4, 2, 2, 4};
    const cuuint32_t estr[5] = {1, 1, 1, 1, 1};
    encode(&tmx, CU_TENSOR_MAP_DATA_TYPE_BFLOAT16, 5, (void*)x, gdim, gstr, box, estr, CU_TENSOR_MAP_INTERLEAVE_NONE,
           CU_TENSOR_MAP_SWIZZLE_128B, CU_TENSOR_MAP_L2_PROMOTION_NONE, CU_TENSOR_MAP_FLOAT_OOB_FILL_NONE);

    CUtensorMap tmp;
    const cuuint64_t pdim[3] = {(cuuint64_t)kC, (cuuint64_t)kHW, (cuuint64_t)kHW};
    const cuuint64_t pstr[2] = {(cuuint64_t)kC * 2, (cuuint64_t)kHW * kC * 2};
    const cuuint32_t pbox[3] = {(cuuint32_t)kC, 8, 8};
    encode(&tmp, CU_TENSOR_MAP_DATA_TYPE_BFLOAT16, 3, (void*)x, pdim, pstr, pbox, estr, CU_TENSOR_MAP_INTERLEAVE_NONE,
           CU_TENSOR_MAP_SWIZZLE_NONE, CU_TENSOR_MAP_L2_PROMOTION_NONE, CU_TENSOR_MAP_FLOAT_OOB_FILL_NONE);
    CUtensorMap tmo;
    const cuuint64_t odim[5] = {64, 6, (cuuint64_t)kHW / 4, 2, (cuuint64_t)kHW};
    const cuuint64_t ostr[4] = {128, (cuuint64_t)kC * 8, (cuuint64_t)kC * 4, (cuuint64_t)kHW * kC * 2};
    const cuuint32_t obox[5] = {64, 2, 2, 2, 2};
    encode(&tmo, CU_TENSOR_MAP_DATA_TYPE_BFLOAT16, 5, d_out, odim, ostr, obox, estr, CU_TENSOR_MAP_INTERLEAVE_NONE,
           CU_TENSOR_MAP_SWIZZLE_128B, CU_TENSOR_MAP_L2_PROMOTION_NONE, CU_TENSOR_MAP_FLOAT_OOB_FILL_NONE);
    if (num_sms >= kJobs)
        swin_attn_kernel<false><<<num_sms, kThreads, kSmemBytes, cudaStreamPerThread>>>(wqkv, wo, x, (Scratch*)scratch, ((Scratch*)scratch)->ticket, num_sms, TRK_HOST, (__nv_bfloat16*)d_out, tmx, tmp, tmo);
    else
        swin_attn_kernel<true><<<num_sms, kThreads, kSmemBytes, cudaStreamPerThread>>>(wqkv, wo, x, (Scratch*)scratch, ((Scratch*)scratch)->ticket, num_sms, TRK_HOST, (__nv_bfloat16*)d_out, tmx, tmp, tmo);
}
```

```cpp
#include <cuda_runtime.h>
#include <cuda_bf16.h>
#include <cuda.h>
#include <stdint.h>

namespace {

constexpr int kC      = 192;
constexpr int kHW     = 512;
#define MAXWIN 4096
constexpr int kNWin   = MAXWIN;
constexpr int kXBytes = 64 * kC * 2;
constexpr int kWBytes = kC * kC * 2;
constexpr int kNWG    = 3;
constexpr int kThreads = kNWG * 128;
constexpr int kJobsM  = 72;
constexpr int kJobs   = 120;
constexpr int kWarmW  = 4;
#define PF_LEAD 400
#define PF_UP 114
#define PF_DOWN 39
#define PF_END 300
#define PF_MIN 135
#define EF_LAST 1000
#define TRK_T0 500
#define TRK_S 1700
#define TRK_HOST (TRK_S * 256 / num_sms)
#define TRK_Q trk
#define X0_LATE 72
#define REQ_T 2340
#define REQ_TV 4200

constexpr int kOffWm  = 0;
constexpr int kOffWv  = kWBytes;
constexpr int kOffX   = 2 * kWBytes;
constexpr int kOffStage = kOffX + kNWG * kXBytes;
constexpr int kOffBar = kOffStage + 8192;
constexpr int kOffBarM = kOffBar + 128;
constexpr int kOffProf = kOffBar + 192;
constexpr int kSmemBytes = kOffProf;
constexpr uint32_t kSmemBase = 1024;

struct Scratch {
    uint4 wfold[2 * kWBytes / 16];
    uint32_t ticket[32];
    uint32_t cnt[32];
};
__device__ __align__(128) Scratch g_scratch;

__device__ __forceinline__ uint32_t smem_u32(const void* p) { return (uint32_t)__cvta_generic_to_shared(p); }

__device__ __forceinline__ void mbar_init(uint32_t bar, uint32_t count) {
    asm volatile("mbarrier.init.shared::cta.b64 [%0], %1;" ::"r"(bar), "r"(count) : "memory");
}
__device__ __forceinline__ void mbar_expect_tx(uint32_t bar, uint32_t bytes) {
    asm volatile("mbarrier.arrive.expect_tx.shared::cta.b64 _, [%0], %1;" ::"r"(bar), "r"(bytes) : "memory");
}
__device__ __forceinline__ void mbar_wait(uint32_t bar, uint32_t parity) {
    uint32_t ok;
    uint32_t spins = 0;
    do {
        asm volatile("{\n.reg .pred p;\n"
                     "mbarrier.try_wait.parity.shared::cta.b64 p, [%1], %2;\n"
                     "selp.b32 %0, 1, 0, p;\n}\n"
                     : "=r"(ok) : "r"(bar), "r"(parity) : "memory");
        if (++spins > (1u << 26)) __trap();
    } while (!ok);
}
__device__ __forceinline__ uint32_t tid_now() {
    uint32_t t;
    asm volatile("mov.u32 %0, %%tid.x;" : "=r"(t));
    return t;
}
__device__ __forceinline__ uint32_t nctaid_now() {
    uint32_t t;
    asm volatile("mov.u32 %0, %%nctaid.x;" : "=r"(t));
    return t;
}
__device__ __forceinline__ bool elect_one() {
    uint32_t pred;
    asm volatile("{\n.reg .pred p;\nelect.sync _|p, 0xffffffff;\nselp.b32 %0, 1, 0, p;\n}\n" : "=r"(pred));
    return pred != 0;
}
#define PASS1 10
#define PASS4 11
#define PASS2 7
#define PASS3 3
__device__ __forceinline__ void ring_wait() {
    asm volatile("bar.sync %0, 256;" ::"r"((tid_now() >> 7) + 8) : "memory");
}
__device__ __forceinline__ void ring_pass() {
    const uint32_t w = tid_now() >> 7;
    asm volatile("bar.arrive %0, 256;" ::"r"(w == kNWG - 1 ? 8u : w + 9u) : "memory");
}
constexpr uint32_t kDone = 0x40000000u;
constexpr int kPhase = 0x10000;
#define SHARED 16
#define SHARED_HOST SHARED
constexpr int kHelp = 0x1000;
__device__ __forceinline__ uint32_t wg_uniform() { return __reduce_or_sync(0xffffffffu, tid_now() >> 7); }
__device__ __forceinline__ uint32_t desc_x(uint32_t w) { return (((kSmemBase + kOffX) >> 4) | (1u << 16)) + w * (kXBytes >> 4); }
__device__ __forceinline__ uint32_t desc_xt(uint32_t w) { return (((kSmemBase + kOffX) >> 4) | ((8192u >> 4) << 16)) + w * (kXBytes >> 4); }
__device__ __forceinline__ void tma_load_x_chunk(uint32_t dst, const CUtensorMap* tm, uint32_t bar, int win, int chunk) {
    asm volatile("cp.async.bulk.tensor.5d.shared::cluster.global.mbarrier::complete_tx::bytes"
                 " [%0], [%1, {%3, %4, %6, %6, %5}], [%2];"
                 ::"r"(dst), "l"(tm), "r"(bar), "r"(chunk * 64), "r"((win & 63) * 4), "r"((win >> 6) * 4), "r"(0) : "memory");
}
__device__ __forceinline__ void tma_load_x_hint(uint32_t dst, const CUtensorMap* tm, uint32_t bar, int win, bool evict_first) {
    uint64_t first, normal;
    asm("createpolicy.fractional.L2::evict_first.b64 %0, 1.0;" : "=l"(first));
    asm("createpolicy.fractional.L2::evict_normal.b64 %0, 1.0;" : "=l"(normal));
#pragma unroll
    for (int c = 0; c < 3; c++)
        asm volatile("cp.async.bulk.tensor.5d.shared::cluster.global.mbarrier::complete_tx::bytes.L2::cache_hint"
                     " [%0], [%1, {%3, %4, %6, %6, %5}], [%2], %7;"
                     ::"r"(dst + c * 8192), "l"(tm), "r"(bar), "r"(c * 64), "r"((win & 63) * 4), "r"((win >> 6) * 4), "r"(0),
                       "l"(evict_first ? first : normal) : "memory");
}
__device__ __forceinline__ void bulk_load(uint32_t dst, const void* src, uint32_t bytes, uint32_t bar) {
    asm volatile("cp.async.bulk.shared::cluster.global.mbarrier::complete_tx::bytes [%0], [%1], %2, [%3];"
                 ::"r"(dst), "l"(src), "r"(bytes), "r"(bar) : "memory");
}

__device__ __forceinline__ void wg_fence()  { asm volatile("wgmma.fence.sync.aligned;" ::: "memory"); }
__device__ __forceinline__ void wg_commit() { asm volatile("wgmma.commit_group.sync.aligned;" ::: "memory"); }
__device__ __forceinline__ void wg_wait0()  { asm volatile("wgmma.wait_group.sync.aligned 0;" ::: "memory"); }
__device__ __forceinline__ void wg_wait1()  { asm volatile("wgmma.wait_group.sync.aligned 1;" ::: "memory"); }
__device__ __forceinline__ void wg_wait2()  { asm volatile("wgmma.wait_group.sync.aligned 2;" ::: "memory"); }

template <int N> __device__ __forceinline__ void fence_regs(float (&d)[N]) {
#pragma unroll
    for (int i = 0; i < N; i++) asm volatile("" : "+f"(d[i])::"memory");
}
template <int N> __device__ __forceinline__ void fence_regs(uint32_t (&d)[N]) {
#pragma unroll
    for (int i = 0; i < N; i++) asm volatile("" : "+r"(d[i])::"memory");
}

#define ACC8(c, d, i) c(d[i]), c(d[i + 1]), c(d[i + 2]), c(d[i + 3]), c(d[i + 4]), c(d[i + 5]), c(d[i + 6]), c(d[i + 7])
#define ACC32(c, d) ACC8(c, d, 0), ACC8(c, d, 8), ACC8(c, d, 16), ACC8(c, d, 24)
#define ACC96(c, d) ACC32(c, d), ACC8(c, d, 32), ACC8(c, d, 40), ACC8(c, d, 48), ACC8(c, d, 56), \
                    ACC8(c, d, 64), ACC8(c, d, 72), ACC8(c, d, 80), ACC8(c, d, 88)
#define C_IO(x) "+f"(x)
#define C_O(x) "=f"(x)
#define REGS32 "{%0, %1, %2, %3, %4, %5, %6, %7, %8, %9, %10, %11, %12, %13, %14, %15, " \
               "%16, %17, %18, %19, %20, %21, %22, %23, %24, %25, %26, %27, %28, %29, %30, %31}"
#define REGS96 "{%0, %1, %2, %3, %4, %5, %6, %7, %8, %9, %10, %11, %12, %13, %14, %15, " \
               "%16, %17, %18, %19, %20, %21, %22, %23, %24, %25, %26, %27, %28, %29, %30, %31, " \
               "%32, %33, %34, %35, %36, %37, %38, %39, %40, %41, %42, %43, %44, %45, %46, %47, " \
               "%48, %49, %50, %51, %52, %53, %54, %55, %56, %57, %58, %59, %60, %61, %62, %63, " \
               "%64, %65, %66, %67, %68, %69, %70, %71, %72, %73, %74, %75, %76, %77, %78, %79, " \
               "%80, %81, %82, %83, %84, %85, %86, %87, %88, %89, %90, %91, %92, %93, %94, %95}"

#define DESC_HI "0x40000040"
#define MK_DESC(name, lo, off) "add.u32 t, " lo ", " off ";\nmov.b64 " name ", {t, " DESC_HI "};\n"

template <bool First, int OA, int OB> __device__ __forceinline__ void wg192_ss(float (&d)[96], uint32_t la, uint32_t lb) {
    if constexpr (First)
        asm volatile("{\n.reg .pred p;\n.reg .b32 t;\n.reg .b64 da, db;\nsetp.ne.b32 p, 0, 0;\n"
                     MK_DESC("da", "%96", "%98") MK_DESC("db", "%97", "%99")
                     "wgmma.mma_async.sync.aligned.m64n192k16.f32.bf16.bf16 " REGS96 ", da, db, p, 1, 1, 0, 0;\n}\n"
                     : ACC96(C_O, d) : "r"(la), "r"(lb), "n"(OA), "n"(OB));
    else
        asm volatile("{\n.reg .pred p;\n.reg .b32 t;\n.reg .b64 da, db;\nsetp.ne.b32 p, 1, 0;\n"
                     MK_DESC("da", "%96", "%98") MK_DESC("db", "%97", "%99")
                     "wgmma.mma_async.sync.aligned.m64n192k16.f32.bf16.bf16 " REGS96 ", da, db, p, 1, 1, 0, 0;\n}\n"
                     : ACC96(C_IO, d) : "r"(la), "r"(lb), "n"(OA), "n"(OB));
}
#define ACC48(c, d, o) ACC8(c, d, o), ACC8(c, d, o + 8), ACC8(c, d, o + 16), ACC8(c, d, o + 24), ACC8(c, d, o + 32), ACC8(c, d, o + 40)
#define REGS48 "{%0, %1, %2, %3, %4, %5, %6, %7, %8, %9, %10, %11, %12, %13, %14, %15, %16, %17, %18, %19, %20, %21, %22, %23, " \
               "%24, %25, %26, %27, %28, %29, %30, %31, %32, %33, %34, %35, %36, %37, %38, %39, %40, %41, %42, %43, %44, %45, %46, %47}"
template <bool First, int OA, int OB> __device__ __forceinline__ void wg96_ss(float (&d)[48], uint32_t la, uint32_t lb) {
    if constexpr (First)
        asm volatile("{\n.reg .pred p;\n.reg .b32 t;\n.reg .b64 da, db;\nsetp.ne.b32 p, 0, 0;\n"
                     MK_DESC("da", "%48", "%50") MK_DESC("db", "%49", "%51")
                     "wgmma.mma_async.sync.aligned.m64n96k16.f32.bf16.bf16 " REGS48 ", da, db, p, 1, 1, 0, 0;\n}\n"
                     : ACC48(C_O, d, 0) : "r"(la), "r"(lb), "n"(OA), "n"(OB));
    else
        asm volatile("{\n.reg .pred p;\n.reg .b32 t;\n.reg .b64 da, db;\nsetp.ne.b32 p, 1, 0;\n"
                     MK_DESC("da", "%48", "%50") MK_DESC("db", "%49", "%51")
                     "wgmma.mma_async.sync.aligned.m64n96k16.f32.bf16.bf16 " REGS48 ", da, db, p, 1, 1, 0, 0;\n}\n"
                     : ACC48(C_IO, d, 0) : "r"(la), "r"(lb), "n"(OA), "n"(OB));
}
template <bool First, int TB, int OB> __device__ __forceinline__ void wg192_rs(float (&d)[96], const uint32_t* a, uint32_t lb) {
    if constexpr (First)
        asm volatile("{\n.reg .pred p;\n.reg .b32 t;\n.reg .b64 db;\nsetp.ne.b32 p, 0, 0;\n"
                     MK_DESC("db", "%100", "%102")
                     "wgmma.mma_async.sync.aligned.m64n192k16.f32.bf16.bf16 " REGS96 ", {%96, %97, %98, %99}, db, p, 1, 1, %101;\n}\n"
                     : ACC96(C_O, d) : "r"(a[0]), "r"(a[1]), "r"(a[2]), "r"(a[3]), "r"(lb), "n"(TB), "n"(OB));
    else
        asm volatile("{\n.reg .pred p;\n.reg .b32 t;\n.reg .b64 db;\nsetp.ne.b32 p, 1, 0;\n"
                     MK_DESC("db", "%100", "%102")
                     "wgmma.mma_async.sync.aligned.m64n192k16.f32.bf16.bf16 " REGS96 ", {%96, %97, %98, %99}, db, p, 1, 1, %101;\n}\n"
                     : ACC96(C_IO, d) : "r"(a[0]), "r"(a[1]), "r"(a[2]), "r"(a[3]), "r"(lb), "n"(TB), "n"(OB));
}
template <bool First, int OB> __device__ __forceinline__ void wg64_rs(float (&d)[32], const uint32_t* a, uint32_t lb) {
    if constexpr (First)
        asm volatile("{\n.reg .pred p;\n.reg .b32 t;\n.reg .b64 db;\nsetp.ne.b32 p, 0, 0;\n"
                     MK_DESC("db", "%36", "%37")
                     "wgmma.mma_async.sync.aligned.m64n64k16.f32.bf16.bf16 " REGS32 ", {%32, %33, %34, %35}, db, p, 1, 1, 0;\n}\n"
                     : ACC32(C_O, d) : "r"(a[0]), "r"(a[1]), "r"(a[2]), "r"(a[3]), "r"(lb), "n"(OB));
    else
        asm volatile("{\n.reg .pred p;\n.reg .b32 t;\n.reg .b64 db;\nsetp.ne.b32 p, 1, 0;\n"
                     MK_DESC("db", "%36", "%37")
                     "wgmma.mma_async.sync.aligned.m64n64k16.f32.bf16.bf16 " REGS32 ", {%32, %33, %34, %35}, db, p, 1, 1, 0;\n}\n"
                     : ACC32(C_IO, d) : "r"(a[0]), "r"(a[1]), "r"(a[2]), "r"(a[3]), "r"(lb), "n"(OB));
}
template <bool First, int OA, int OB> __device__ __forceinline__ void wg64_ss(float (&d)[32], uint32_t la, uint32_t lb) {
    if constexpr (First)
        asm volatile("{\n.reg .pred p;\n.reg .b32 t;\n.reg .b64 da, db;\nsetp.ne.b32 p, 0, 0;\n"
                     MK_DESC("da", "%32", "%34") MK_DESC("db", "%33", "%35")
                     "wgmma.mma_async.sync.aligned.m64n64k16.f32.bf16.bf16 " REGS32 ", da, db, p, 1, 1, 0, 1;\n}\n"
                     : ACC32(C_O, d) : "r"(la), "r"(lb), "n"(OA), "n"(OB));
    else
        asm volatile("{\n.reg .pred p;\n.reg .b32 t;\n.reg .b64 da, db;\nsetp.ne.b32 p, 1, 0;\n"
                     MK_DESC("da", "%32", "%34") MK_DESC("db", "%33", "%35")
                     "wgmma.mma_async.sync.aligned.m64n64k16.f32.bf16.bf16 " REGS32 ", da, db, p, 1, 1, 0, 1;\n}\n"
                     : ACC32(C_IO, d) : "r"(la), "r"(lb), "n"(OA), "n"(OB));
}
__host__ __device__ constexpr int koff(int kk, int chunk) { return ((kk >> 2) * chunk + (kk & 3) * 32) >> 4; }

__device__ __forceinline__ uint32_t clock_now() {
    uint32_t t;
    asm volatile("mov.u32 %0, %%clock;" : "=r"(t));
    return t;
}
template <int K> __device__ __forceinline__ void stage_put(const uint4 (&h)[12], uint32_t buf) {
    const uint32_t t = tid_now(), line = ((t >> 2) & 2) + (t & 4) + ((t >> 1) & 8);
    const uint32_t adr = buf + line * 128 + (((t & 3) ^ (line & 7)) << 4);
#pragma unroll
    for (int j = 0; j < 4; j++) {
        const int i = 4 * K + j, n = 2 * (i % 6) + i / 6;
        asm volatile("st.shared.v4.b32 [%4], {%0, %1, %2, %3};"
                     :: "r"(h[n].x), "r"(h[n].y), "r"(h[n].z), "r"(h[n].w), "r"((adr ^ ((j & 1) * 64 + (j >> 1) * 16)) + (j >> 1) * 128) : "memory");
    }
}
__device__ __forceinline__ void stage_send(const CUtensorMap* tm, uint32_t pos, int k, uint32_t buf) {
    asm volatile("fence.proxy.async.shared::cta;" ::: "memory");
    __syncwarp();
    if (elect_one()) {
        asm volatile("cp.async.bulk.tensor.5d.global.shared::cta.bulk_group [%0, {%2, %5, %3, %2, %4}], [%1];"
                     ::"l"(tm), "r"(buf), "r"(0), "r"(pos & 0xffff), "r"(pos >> 16), "r"(2 * k) : "memory");
        asm volatile("cp.async.bulk.commit_group;" ::: "memory");
    }
    __syncwarp();
}
__device__ __forceinline__ void stage_wait() {
    asm volatile("cp.async.bulk.wait_group.read 0;" ::: "memory");
    __syncwarp();
}
__device__ __forceinline__ uint32_t out_pos(int win) {
    return ((win & 63) * 2) | (((((win & 4095) >> 6) & 63) * 8 + 2 * ((tid_now() >> 5) & 3)) << 16);
}
__device__ __forceinline__ uint32_t stage_buf() { return kSmemBase + kOffStage + ((tid_now() >> 5) & 3) * 2048; }
template <int K> __device__ __forceinline__ void stage_window(uint4 (&h)[12], const CUtensorMap* tm, uint32_t pos, [[maybe_unused]] int win) {
    if constexpr (K < 3) {
        if constexpr (K > 0) stage_wait();
        stage_put<K>(h, stage_buf());
        stage_send(tm, pos, K, stage_buf());
        stage_window<K + 1>(h, tm, pos, win);
    }
}
__device__ __forceinline__ void stg128(void* p, uint4 v) {
    asm volatile("st.global.v4.b32 [%0], {%1, %2, %3, %4};" ::"l"(p), "r"(v.x), "r"(v.y), "r"(v.z), "r"(v.w) : "memory");
}
#define TAIL_DT 75
#define TAIL_FREE 2
template <int J> __device__ __forceinline__ void store_tail(uint4 (&h)[12], uint8_t* hptr, uint32_t t0) {
    if constexpr (J < 12) {
        if (J > TAIL_FREE) { while (clock_now() - t0 < (uint32_t)((J - TAIL_FREE) * TAIL_DT)) {} }
        stg128(hptr + J * 64, h[2 * (J % 6) + J / 6]);
        store_tail<J + 1>(h, hptr, t0);
    }
}
__device__ __forceinline__ uint8_t* out_address(__nv_bfloat16* out, uint32_t pos) {
    const uint32_t ln = tid_now() & 31;
    return reinterpret_cast<uint8_t*>(out) + (((pos >> 16) + (ln >> 4)) * kHW + (pos & 0xffff) * 4 + ((ln >> 1) & 6)) * (uint32_t)(kC * 2) + (ln & 3) * 16;
}
template <int K0, int K> struct Gemm1 {
    static __device__ __forceinline__ void run(float (&d)[96], uint32_t lx, uint32_t lw) {
        if constexpr (K > K0) Gemm1<K0, K - 1>::run(d, lx, lw);
        wg192_ss<K == 0, koff(K, 8192), koff(K, 24576)>(d, lx, lw);
    }
};
__device__ __forceinline__ uint32_t draw_ticket(uint32_t* counter, uint32_t last) {
    uint32_t ticket = 0;
    asm volatile("{\n.reg .pred p;\nsetp.eq.u32 p, %2, 0;\n@p atom.relaxed.gpu.global.inc.u32 %0, [%1], %3;\n}\n"
                 : "+r"(ticket) : "l"(counter), "r"(tid_now() & 127), "r"(last) : "memory");
    return ticket;
}
template <int KK> struct Gemm2 { static __device__ __forceinline__ void run(float (&d)[32], const uint32_t* a, uint32_t lx) {
    Gemm2<KK - 1>::run(d, a, lx); wg64_rs<KK == 0, koff(KK, 8192)>(d, a + 4 * KK, lx);
    if constexpr (KK == PASS2 && KK < 11) ring_pass(); } };
template <int K0, int KK> struct Gemm2p { static __device__ __forceinline__ void run(float (&d)[32], const uint32_t* a, uint32_t lx) {
    if constexpr (KK > K0) Gemm2p<K0, KK - 1>::run(d, a, lx);
    wg64_rs<KK == 0, koff(KK, 8192)>(d, a + 4 * KK, lx); } };
template <int H, int C, int KK = 3> struct Gemm1h { static __device__ __forceinline__ void run(float (&d)[48], uint32_t lx, uint32_t lw) {
    if constexpr (KK > 0) Gemm1h<H, C, KK - 1>::run(d, lx, lw);
    wg96_ss<C == 0 && KK == 0, koff(4 * C + KK, 8192), koff(4 * C + KK, 24576) + H * 96 * 8>(d, lx, lw); } };
template <> struct Gemm2<-1> { static __device__ __forceinline__ void run(float (&)[32], const uint32_t*, uint32_t) {} };
template <int KK> struct Gemm3 { static __device__ __forceinline__ void run(float (&d)[96], const uint32_t* a, uint32_t lxt) {
    Gemm3<KK - 1>::run(d, a, lxt); wg192_rs<KK == 0, 1, KK * (2048 >> 4)>(d, a + 4 * KK, lxt);
    if constexpr (KK == PASS3 && KK < 3) ring_pass(); } };
template <> struct Gemm3<-1> { static __device__ __forceinline__ void run(float (&)[96], const uint32_t*, uint32_t) {} };
template <int K0, int KK> struct Gemm4 { static __device__ __forceinline__ void run(float (&d)[96], const uint32_t* a, uint32_t lw) {
    if constexpr (KK > K0) Gemm4<K0, KK - 1>::run(d, a, lw);
    wg192_rs<KK == 0, 0, koff(KK, 24576)>(d, a + 4 * KK, lw); } };

template <int J, int KK> struct Gemm3s { static __device__ __forceinline__ void run(float (&d)[32], uint32_t lp, uint32_t lxt) {
    if constexpr (KK > 0) Gemm3s<J, KK - 1>::run(d, lp, lxt);
    wg64_ss<KK == 0, KK * 2, (J * 8192 + KK * 2048) / 16>(d, lp, lxt); } };
template <int J, int K0, int KK> struct Gemm4s { static __device__ __forceinline__ void run(float (&d)[32], const uint32_t* a, uint32_t lw) {
    if constexpr (KK > K0) Gemm4s<J, K0, KK - 1>::run(d, a, lw);
    wg64_rs<KK == 0, koff(KK, 24576) + J * (8192 / 16)>(d, a + 4 * KK, lw); } };

__device__ __forceinline__ uint32_t pack_bf16(float lo, float hi) {
    uint32_t r;
    asm("cvt.rn.bf16x2.f32 %0, %1, %2;" : "=r"(r) : "f"(hi), "f"(lo));
    return r;
}
__device__ __forceinline__ float ex2(float x) {
    float r;
    asm("ex2.approx.ftz.f32 %0, %1;" : "=f"(r) : "f"(x));
    return r;
}
__device__ __forceinline__ float rcp(float x) {
    float r;
    asm("rcp.approx.ftz.f32 %0, %1;" : "=f"(r) : "f"(x));
    return r;
}

__device__ __forceinline__ void pack_slice(uint32_t* a, float (&d)[32]) {
    fence_regs(d);
#pragma unroll
    for (int i = 0; i < 16; i++) a[i] = pack_bf16(d[2 * i], d[2 * i + 1]);
#pragma unroll
    for (int i = 0; i < 16; i++) asm volatile("" : "+r"(a[i])::"memory");
}
template <int J> __device__ __forceinline__ void store_slice(float (&d)[32], uint8_t* hptr) {
    fence_regs(d);
#pragma unroll
    for (int r = 0; r < 2; r++) {
        uint4 h[2];
#pragma unroll
        for (int a = 0; a < 2; a++) {
            const int o = 16 * a + 2 * r;
            h[a] = make_uint4(pack_bf16(d[o], d[o + 1]), pack_bf16(d[o + 4], d[o + 5]), pack_bf16(d[o + 8], d[o + 9]), pack_bf16(d[o + 12], d[o + 13]));
        }
        stg128(hptr + r * (kC * 2) + J * 128, h[0]);
        stg128(hptr + r * (kC * 2) + J * 128 + 64, h[1]);
    }
    __syncwarp();
}
__device__ __forceinline__ void store_p_if(const uint32_t (&pa)[16], bool cond) {
    const uint32_t t = tid_now(), row = ((t >> 1) & 48) + (t & 15);
    const uint32_t adr = kSmemBase + kOffStage + row * 128 + ((((t >> 4) & 1) ^ (t & 7)) << 4);
#pragma unroll
    for (int i = 0; i < 4; i++)
        asm volatile("{\n.reg .pred p;\nsetp.ne.u32 p, %5, 0;\n@p stmatrix.sync.aligned.m8n8.x4.shared.b16 [%4], {%0, %1, %2, %3};\n}\n"
                     :: "r"(pa[4 * i]), "r"(pa[4 * i + 1]), "r"(pa[4 * i + 2]), "r"(pa[4 * i + 3]), "r"(adr ^ (i << 5)), "r"((uint32_t)cond) : "memory");
}
__device__ __forceinline__ void last_window(__nv_bfloat16* out, int win) {
    constexpr uint32_t dWv = ((kSmemBase + kOffWv) >> 4) | (1u << 16);
    asm volatile("fence.proxy.async.shared::cta;" ::: "memory");
    const uint32_t w = wg_uniform();
    const uint32_t dXt = desc_xt(w);
    constexpr uint32_t dP = ((kSmemBase + kOffStage) >> 4) | (1u << 16);
    float u0[32], u1[32], u2[32];
    uint32_t fa[48];
    const bool help = (win & kHelp) != 0;
    uint8_t* hptr = out_address(out, out_pos(win)) + (help ? 256 : 0);
    const uint32_t dW0 = dWv + (help ? 2 * 8192 / 16 : 0);
    asm volatile("" : "+l"(hptr) :: "memory");
    ring_wait();
    wg_fence();
    Gemm3s<0, 3>::run(u0, dP, dXt); wg_commit();
    Gemm3s<1, 3>::run(u1, dP, dXt); wg_commit();
    Gemm3s<2, 3>::run(u2, dP, dXt); wg_commit();
    wg_wait2();
    pack_slice(fa, u0);
    wg_fence();
    Gemm4s<0, 0, 3>::run(u0, fa, dW0); wg_commit();
    wg_wait2();
    pack_slice(fa + 16, u1);
    wg_fence();
    Gemm4s<0, 4, 7>::run(u0, fa, dW0); wg_commit();
    wg_wait2();
    pack_slice(fa + 32, u2);
    wg_fence();
    Gemm4s<0, 8, 11>::run(u0, fa, dW0); wg_commit();
    if (help) {
        wg_wait0();
        fence_regs(fa);
        store_slice<0>(u0, hptr);
    } else {
        wg_fence();
        Gemm4s<1, 0, 5>::run(u1, fa, dWv); wg_commit();
        wg_wait1();
        store_slice<0>(u0, hptr);
        wg_fence();
        Gemm4s<1, 6, 11>::run(u1, fa, dWv); wg_commit();
        if ((win & 4095) >= kNWin - SHARED) {
            wg_wait0();
            fence_regs(fa);
            store_slice<1>(u1, hptr);
        } else {
            wg_fence();
            Gemm4s<2, 0, 5>::run(u2, fa, dWv); wg_commit();
            wg_wait1();
            store_slice<1>(u1, hptr);
            wg_fence();
            Gemm4s<2, 6, 11>::run(u2, fa, dWv); wg_commit();
            wg_wait0();
            fence_regs(fa);
            store_slice<2>(u2, hptr);
        }
    }
}

__device__ __forceinline__ int fold_offset(int n, int k0, int q) {
    const int u = ((k0 & 63) >> 3) + (q >> 1);
    return (k0 >> 6) * 24576 + (q & 1) * 8 + n * 128 + ((u ^ (n & 7)) << 4);
}
__device__ __forceinline__ void mma16816x2(float (&c)[4], float (&d)[4], const uint32_t (&a)[4], const uint32_t (&b)[4]) {
    asm volatile("mma.sync.aligned.m16n8k16.row.col.f32.bf16.bf16.f32 {%0,%1,%2,%3}, {%8,%9,%10,%11}, {%12,%13}, {%0,%1,%2,%3};\n"
                 "mma.sync.aligned.m16n8k16.row.col.f32.bf16.bf16.f32 {%4,%5,%6,%7}, {%8,%9,%10,%11}, {%14,%15}, {%4,%5,%6,%7};"
                 : "+f"(c[0]), "+f"(c[1]), "+f"(c[2]), "+f"(c[3]), "+f"(d[0]), "+f"(d[1]), "+f"(d[2]), "+f"(d[3])
                 : "r"(a[0]), "r"(a[1]), "r"(a[2]), "r"(a[3]), "r"(b[0]), "r"(b[1]), "r"(b[2]), "r"(b[3]));
}
__device__ __forceinline__ void cp_async16(uint32_t dst, const void* src) {
    asm volatile("cp.async.cg.shared.global [%0], [%1], 16;" ::"r"(dst), "l"(src) : "memory");
}
template <bool kTrans> __device__ __forceinline__ void ldsm4(uint32_t (&r)[4], uint32_t addr) {
    if constexpr (kTrans)
        asm volatile("ldmatrix.sync.aligned.m8n8.x4.trans.shared.b16 {%0, %1, %2, %3}, [%4];" : "=r"(r[0]), "=r"(r[1]), "=r"(r[2]), "=r"(r[3]) : "r"(addr) : "memory");
    else
        asm volatile("ldmatrix.sync.aligned.m8n8.x4.shared.b16 {%0, %1, %2, %3}, [%4];" : "=r"(r[0]), "=r"(r[1]), "=r"(r[2]), "=r"(r[3]) : "r"(addr) : "memory");
}
__device__ __forceinline__ uint32_t nonzero(uint32_t w) { return w ? w : 0x80000000u; }
template <bool vo>
__device__ __forceinline__ void fold_job(Scratch* sc, const __nv_bfloat16* __restrict__ wqkv, const __nv_bfloat16* __restrict__ wo,
                                         int job, int warp, int lane) {
    constexpr int nw = vo ? 3 : 2;
    const int nb = vo ? job >> 2 : (job * 43) >> 8;
    const int n0 = nb * 16, k0 = (nw * (vo ? job & 3 : job - 6 * nb) + max(warp, 1) - 1) * 16;
    const uint32_t stage = kSmemBase + kOffWv;
    if (warp != kWarmW) {
        if (vo) {
            const char* src = reinterpret_cast<const char*>(wo) + (uint32_t)(((warp * 48 + (lane >> 1)) * kC + n0 + (lane & 1) * 8) * 2);
            const uint32_t dst = stage + warp * 1536 + ((lane ^ ((lane >> 3) & 1)) << 4);
#pragma unroll
            for (int i = 0; i < 3; i++) cp_async16(dst + i * 512, src + i * 16 * kC * 2);
        }
        if (!vo || warp != 0) {
            const int row0 = warp == 0 ? n0 : k0, col0 = warp == 0 ? kC : vo ? 2 * kC : 0;
            const char* src = reinterpret_cast<const char*>(wqkv) + (uint32_t)(((row0 + (lane >> 3)) * (3 * kC) + col0 + (lane & 7) * 8) * 2);
            const uint32_t dst = stage + warp * 6144 + (lane >> 3) * 384 + (((lane & 7) ^ (lane >> 3)) << 4);
#pragma unroll
            for (int i = 0; i < 12; i++) cp_async16((dst ^ (((i / 3) & 1) << 6)) + (i / 3) * 1536 + (i % 3) * 128, src + (i / 3) * 4 * 3 * kC * 2 + (i % 3) * 128);
        }
    }
    const int g = lane >> 2, q = lane & 3, mi = lane >> 3, r8 = lane & 7;
    const int row = 4 * (r8 >> 1) + (r8 & 1) + 2 * (mi >> 1), c = r8 + 8 * (mi >> 1);
    uint32_t baseB = stage + warp * 6144 + row * 384 + (((mi & 1) ^ (row & 7)) << 4);
    uint32_t baseA = stage + (vo ? ((2 * c + (mi & 1)) ^ ((c >> 2) & 1)) << 4 : (r8 + 8 * (mi & 1)) * 384 + (((mi >> 1) ^ r8) << 4));
    const int ch = n0 + g;
    const int n = vo ? 32 * (ch >> 5) + 8 * ((ch >> 1) & 3) + 2 * ((ch >> 3) & 3) + (ch & 1) : ch;
    char* img = reinterpret_cast<char*>(sc->wfold) + (vo ? kWBytes : 0);
    char* dst0 = img + fold_offset(n, k0, q);
    char* dst1 = img + fold_offset(n + (vo ? 2 : 8), k0, q);
    asm volatile("" : "+r"(baseA), "+r"(baseB), "+l"(dst0), "+l"(dst1));
    if (warp != kWarmW) {
        asm volatile("cp.async.wait_all;" ::: "memory");
        if (warp == 0) {
            asm volatile("bar.arrive 13, %0;" ::"n"(32 * nw + 32) : "memory");
            return;
        }
        asm volatile("bar.sync 13, %0;" ::"n"(32 * nw + 32) : "memory");
    }
    float c0[4] = {0.f, 0.f, 0.f, 0.f}, c1[4] = {0.f, 0.f, 0.f, 0.f}, c2[4] = {0.f, 0.f, 0.f, 0.f}, c3[4] = {0.f, 0.f, 0.f, 0.f};
    uint32_t A[12][4], B[12][4];
#pragma unroll
    for (int ks = 0; ks < 12; ks++) {
        ldsm4<vo>(A[ks], vo ? baseA + ks * 512 : (baseA ^ ((ks & 3) << 5)) + (ks >> 2) * 128);
        ldsm4<false>(B[ks], (baseB ^ ((ks & 3) << 5)) + (ks >> 2) * 128);
    }
#pragma unroll
    for (int ks = 0; ks < 12; ks += 2) {
        mma16816x2(c0, c1, A[ks], B[ks]);
        mma16816x2(c2, c3, A[ks + 1], B[ks + 1]);
    }
#pragma unroll
    for (int i = 0; i < 4; i++) { c0[i] += c2[i]; c1[i] += c3[i]; }
    asm volatile("{\n.reg .pred p;\nsetp.ne.u32 p, %6, %7;\n@p st.global.v2.u32 [%0], {%2, %3};\n@p st.global.v2.u32 [%1], {%4, %5};\n}\n"
                 ::"l"(dst0), "l"(dst1),
                   "r"(nonzero(pack_bf16(c0[0], c0[1]))), "r"(nonzero(pack_bf16(c1[0], c1[1]))), "r"(nonzero(pack_bf16(c0[2], c0[3]))), "r"(nonzero(pack_bf16(c1[2], c1[3]))),
                   "r"(warp), "n"(kWarmW) : "memory");
}
constexpr uint32_t kWarpsQK = 0x17;

__device__ __forceinline__ bool bar_or(uint32_t id, uint32_t n, bool pred) {
    uint32_t r;
    asm volatile("{\n.reg .pred p, q;\nsetp.ne.u32 q, %3, 0;\nbar.red.or.pred p, %1, %2, q;\nselp.u32 %0, 1, 0, p;\n}\n"
                 : "=r"(r) : "r"(id), "r"(n), "r"((uint32_t)pred) : "memory");
    return r != 0;
}
template <int N = 6> __device__ __forceinline__ bool chunk_incomplete(uint32_t base) {
    const uint32_t t = tid_now(), r = (t >> 2) & 7;
    const uint32_t adr = base + (((t >> 5) & 3) * 8 * N + r) * 128 + (t & 3) * 32 + r * 4;
    uint32_t m = ~0u;
#pragma unroll
    for (int j = 0; j < N; j++) {
        uint32_t v;
        asm volatile("ld.shared.u32 %0, [%1];" : "=r"(v) : "r"(adr + j * 1024) : "memory");
        m = min(m, v);
    }
    return m == 0;
}
__device__ __forceinline__ void load_image(uint32_t dst, const void* src, uint32_t bar) {
    mbar_expect_tx(bar, kWBytes);
#pragma unroll
    for (int c = 0; c < 3; c++) bulk_load(dst + c * 24576, reinterpret_cast<const char*>(src) + c * 24576, 24576, bar);
}
__device__ __forceinline__ void repair_image(uint32_t dst, const void* src, uint32_t bar, uint32_t par) {
    uint32_t tries = 0;
    bool bad;
    do {
        if (((tid_now() >> 5) & 3) == 0) {
            if (elect_one()) {
                asm volatile("fence.proxy.async;" ::: "memory");
                load_image(dst, src, bar);
            }
            __syncwarp();
        }
        mbar_wait(bar, par);
        par ^= 1;
        bad = chunk_incomplete(dst) | chunk_incomplete(dst + 24576) | chunk_incomplete(dst + 2 * 24576);
        if (++tries > (1u << 16)) __trap();
    } while (bar_or((tid_now() >> 7) + 1, 128, bad));
}
__device__ __forceinline__ void count_image(Scratch* sc) {
    asm volatile("red.relaxed.gpu.global.inc.u32 [%0], %1;" ::"l"(sc->cnt), "r"(3 * nctaid_now() - 1) : "memory");
}
__device__ __forceinline__ uint32_t ld_acquire(const uint32_t* p) {
    uint32_t v;
    asm volatile("ld.acquire.gpu.global.u32 %0, [%1];" : "=r"(v) : "l"(p) : "memory");
    return v;
}
__device__ __noinline__ void clear_images(Scratch* sc) {
    const uint32_t g = gridDim.x, t = threadIdx.x & 127;
    if (t == 0) {
        uint32_t spins = 0;
        while (ld_acquire(sc->cnt) < 2 * g) { if (++spins > (1u << 24)) __trap(); }
    }
    asm volatile("bar.sync %0, 128;" ::"r"((threadIdx.x >> 7) + 1) : "memory");
    for (uint32_t i = blockIdx.x * 64 + t; t < 64 && i < 2 * kWBytes / 16; i += g * 64) sc->wfold[i] = make_uint4(0, 0, 0, 0);
    if (t == 0) count_image(sc);
}
__device__ __forceinline__ void prefetch_x(const CUtensorMap* tm, int win) {
    const int wh = win >> 6, ww = win & 63;
    asm volatile("cp.async.bulk.prefetch.tensor.3d.L2.global.tile [%0, {%1, %2, %3}];"
                 ::"l"(tm), "r"(0), "r"(ww * 8), "r"(wh * 8) : "memory");
}
__device__ __forceinline__ void prefetch_x_chunk(const CUtensorMap* tm, int win, int chunk) {
    asm volatile("cp.async.bulk.prefetch.tensor.5d.L2.global.tile [%0, {%1, %2, %4, %4, %3}];"
                 ::"l"(tm), "r"(chunk * 64), "r"((win & 63) * 4), "r"((win >> 6) * 4), "r"(0) : "memory");
}

__device__ __forceinline__ void prefetch_ahead_of(const CUtensorMap* tmp, int w, int G) {
    auto lead = [&](int v) {
        int down = max(((kNWin - PF_END - v) * PF_DOWN) >> 8, PF_MIN);
        return min(min(G + (((v - kNWG * G) * PF_UP) >> 8), PF_LEAD), down);
    };
    const int hi = w + lead(w);
    int lo = max(w - 1 + lead(w - 1), w) + 1;
#pragma unroll 1
    for (; lo <= hi && lo < kNWin; lo++) prefetch_x(tmp, lo);
}

__device__ __forceinline__ void publish(uint32_t ticket, int G) {
    constexpr uint32_t sbase = kSmemBase;
    if (((tid_now() >> 5) & 3) == 0) {
        if ((tid_now() & 31) == 0) {
            uint32_t nxt = 2 * kNWG * G + ticket;
            if (nxt >= kNWin) nxt = nxt < kNWin + SHARED ? (2 * kNWin - 1 - nxt) | kHelp : kDone;
            if (nxt == kDone) {
                uint32_t p0, p1, p2, p3;
                asm volatile("ld.shared.v4.u32 {%0, %1, %2, %3}, [%4];" : "=r"(p0), "=r"(p1), "=r"(p2), "=r"(p3) : "r"(sbase + kOffBar + 64) : "memory");
                nxt = kDone + (p0 >> 30) + (p1 >> 30) + (p2 >> 30);
            }
            asm volatile("st.shared.u32 [%0], %1;" ::"r"(sbase + kOffBar + 64 + 4 * (tid_now() >> 7)), "r"(nxt) : "memory");
        }
        __syncwarp();
        asm volatile("bar.arrive %0, 128;" ::"r"((tid_now() >> 7) + 4) : "memory");
    }
}

template <bool kFewSMs>
__global__ void __launch_bounds__(kThreads, 1)
swin_attn_kernel(const __nv_bfloat16* __restrict__ wqkv, const __nv_bfloat16* __restrict__ wo, const __nv_bfloat16* __restrict__ xin, Scratch* sc, uint32_t* tickets,
                 const int G, const uint32_t trk, __nv_bfloat16* __restrict__ out, const uint32_t last_ticket,
                 const __grid_constant__ CUtensorMap tmx, const __grid_constant__ CUtensorMap tmp, const __grid_constant__ CUtensorMap tmo) {
    extern __shared__ uint8_t smem_raw[];
    constexpr uint32_t sbase = kSmemBase;
    const uint32_t t_start = clock_now();
    asm volatile("{\n.reg .pred p, q;\n.reg .b32 i, j;\n.reg .b64 a, b;\nmad.lo.u32 i, %2, 14, %3;\nsetp.lt.u32 p, %3, 14;\nsetp.lt.and.u32 p, i, 1728, p;\n"
                 "mad.wide.u32 a, i, 128, %0;\n@p prefetch.global.L2 [a];\n"
                 "mad.lo.u32 j, %2, 5, %3;\nsetp.lt.u32 q, %3, 5;\nsetp.lt.and.u32 q, j, 576, q;\n"
                 "mad.wide.u32 b, j, 128, %1;\n@q prefetch.global.L2 [b];\n}\n" ::"l"(wqkv), "l"(wo), "r"(blockIdx.x), "r"(threadIdx.x) : "memory");
    if (smem_u32(smem_raw) != kSmemBase) __trap();
    const int tid = threadIdx.x, lane = tid & 31;
    const uint32_t warpu = __reduce_or_sync(0xffffffffu, (uint32_t)tid >> 5), wgu = warpu >> 2;
    const int warp = (int)warpu, wg = (int)wgu;
    const uint32_t bar_full = sbase + kOffBar + 8 * wg;
    constexpr uint32_t bar_m = sbase + kOffBarM, bar_w1 = sbase + kOffBar + 40;
    auto bar_v = [](int c) { return bar_w1 + 16 - 8 * c; };
    int win = wg * G + blockIdx.x;

    const int direct = blockIdx.x >= X0_LATE ? 1 : 2;
    if (!kFewSMs && blockIdx.x < kJobsM && ((kWarpsQK >> warp) & 1)) fold_job<false>(sc, wqkv, wo, blockIdx.x, warp, lane);
    if (warp == 10) {
        auto x_lines = [&](int c) {
            const int w = (c / 3) * G + blockIdx.x;
            return reinterpret_cast<const char*>(xin) + (uint32_t)((((w >> 6) * 8 + (lane >> 3)) * kHW + (w & 63) * 8 + (lane & 7)) * (kC * 2) + (c % 3) * 128);
        };
        if (elect_one()) {
            asm volatile("prefetch.tensormap [%0];" ::"l"(&tmx) : "memory");
#pragma unroll
            for (int w = 0; w < kNWG; w++) mbar_init(sbase + kOffBar + 8 * w, 1);
            mbar_init(sbase + kOffBar + 24, 1);
            mbar_init(sbase + kOffBar + 88, 1);
            mbar_init(sbase + kOffBar + 96, 1);
            mbar_init(sbase + kOffBar + 104, 1);
            mbar_init(sbase + kOffBar + 112, 1);
#pragma unroll
            for (int c = 0; c < 3; c++) mbar_init(bar_v(c), 1);
#pragma unroll
            for (int i = 0; i < 6; i++) mbar_init(bar_m + 8 * i, 1);
            asm volatile("st.shared.v4.u32 [%0], {%1, %1, %1, %1};" ::"r"(sbase + kOffBar + 64), "r"(0) : "memory");
            asm volatile("fence.mbarrier_init.release.cluster;" ::: "memory");
            asm volatile("mbarrier.arrive.shared::cta.b64 _, [%0];" ::"r"(sbase + kOffBar) : "memory");
        }
        __syncwarp();
        asm volatile("bar.arrive 15, 64;" ::: "memory");
        asm volatile("bar.arrive 0, %0;" ::"n"(kThreads) : "memory");
        const uint32_t due = (blockIdx.x * TRK_Q) >> 8;
        if (elect_one()) {
#pragma unroll
            for (int c = 0; c < 2; c++) {
                if (c >= direct) break;
                while (clock_now() - t_start < TRK_T0 + (due + c * TRK_S) / 3) {}
                tma_load_x_chunk(sbase + kOffX + c * 8192, &tmx, bar_m + 16 * c, blockIdx.x, c);
            }
        }
        __syncwarp();
#pragma unroll 1
        for (int c = direct; c < 3 * kNWG; c++) {
            const char* p = x_lines(c);
            while (clock_now() - t_start < TRK_T0 + (due + c * TRK_S) / 3) {}
            asm volatile("prefetch.global.L2 [%0];\nprefetch.global.L2 [%0 + %1];" ::"l"(p), "n"(4 * kHW * kC * 2) : "memory");
        }
        asm volatile("prefetch.tensormap [%0];" ::"l"(&tmp) : "memory");
        asm volatile("prefetch.tensormap [%0];" ::"l"(&tmo) : "memory");
    }
    int role = warp;
    asm volatile("" : "+r"(role));
    if (role == 10) {
    } else if (warp > kWarmW) {
        if (warp == 11) {
            asm volatile("bar.sync 15, 64;" ::: "memory");
            asm volatile("bar.arrive 0, %0;" ::"n"(kThreads) : "memory");
            if (elect_one()) {
                const char* img = reinterpret_cast<const char*>(sc->wfold);
#pragma unroll
                for (int i = 0; i < 6; i++) mbar_expect_tx(bar_m + 8 * i, 12288 + (i & 1 ? 0 : 8192));
#pragma unroll
                for (int c = 0; c < 3; c++) mbar_expect_tx(sbase + kOffBar + (c == 0 ? 8 : 80 + 8 * c), 8192);
                while (clock_now() - t_start < REQ_T) {}
#pragma unroll
                for (int i = 0; i < 6; i++) {
                    if (i >= 2 * direct && !(i & 1)) tma_load_x_chunk(sbase + kOffX + (i >> 1) * 8192, &tmx, bar_m + 8 * i, blockIdx.x, i >> 1);
                    bulk_load(sbase + kOffWm + i * 12288, img + i * 12288, 12288, bar_m + 8 * i);
                }
                mbar_wait(bar_m + 8, 0);
#pragma unroll
                for (int c = 0; c < 3; c++)
                    tma_load_x_chunk(sbase + kOffX + kXBytes + c * 8192, &tmx, sbase + kOffBar + (c == 0 ? 8 : 80 + 8 * c), G + blockIdx.x, c);
            }
            __syncwarp();
        } else {
            asm volatile("bar.sync 0, %0;" ::"n"(kThreads) : "memory");
            if (warp == 9) {
                if (elect_one()) {
                    while (clock_now() - t_start < REQ_TV) {}
                    mbar_wait(bar_m + 24, 0);
                    asm volatile("fence.proxy.async.shared::cta;" ::: "memory");
#pragma unroll
                    for (int c = 0; c < 3; c++) {
                        mbar_expect_tx(bar_v(c), 24576);
                        bulk_load(sbase + kOffWv + c * 24576, reinterpret_cast<const char*>(sc->wfold) + kWBytes + c * 24576, 24576, bar_v(c));
                    }
#pragma unroll
                    for (int c = 0; c < 3; c++) {
                        const uint32_t bar = sbase + kOffBar + (c == 0 ? 16 : 96 + 8 * c);
                        mbar_expect_tx(bar, 8192);
                        tma_load_x_chunk(sbase + kOffX + 2 * kXBytes + c * 8192, &tmx, bar, 2 * G + blockIdx.x, c);
                    }
                }
                __syncwarp();
            }
        }
    } else {
        if constexpr (kFewSMs) {
#pragma unroll 1
            for (int j = blockIdx.x; j < kJobs; j += G) {
                if (j >= kJobsM) fold_job<true>(sc, wqkv, wo, j - kJobsM, warp, lane);
                else if ((kWarpsQK >> warp) & 1) fold_job<false>(sc, wqkv, wo, j, warp, lane);
                asm volatile("bar.sync 14, %0;" ::"n"(32 * kWarmW + 32) : "memory");
            }
        } else {
            if (blockIdx.x - kJobsM < kJobs - kJobsM) fold_job<true>(sc, wqkv, wo, blockIdx.x - kJobsM, warp, lane);
        }
        asm volatile("bar.sync 0, %0;" ::"n"(kThreads) : "memory");
    }
    bool bad_v = false;
    if (wg == 1) {
        mbar_wait(bar_m + 8 * (warp & 3), 0);
        bool bad = chunk_incomplete<12>(sbase + kOffWm);
#pragma unroll
        for (int i = 4; i < 6; i++) {
            mbar_wait(bar_m + 8 * i, 0);
            bad |= chunk_incomplete<3>(sbase + kOffWm + i * 12288);
        }
        bad = bar_or(2, 128, bad);
        if (bad) {
            repair_image(sbase + kOffWm, sc->wfold, sbase + kOffBar + 24, 0);
        }
        asm volatile("st.shared.u32 [%0], %1;" ::"r"(sbase + kOffBar + 80), "r"((uint32_t)bad) : "memory");
        asm volatile("bar.arrive 11, 256;" ::: "memory");
    } else if (wg == 2) {
#pragma unroll
        for (int c = 0; c < 2; c++) {
            mbar_wait(bar_v(c), 0);
            bad_v |= chunk_incomplete(sbase + kOffWv + c * 24576);
        }
    }

    constexpr uint32_t dWm = ((sbase + kOffWm) >> 4) | (1u << 16);
    constexpr uint32_t dWv = ((sbase + kOffWv) >> 4) | (1u << 16);
    const float cs = 0.07216878364870322f * 1.4426950408889634f;
    mbar_wait(wg == 0 ? bar_m : bar_full, 0);

    uint4 hv[12];
    uint32_t pos;
    float acc[96];
    asm volatile("" : "+r"(win));
    uint32_t ticket = win - kNWG * G;
    float s[32];
    {
        const uint32_t dX = desc_x(wg_uniform());
        uint32_t fa[48];
        if (wg == 0) {
            uint32_t redo = 0;
            do {
                float ta[48], tb[48];
                wg_fence();
                Gemm1h<0, 0>::run(ta, dX, dWm);
                mbar_wait(bar_m + 8, 0);
                wg_fence();
                Gemm1h<1, 0>::run(tb, dX, dWm);
                mbar_wait(bar_m + 16, 0);
                wg_fence();
                Gemm1h<0, 1>::run(ta, dX, dWm);
                mbar_wait(bar_m + 24, 0);
                wg_fence();
                Gemm1h<1, 1>::run(tb, dX, dWm);
                mbar_wait(bar_m + 32, 0);
                wg_fence();
                Gemm1h<0, 2>::run(ta, dX, dWm);
                wg_commit();
                mbar_wait(bar_m + 40, 0);
                wg_fence();
                Gemm1h<1, 2>::run(tb, dX, dWm);
                wg_commit();
                wg_wait1();
                fence_regs(ta);
#pragma unroll
                for (int i = 0; i < 24; i++) fa[i] = pack_bf16(ta[2 * i], ta[2 * i + 1]);
#pragma unroll
                for (int i = 0; i < 24; i++) asm volatile("" : "+r"(fa[i])::"memory");
                wg_fence();
                Gemm2p<0, 5>::run(s, fa, dX);
                wg_commit();
                wg_wait1();
                fence_regs(tb);
#pragma unroll
                for (int i = 0; i < 24; i++) fa[24 + i] = pack_bf16(tb[2 * i], tb[2 * i + 1]);
#pragma unroll
                for (int i = 24; i < 48; i++) asm volatile("" : "+r"(fa[i])::"memory");
                wg_fence();
                Gemm2p<6, 11>::run(s, fa, dX);
                wg_commit();
                if (!redo) {
                    ring_pass();
                    asm volatile("bar.sync 11, 256;" ::: "memory");
                    asm volatile("ld.shared.u32 %0, [%1];" : "=r"(redo) : "r"(sbase + kOffBar + 80) : "memory");
                    publish(ticket, G);
                    asm volatile("bar.arrive 15, 256;" ::: "memory");
                } else {
                    redo = 0;
                }
                redo = __reduce_or_sync(0xffffffffu, redo);
                wg_wait0();
                fence_regs(s);
                fence_regs(fa);
            } while (redo);
        } else {
            ring_wait();
            wg_fence();
            Gemm1<0, 3>::run(acc, dX, dWm);
            if (wg == 2) {
                mbar_wait(bar_v(2), 0);
                bad_v |= chunk_incomplete(sbase + kOffWv + 2 * 24576);
            }
            const uint32_t bar_c1 = sbase + kOffBar + 72 + 16 * wg;
            mbar_wait(bar_c1, 0);
            wg_fence();
            Gemm1<4, 7>::run(acc, dX, dWm);
            mbar_wait(bar_c1 + 8, 0);
            wg_fence();
            Gemm1<8, 11>::run(acc, dX, dWm);
            wg_commit();
            if (wg == 2) bad_v = bar_or(3, 128, bad_v);
            if (!bad_v) asm volatile("bar.arrive 8, 256;" ::: "memory");
            if (warp == 5) {
                if (elect_one()) prefetch_x(&tmp, kNWG * G + blockIdx.x);
                __syncwarp();
            }
            if (!bad_v && (tid & 127) == 0) count_image(sc);
            wg_wait0();
            fence_regs(acc);
            if (bad_v) {
                repair_image(sbase + kOffWv, reinterpret_cast<const char*>(sc->wfold) + kWBytes, bar_w1, 1);
                asm volatile("bar.arrive 8, 256;" ::: "memory");
                if (tid == 256) count_image(sc);
            }
#pragma unroll
            for (int i = 0; i < 48; i++) fa[i] = pack_bf16(acc[2 * i], acc[2 * i + 1]);
            fence_regs(fa);
            wg_fence();
            ring_wait();
            Gemm2<11>::run(s, fa, dX);
            wg_commit();
            publish(ticket, G);
            asm volatile("bar.arrive 15, 256;" ::: "memory");
            wg_wait0();
            fence_regs(s);
            fence_regs(fa);
        }
        __syncwarp();
    }

    while (true) {
        uint32_t fa[48];
        uint32_t pa[16];
        {
            float a0[8], a1[8];
#pragma unroll
            for (int j = 0; j < 8; j++) { a0[j] = fmaxf(s[4 * j], s[4 * j + 1]); a1[j] = fmaxf(s[4 * j + 2], s[4 * j + 3]); }
#pragma unroll
            for (int d = 4; d > 0; d >>= 1)
#pragma unroll
                for (int j = 0; j < d; j++) { a0[j] = fmaxf(a0[j], a0[j + d]); a1[j] = fmaxf(a1[j], a1[j + d]); }
            float m0 = a0[0], m1 = a1[0];
            m0 = fmaxf(m0, __shfl_xor_sync(0xffffffffu, m0, 1));
            m1 = fmaxf(m1, __shfl_xor_sync(0xffffffffu, m1, 1));
            m0 = fmaxf(m0, __shfl_xor_sync(0xffffffffu, m0, 2));
            m1 = fmaxf(m1, __shfl_xor_sync(0xffffffffu, m1, 2));
            m0 *= cs; m1 *= cs;
            float l0 = 0.f, l1 = 0.f;
#pragma unroll
            for (int j = 0; j < 8; j++) {
                s[4 * j]     = ex2(fmaf(s[4 * j], cs, -m0));
                s[4 * j + 1] = ex2(fmaf(s[4 * j + 1], cs, -m0));
                s[4 * j + 2] = ex2(fmaf(s[4 * j + 2], cs, -m1));
                s[4 * j + 3] = ex2(fmaf(s[4 * j + 3], cs, -m1));
                l0 += s[4 * j] + s[4 * j + 1];
                l1 += s[4 * j + 2] + s[4 * j + 3];
            }
            l0 += __shfl_xor_sync(0xffffffffu, l0, 1);
            l1 += __shfl_xor_sync(0xffffffffu, l1, 1);
            l0 += __shfl_xor_sync(0xffffffffu, l0, 2);
            l1 += __shfl_xor_sync(0xffffffffu, l1, 2);
            const float r0 = rcp(l0), r1 = rcp(l1);
#pragma unroll
            for (int j = 0; j < 8; j++) {
                pa[2 * j]     = pack_bf16(s[4 * j] * r0, s[4 * j + 1] * r0);
                pa[2 * j + 1] = pack_bf16(s[4 * j + 2] * r1, s[4 * j + 3] * r1);
            }
        }

        const uint32_t wu = __reduce_or_sync(0xffffffffu, tid_now() >> 5);
        const uint32_t dXt = desc_xt(wu >> 2);
        if ((wu & 3) != 0) asm volatile("bar.sync %0, 128;" ::"r"((wu >> 2) + 4) : "memory");
        uint32_t pub;
        asm volatile("ld.shared.u32 %0, [%1];" : "=r"(pub) : "r"(sbase + kOffBar + 64 + 4 * (tid_now() >> 7)) : "memory");
        const int nxt = (int)__reduce_or_sync(0xffffffffu, pub);
        store_p_if(pa, nxt == (int)kDone + kNWG - 1);
        if (nxt == (int)kDone + kNWG - 1) {
            last_window(out, win);
            asm volatile("exit;");
            __builtin_unreachable();
        }
        fence_regs(pa);
        wg_fence();
        ring_wait();
        Gemm3<3>::run(acc, pa, dXt);
        wg_commit();
        if constexpr (PASS3 == 3) ring_pass();
        wg_wait0();
        fence_regs(acc);
        fence_regs(pa);

        if (((tid_now() >> 5) & 3) == 0) {
            asm volatile("bar.sync %0, 128;" ::"r"((tid_now() >> 7) + 1) : "memory");
            if (elect_one()) {
                const uint32_t wgl = tid_now() >> 7;
                const uint32_t bar = sbase + kOffBar + 8 * wgl;
                if (nxt < (int)kDone) {
                    mbar_expect_tx(bar, kXBytes);
                    tma_load_x_hint(sbase + kOffX + wgl * kXBytes, &tmx, bar, nxt & 4095, nxt >= kNWin - EF_LAST);
                    uint32_t again;
                    asm volatile("ld.volatile.shared.u32 %0, [%1];" : "=r"(again) : "r"(sbase + kOffBar + 64 + 4 * wgl) : "memory");
                    prefetch_ahead_of(&tmp, (int)again, G);
                }
            }
            __syncwarp();
        } else {
            asm volatile("bar.arrive %0, 128;" ::"r"((tid_now() >> 7) + 1) : "memory");
        }
#pragma unroll
        for (int i = 0; i < 48; i++) fa[i] = pack_bf16(acc[2 * i], acc[2 * i + 1]);

        asm volatile("{\n.reg .pred p;\nsetp.lt.s32 p, %5, 0;\n@p st.volatile.shared.v4.b32 [%4], {%0, %1, %2, %3};\n}\n"
                     :: "r"(fa[44]), "r"(fa[45]), "r"(fa[46]), "r"(fa[47]), "r"(sbase + kOffBar + 64), "r"(nxt) : "memory");
        fence_regs(fa);
        wg_fence();
        ring_wait();
        Gemm4<0, 1>::run(acc, fa, dWv);
        wg_commit();
        Gemm4<2, 10>::run(acc, fa, dWv);
        wg_commit();
        wg_wait1();
        uint32_t fl[4];
        uint32_t zero;
        asm volatile("ld.volatile.shared.u32 %0, [%1];" : "=r"(zero) : "r"(sbase + kOffBar + 76) : "memory");
#pragma unroll
        for (int i = 0; i < 4; i++) fl[i] = fa[44 + i] ^ zero;
        if constexpr (PASS4 == 10) ring_pass();
        wg_fence();
        wg192_rs<false, 0, koff(11, 24576)>(acc, fl, dWv);
        wg_commit();
        if constexpr (PASS4 == 11) ring_pass();
        pos = out_pos(win ^ zero);
        win = nxt | (~win & kPhase);
        const uint32_t dX = desc_x(__reduce_or_sync(0xffffffffu, (tid_now() >> 7) ^ zero));
        asm volatile("" : "+r"(pos) :: "memory");
        wg_wait0();
        fence_regs(acc);
        fence_regs(fa);
        fence_regs(fl);

#pragma unroll
        for (int a = 0; a < 6; a++) {
            hv[2 * a].x     = pack_bf16(acc[16 * a + 0], acc[16 * a + 1]);
            hv[2 * a].y     = pack_bf16(acc[16 * a + 4], acc[16 * a + 5]);
            hv[2 * a].z     = pack_bf16(acc[16 * a + 8], acc[16 * a + 9]);
            hv[2 * a].w     = pack_bf16(acc[16 * a + 12], acc[16 * a + 13]);
            hv[2 * a + 1].x = pack_bf16(acc[16 * a + 2], acc[16 * a + 3]);
            hv[2 * a + 1].y = pack_bf16(acc[16 * a + 6], acc[16 * a + 7]);
            hv[2 * a + 1].z = pack_bf16(acc[16 * a + 10], acc[16 * a + 11]);
            hv[2 * a + 1].w = pack_bf16(acc[16 * a + 14], acc[16 * a + 15]);
        }
        if (win < (int)kDone) mbar_wait(sbase + kOffBar + 8 * (tid_now() >> 7), (win >> 16) & 1);
        if (win >= (int)kDone) break;
        wg_fence();
        ring_wait();
        Gemm1<0, PASS1>::run(acc, dX, dWm);
        if constexpr (PASS1 < 11) {
            ring_pass();
            Gemm1<PASS1 + 1, 11>::run(acc, dX, dWm);
        }
        wg_commit();
        if constexpr (PASS1 == 11) ring_pass();
        ticket = draw_ticket(tickets, last_ticket);
        asm volatile("bar.sync 15, 256;" ::: "memory");
        stage_window<0>(hv, &tmo, pos, win);
        wg_wait0();
        fence_regs(acc);
#pragma unroll
        for (int i = 0; i < 48; i++) fa[i] = pack_bf16(acc[2 * i], acc[2 * i + 1]);

        fence_regs(fa);
        wg_fence();
        ring_wait();
        Gemm2<11>::run(s, fa, dX);
        wg_commit();
        if constexpr (PASS2 == 11) ring_pass();
        publish(ticket, G);
        asm volatile("cp.async.bulk.wait_group.read 0;" ::: "memory");
        asm volatile("bar.arrive 15, 256;" ::: "memory");
        wg_wait0();
        fence_regs(s);
        fence_regs(fa);
    }
    if ((win & 3) == 0) {
        const uint32_t buf = sbase + kOffX + (tid_now() >> 7) * kXBytes + ((tid_now() >> 5) & 3) * 2048;
        asm volatile("bar.sync %0, 128;" ::"r"((tid_now() >> 7) + 1) : "memory");
        ring_wait();
        ring_pass();
        stage_put<0>(hv, buf);
        stage_send(&tmo, pos, 0, buf);
        stage_put<1>(hv, buf + 8192);
        stage_send(&tmo, pos, 1, buf + 8192);
        stage_put<2>(hv, buf + 2 * 8192);
        stage_send(&tmo, pos, 2, buf + 2 * 8192);
        clear_images(sc);
        asm volatile("bar.sync 15, 256;" ::: "memory");
        stage_wait();
    } else {
        uint8_t* hptr = out_address(out, pos);
        store_tail<0>(hv, hptr, clock_now());
    }
}

typedef CUresult (*EncodeTiledFn)(CUtensorMap*, CUtensorMapDataType, cuuint32_t, void*, const cuuint64_t*,
                                  const cuuint64_t*, const cuuint32_t*, const cuuint32_t*, CUtensorMapInterleave,
                                  CUtensorMapSwizzle, CUtensorMapL2promotion, CUtensorMapFloatOOBfill);

}

extern "C" void kernel_launch(void* const* d_in, const int* in_sizes, int n_in, void* d_out, int out_size) {
    (void)in_sizes; (void)n_in; (void)out_size;
    const __nv_bfloat16* x    = (const __nv_bfloat16*)d_in[0];
    const __nv_bfloat16* wqkv = (const __nv_bfloat16*)d_in[1];
    const __nv_bfloat16* wo   = (const __nv_bfloat16*)d_in[2];

    static EncodeTiledFn encode = nullptr;
    static int num_sms = 0;
    static void* scratch = nullptr;
    if (!encode) {
        void* fn = nullptr;
        cudaDriverEntryPointQueryResult qr;
        cudaGetDriverEntryPoint("cuTensorMapEncodeTiled", &fn, cudaEnableDefault, &qr);
        encode = (EncodeTiledFn)fn;
        int dev = 0;
        cudaGetDevice(&dev);
        cudaDeviceGetAttribute(&num_sms, cudaDevAttrMultiProcessorCount, dev);
        if (num_sms > kNWin / 16) num_sms = kNWin / 16;
        cudaGetSymbolAddress(&scratch, g_scratch);
        cudaFuncSetAttribute(swin_attn_kernel<false>, cudaFuncAttributeMaxDynamicSharedMemorySize, kSmemBytes);
        cudaFuncSetAttribute(swin_attn_kernel<true>, cudaFuncAttributeMaxDynamicSharedMemorySize, kSmemBytes);
    }
    CUtensorMap tmx;
    const cuuint64_t gdim[5] = {(cuuint64_t)kC, (cuuint64_t)kHW / 2, 2, 2, (cuuint64_t)kHW / 2};
    const cuuint64_t gstr[4] = {(cuuint64_t)kC * 4, (cuuint64_t)kHW * kC * 2, (cuuint64_t)kC * 2, (cuuint64_t)kHW * kC * 4};
    const cuuint32_t box[5] = {64, 4, 2, 2, 4};
    const cuuint32_t estr[5] = {1, 1, 1, 1, 1};
    encode(&tmx, CU_TENSOR_MAP_DATA_TYPE_BFLOAT16, 5, (void*)x, gdim, gstr, box, estr, CU_TENSOR_MAP_INTERLEAVE_NONE,
           CU_TENSOR_MAP_SWIZZLE_128B, CU_TENSOR_MAP_L2_PROMOTION_NONE, CU_TENSOR_MAP_FLOAT_OOB_FILL_NONE);

    CUtensorMap tmp;
    const cuuint64_t pdim[3] = {(cuuint64_t)kC, (cuuint64_t)kHW, (cuuint64_t)kHW};
    const cuuint64_t pstr[2] = {(cuuint64_t)kC * 2, (cuuint64_t)kHW * kC * 2};
    const cuuint32_t pbox[3] = {(cuuint32_t)kC, 8, 8};
    encode(&tmp, CU_TENSOR_MAP_DATA_TYPE_BFLOAT16, 3, (void*)x, pdim, pstr, pbox, estr, CU_TENSOR_MAP_INTERLEAVE_NONE,
           CU_TENSOR_MAP_SWIZZLE_NONE, CU_TENSOR_MAP_L2_PROMOTION_NONE, CU_TENSOR_MAP_FLOAT_OOB_FILL_NONE);
    CUtensorMap tmo;
    const cuuint64_t odim[5] = {64, 6, (cuuint64_t)kHW / 4, 2, (cuuint64_t)kHW};
    const cuuint64_t ostr[4] = {128, (cuuint64_t)kC * 8, (cuuint64_t)kC * 4, (cuuint64_t)kHW * kC * 2};
    const cuuint32_t obox[5] = {64, 2, 2, 2, 2};
    encode(&tmo, CU_TENSOR_MAP_DATA_TYPE_BFLOAT16, 5, d_out, odim, ostr, obox, estr, CU_TENSOR_MAP_INTERLEAVE_NONE,
           CU_TENSOR_MAP_SWIZZLE_128B, CU_TENSOR_MAP_L2_PROMOTION_NONE, CU_TENSOR_MAP_FLOAT_OOB_FILL_NONE);
    if (num_sms >= kJobs)
        swin_attn_kernel<false><<<num_sms, kThreads, kSmemBytes, cudaStreamPerThread>>>(wqkv, wo, x, (Scratch*)scratch, ((Scratch*)scratch)->ticket, num_sms, TRK_HOST, (__nv_bfloat16*)d_out, kNWin + SHARED_HOST - 1 - kNWG * num_sms, tmx, tmp, tmo);
    else
        swin_attn_kernel<true><<<num_sms, kThreads, kSmemBytes, cudaStreamPerThread>>>(wqkv, wo, x, (Scratch*)scratch, ((Scratch*)scratch)->ticket, num_sms, TRK_HOST, (__nv_bfloat16*)d_out, kNWin + SHARED_HOST - 1 - kNWG * num_sms, tmx, tmp, tmo);
}
```

```cpp
#include <cuda_runtime.h>
#include <cuda_bf16.h>
#include <cuda.h>
#include <stdint.h>

namespace {

constexpr int kC      = 192;
constexpr int kHW     = 512;
#define MAXWIN 4096
constexpr int kNWin   = MAXWIN;
constexpr int kXBytes = 64 * kC * 2;
constexpr int kWBytes = kC * kC * 2;
constexpr int kNWG    = 3;
constexpr int kThreads = kNWG * 128;
constexpr int kJobsM  = 72;
constexpr int kJobs   = 120;
constexpr int kWarmW  = 4;
#define PF_LEAD 400
#define PF_UP 114
#define PF_DOWN 39
#define PF_END 300
#define PF_MIN 135
#define EF_LAST 1000
#define TRK_T0 500
#define TRK_S 1700
#define TRK_HOST (TRK_S * 256 / num_sms)
#define TRK_Q trk
#define X0_LATE kJobsM
#define REQ_T 2340
#define REQ_TV 4200

constexpr int kOffWm  = 0;
constexpr int kOffWv  = kWBytes;
constexpr int kOffX   = 2 * kWBytes;
constexpr int kOffStage = kOffX + kNWG * kXBytes;
constexpr int kOffBar = kOffStage + 8192;
constexpr int kOffBarM = kOffBar + 128;
constexpr int kOffProf = kOffBar + 192;
constexpr int kSmemBytes = kOffProf;
constexpr uint32_t kSmemBase = 1024;

struct Scratch {
    uint4 wfold[2 * kWBytes / 16];
    uint32_t ticket[32];
    uint32_t cnt[32];
};
__device__ __align__(128) Scratch g_scratch;

__device__ __forceinline__ uint32_t smem_u32(const void* p) { return (uint32_t)__cvta_generic_to_shared(p); }

__device__ __forceinline__ void mbar_init(uint32_t bar, uint32_t count) {
    asm volatile("mbarrier.init.shared::cta.b64 [%0], %1;" ::"r"(bar), "r"(count) : "memory");
}
__device__ __forceinline__ void mbar_expect_tx(uint32_t bar, uint32_t bytes) {
    asm volatile("mbarrier.arrive.expect_tx.shared::cta.b64 _, [%0], %1;" ::"r"(bar), "r"(bytes) : "memory");
}
__device__ __forceinline__ void mbar_wait(uint32_t bar, uint32_t parity) {
    uint32_t ok;
    uint32_t spins = 0;
    do {
        asm volatile("{\n.reg .pred p;\n"
                     "mbarrier.try_wait.parity.shared::cta.b64 p, [%1], %2;\n"
                     "selp.b32 %0, 1, 0, p;\n}\n"
                     : "=r"(ok) : "r"(bar), "r"(parity) : "memory");
        if (++spins > (1u << 26)) __trap();
    } while (!ok);
}
__device__ __forceinline__ uint32_t tid_now() {
    uint32_t t;
    asm volatile("mov.u32 %0, %%tid.x;" : "=r"(t));
    return t;
}
__device__ __forceinline__ uint32_t nctaid_now() {
    uint32_t t;
    asm volatile("mov.u32 %0, %%nctaid.x;" : "=r"(t));
    return t;
}
__device__ __forceinline__ bool elect_one() {
    uint32_t pred;
    asm volatile("{\n.reg .pred p;\nelect.sync _|p, 0xffffffff;\nselp.b32 %0, 1, 0, p;\n}\n" : "=r"(pred));
    return pred != 0;
}
#define PASS1 10
#define PASS4 11
#define PASS2 7
#define PASS3 3
__device__ __forceinline__ void ring_wait() {
    asm volatile("bar.sync %0, 256;" ::"r"((tid_now() >> 7) + 8) : "memory");
}
__device__ __forceinline__ void ring_pass() {
    const uint32_t w = tid_now() >> 7;
    asm volatile("bar.arrive %0, 256;" ::"r"(w == kNWG - 1 ? 8u : w + 9u) : "memory");
}
constexpr uint32_t kDone = 0x40000000u;
constexpr int kPhase = 0x10000;
#define SHARED 16
#define SHARED_HOST SHARED
constexpr int kHelp = 0x1000;
__device__ __forceinline__ uint32_t wg_uniform() { return __reduce_or_sync(0xffffffffu, tid_now() >> 7); }
__device__ __forceinline__ uint32_t desc_x(uint32_t w) { return (((kSmemBase + kOffX) >> 4) | (1u << 16)) + w * (kXBytes >> 4); }
__device__ __forceinline__ uint32_t desc_xt(uint32_t w) { return (((kSmemBase + kOffX) >> 4) | ((8192u >> 4) << 16)) + w * (kXBytes >> 4); }
__device__ __forceinline__ void tma_load_x_chunk(uint32_t dst, const CUtensorMap* tm, uint32_t bar, int win, int chunk) {
    asm volatile("cp.async.bulk.tensor.5d.shared::cluster.global.mbarrier::complete_tx::bytes"
                 " [%0], [%1, {%3, %4, %6, %6, %5}], [%2];"
                 ::"r"(dst), "l"(tm), "r"(bar), "r"(chunk * 64), "r"((win & 63) * 4), "r"((win >> 6) * 4), "r"(0) : "memory");
}
__device__ __forceinline__ void tma_load_x_hint(uint32_t dst, const CUtensorMap* tm, uint32_t bar, int win, bool evict_first) {
    uint64_t first, normal;
    asm("createpolicy.fractional.L2::evict_first.b64 %0, 1.0;" : "=l"(first));
    asm("createpolicy.fractional.L2::evict_normal.b64 %0, 1.0;" : "=l"(normal));
#pragma unroll
    for (int c = 0; c < 3; c++)
        asm volatile("cp.async.bulk.tensor.5d.shared::cluster.global.mbarrier::complete_tx::bytes.L2::cache_hint"
                     " [%0], [%1, {%3, %4, %6, %6, %5}], [%2], %7;"
                     ::"r"(dst + c * 8192), "l"(tm), "r"(bar), "r"(c * 64), "r"((win & 63) * 4), "r"((win >> 6) * 4), "r"(0),
                       "l"(evict_first ? first : normal) : "memory");
}
__device__ __forceinline__ void bulk_load(uint32_t dst, const void* src, uint32_t bytes, uint32_t bar) {
    asm volatile("cp.async.bulk.shared::cluster.global.mbarrier::complete_tx::bytes [%0], [%1], %2, [%3];"
                 ::"r"(dst), "l"(src), "r"(bytes), "r"(bar) : "memory");
}

__device__ __forceinline__ void wg_fence()  { asm volatile("wgmma.fence.sync.aligned;" ::: "memory"); }
__device__ __forceinline__ void wg_commit() { asm volatile("wgmma.commit_group.sync.aligned;" ::: "memory"); }
__device__ __forceinline__ void wg_wait0()  { asm volatile("wgmma.wait_group.sync.aligned 0;" ::: "memory"); }
__device__ __forceinline__ void wg_wait1()  { asm volatile("wgmma.wait_group.sync.aligned 1;" ::: "memory"); }
__device__ __forceinline__ void wg_wait2()  { asm volatile("wgmma.wait_group.sync.aligned 2;" ::: "memory"); }

template <int N> __device__ __forceinline__ void fence_regs(float (&d)[N]) {
#pragma unroll
    for (int i = 0; i < N; i++) asm volatile("" : "+f"(d[i])::"memory");
}
template <int N> __device__ __forceinline__ void fence_regs(uint32_t (&d)[N]) {
#pragma unroll
    for (int i = 0; i < N; i++) asm volatile("" : "+r"(d[i])::"memory");
}

#define ACC8(c, d, i) c(d[i]), c(d[i + 1]), c(d[i + 2]), c(d[i + 3]), c(d[i + 4]), c(d[i + 5]), c(d[i + 6]), c(d[i + 7])
#define ACC32(c, d) ACC8(c, d, 0), ACC8(c, d, 8), ACC8(c, d, 16), ACC8(c, d, 24)
#define ACC96(c, d) ACC32(c, d), ACC8(c, d, 32), ACC8(c, d, 40), ACC8(c, d, 48), ACC8(c, d, 56), \
                    ACC8(c, d, 64), ACC8(c, d, 72), ACC8(c, d, 80), ACC8(c, d, 88)
#define C_IO(x) "+f"(x)
#define C_O(x) "=f"(x)
#define REGS32 "{%0, %1, %2, %3, %4, %5, %6, %7, %8, %9, %10, %11, %12, %13, %14, %15, " \
               "%16, %17, %18, %19, %20, %21, %22, %23, %24, %25, %26, %27, %28, %29, %30, %31}"
#define REGS96 "{%0, %1, %2, %3, %4, %5, %6, %7, %8, %9, %10, %11, %12, %13, %14, %15, " \
               "%16, %17, %18, %19, %20, %21, %22, %23, %24, %25, %26, %27, %28, %29, %30, %31, " \
               "%32, %33, %34, %35, %36, %37, %38, %39, %40, %41, %42, %43, %44, %45, %46, %47, " \
               "%48, %49, %50, %51, %52, %53, %54, %55, %56, %57, %58, %59, %60, %61, %62, %63, " \
               "%64, %65, %66, %67, %68, %69, %70, %71, %72, %73, %74, %75, %76, %77, %78, %79, " \
               "%80, %81, %82, %83, %84, %85, %86, %87, %88, %89, %90, %91, %92, %93, %94, %95}"

#define DESC_HI "0x40000040"
#define MK_DESC(name, lo, off) "add.u32 t, " lo ", " off ";\nmov.b64 " name ", {t, " DESC_HI "};\n"

template <bool First, int OA, int OB> __device__ __forceinline__ void wg192_ss(float (&d)[96], uint32_t la, uint32_t lb) {
    if constexpr (First)
        asm volatile("{\n.reg .pred p;\n.reg .b32 t;\n.reg .b64 da, db;\nsetp.ne.b32 p, 0, 0;\n"
                     MK_DESC("da", "%96", "%98") MK_DESC("db", "%97", "%99")
                     "wgmma.mma_async.sync.aligned.m64n192k16.f32.bf16.bf16 " REGS96 ", da, db, p, 1, 1, 0, 0;\n}\n"
                     : ACC96(C_O, d) : "r"(la), "r"(lb), "n"(OA), "n"(OB));
    else
        asm volatile("{\n.reg .pred p;\n.reg .b32 t;\n.reg .b64 da, db;\nsetp.ne.b32 p, 1, 0;\n"
                     MK_DESC("da", "%96", "%98") MK_DESC("db", "%97", "%99")
                     "wgmma.mma_async.sync.aligned.m64n192k16.f32.bf16.bf16 " REGS96 ", da, db, p, 1, 1, 0, 0;\n}\n"
                     : ACC96(C_IO, d) : "r"(la), "r"(lb), "n"(OA), "n"(OB));
}
#define ACC48(c, d, o) ACC8(c, d, o), ACC8(c, d, o + 8), ACC8(c, d, o + 16), ACC8(c, d, o + 24), ACC8(c, d, o + 32), ACC8(c, d, o + 40)
#define REGS48 "{%0, %1, %2, %3, %4, %5, %6, %7, %8, %9, %10, %11, %12, %13, %14, %15, %16, %17, %18, %19, %20, %21, %22, %23, " \
               "%24, %25, %26, %27, %28, %29, %30, %31, %32, %33, %34, %35, %36, %37, %38, %39, %40, %41, %42, %43, %44, %45, %46, %47}"
template <bool First, int OA, int OB> __device__ __forceinline__ void wg96_ss(float (&d)[48], uint32_t la, uint32_t lb) {
    if constexpr (First)
        asm volatile("{\n.reg .pred p;\n.reg .b32 t;\n.reg .b64 da, db;\nsetp.ne.b32 p, 0, 0;\n"
                     MK_DESC("da", "%48", "%50") MK_DESC("db", "%49", "%51")
                     "wgmma.mma_async.sync.aligned.m64n96k16.f32.bf16.bf16 " REGS48 ", da, db, p, 1, 1, 0, 0;\n}\n"
                     : ACC48(C_O, d, 0) : "r"(la), "r"(lb), "n"(OA), "n"(OB));
    else
        asm volatile("{\n.reg .pred p;\n.reg .b32 t;\n.reg .b64 da, db;\nsetp.ne.b32 p, 1, 0;\n"
                     MK_DESC("da", "%48", "%50") MK_DESC("db", "%49", "%51")
                     "wgmma.mma_async.sync.aligned.m64n96k16.f32.bf16.bf16 " REGS48 ", da, db, p, 1, 1, 0, 0;\n}\n"
                     : ACC48(C_IO, d, 0) : "r"(la), "r"(lb), "n"(OA), "n"(OB));
}
template <bool First, int TB, int OB> __device__ __forceinline__ void wg192_rs(float (&d)[96], const uint32_t* a, uint32_t lb) {
    if constexpr (First)
        asm volatile("{\n.reg .pred p;\n.reg .b32 t;\n.reg .b64 db;\nsetp.ne.b32 p, 0, 0;\n"
                     MK_DESC("db", "%100", "%102")
                     "wgmma.mma_async.sync.aligned.m64n192k16.f32.bf16.bf16 " REGS96 ", {%96, %97, %98, %99}, db, p, 1, 1, %101;\n}\n"
                     : ACC96(C_O, d) : "r"(a[0]), "r"(a[1]), "r"(a[2]), "r"(a[3]), "r"(lb), "n"(TB), "n"(OB));
    else
        asm volatile("{\n.reg .pred p;\n.reg .b32 t;\n.reg .b64 db;\nsetp.ne.b32 p, 1, 0;\n"
                     MK_DESC("db", "%100", "%102")
                     "wgmma.mma_async.sync.aligned.m64n192k16.f32.bf16.bf16 " REGS96 ", {%96, %97, %98, %99}, db, p, 1, 1, %101;\n}\n"
                     : ACC96(C_IO, d) : "r"(a[0]), "r"(a[1]), "r"(a[2]), "r"(a[3]), "r"(lb), "n"(TB), "n"(OB));
}
template <bool First, int OB> __device__ __forceinline__ void wg64_rs(float (&d)[32], const uint32_t* a, uint32_t lb) {
    if constexpr (First)
        asm volatile("{\n.reg .pred p;\n.reg .b32 t;\n.reg .b64 db;\nsetp.ne.b32 p, 0, 0;\n"
                     MK_DESC("db", "%36", "%37")
                     "wgmma.mma_async.sync.aligned.m64n64k16.f32.bf16.bf16 " REGS32 ", {%32, %33, %34, %35}, db, p, 1, 1, 0;\n}\n"
                     : ACC32(C_O, d) : "r"(a[0]), "r"(a[1]), "r"(a[2]), "r"(a[3]), "r"(lb), "n"(OB));
    else
        asm volatile("{\n.reg .pred p;\n.reg .b32 t;\n.reg .b64 db;\nsetp.ne.b32 p, 1, 0;\n"
                     MK_DESC("db", "%36", "%37")
                     "wgmma.mma_async.sync.aligned.m64n64k16.f32.bf16.bf16 " REGS32 ", {%32, %33, %34, %35}, db, p, 1, 1, 0;\n}\n"
                     : ACC32(C_IO, d) : "r"(a[0]), "r"(a[1]), "r"(a[2]), "r"(a[3]), "r"(lb), "n"(OB));
}
template <bool First, int OA, int OB> __device__ __forceinline__ void wg64_ss(float (&d)[32], uint32_t la, uint32_t lb) {
    if constexpr (First)
        asm volatile("{\n.reg .pred p;\n.reg .b32 t;\n.reg .b64 da, db;\nsetp.ne.b32 p, 0, 0;\n"
                     MK_DESC("da", "%32", "%34") MK_DESC("db", "%33", "%35")
                     "wgmma.mma_async.sync.aligned.m64n64k16.f32.bf16.bf16 " REGS32 ", da, db, p, 1, 1, 0, 1;\n}\n"
                     : ACC32(C_O, d) : "r"(la), "r"(lb), "n"(OA), "n"(OB));
    else
        asm volatile("{\n.reg .pred p;\n.reg .b32 t;\n.reg .b64 da, db;\nsetp.ne.b32 p, 1, 0;\n"
                     MK_DESC("da", "%32", "%34") MK_DESC("db", "%33", "%35")
                     "wgmma.mma_async.sync.aligned.m64n64k16.f32.bf16.bf16 " REGS32 ", da, db, p, 1, 1, 0, 1;\n}\n"
                     : ACC32(C_IO, d) : "r"(la), "r"(lb), "n"(OA), "n"(OB));
}
__host__ __device__ constexpr int koff(int kk, int chunk) { return ((kk >> 2) * chunk + (kk & 3) * 32) >> 4; }

__device__ __forceinline__ uint32_t clock_now() {
    uint32_t t;
    asm volatile("mov.u32 %0, %%clock;" : "=r"(t));
    return t;
}
template <int K> __device__ __forceinline__ void stage_put(const uint4 (&h)[12], uint32_t buf) {
    const uint32_t t = tid_now(), line = ((t >> 2) & 2) + (t & 4) + ((t >> 1) & 8);
    const uint32_t adr = buf + line * 128 + (((t & 3) ^ (line & 7)) << 4);
#pragma unroll
    for (int j = 0; j < 4; j++) {
        const int i = 4 * K + j, n = 2 * (i % 6) + i / 6;
        asm volatile("st.shared.v4.b32 [%4], {%0, %1, %2, %3};"
                     :: "r"(h[n].x), "r"(h[n].y), "r"(h[n].z), "r"(h[n].w), "r"((adr ^ ((j & 1) * 64 + (j >> 1) * 16)) + (j >> 1) * 128) : "memory");
    }
}
__device__ __forceinline__ void stage_send(const CUtensorMap* tm, uint32_t pos, int k, uint32_t buf) {
    asm volatile("fence.proxy.async.shared::cta;" ::: "memory");
    __syncwarp();
    if (elect_one()) {
        asm volatile("cp.async.bulk.tensor.5d.global.shared::cta.bulk_group [%0, {%2, %5, %3, %2, %4}], [%1];"
                     ::"l"(tm), "r"(buf), "r"(0), "r"(pos & 0xffff), "r"(pos >> 16), "r"(2 * k) : "memory");
        asm volatile("cp.async.bulk.commit_group;" ::: "memory");
    }
    __syncwarp();
}
__device__ __forceinline__ void stage_wait() {
    asm volatile("cp.async.bulk.wait_group.read 0;" ::: "memory");
    __syncwarp();
}
__device__ __forceinline__ uint32_t out_pos(int win) {
    return ((win & 63) * 2) | (((((win & 4095) >> 6) & 63) * 8 + 2 * ((tid_now() >> 5) & 3)) << 16);
}
__device__ __forceinline__ uint32_t stage_buf() { return kSmemBase + kOffStage + ((tid_now() >> 5) & 3) * 2048; }
template <int K> __device__ __forceinline__ void stage_window(uint4 (&h)[12], const CUtensorMap* tm, uint32_t pos, [[maybe_unused]] int win) {
    if constexpr (K < 3) {
        if constexpr (K > 0) stage_wait();
        stage_put<K>(h, stage_buf());
        stage_send(tm, pos, K, stage_buf());
        stage_window<K + 1>(h, tm, pos, win);
    }
}
__device__ __forceinline__ void stg128(void* p, uint4 v) {
    asm volatile("st.global.v4.b32 [%0], {%1, %2, %3, %4};" ::"l"(p), "r"(v.x), "r"(v.y), "r"(v.z), "r"(v.w) : "memory");
}
#define TAIL_DT 75
#define TAIL_FREE 2
template <int J> __device__ __forceinline__ void store_tail(uint4 (&h)[12], uint8_t* hptr, uint32_t t0) {
    if constexpr (J < 12) {
        if (J > TAIL_FREE) { while (clock_now() - t0 < (uint32_t)((J - TAIL_FREE) * TAIL_DT)) {} }
        stg128(hptr + J * 64, h[2 * (J % 6) + J / 6]);
        store_tail<J + 1>(h, hptr, t0);
    }
}
__device__ __forceinline__ uint8_t* out_address(__nv_bfloat16* out, uint32_t pos) {
    const uint32_t ln = tid_now() & 31;
    return reinterpret_cast<uint8_t*>(out) + (((pos >> 16) + (ln >> 4)) * kHW + (pos & 0xffff) * 4 + ((ln >> 1) & 6)) * (uint32_t)(kC * 2) + (ln & 3) * 16;
}
template <int K0, int K> struct Gemm1 {
    static __device__ __forceinline__ void run(float (&d)[96], uint32_t lx, uint32_t lw) {
        if constexpr (K > K0) Gemm1<K0, K - 1>::run(d, lx, lw);
        wg192_ss<K == 0, koff(K, 8192), koff(K, 24576)>(d, lx, lw);
    }
};
__device__ __forceinline__ uint32_t draw_ticket(uint32_t* counter, uint32_t last) {
    uint32_t ticket = 0;
    asm volatile("{\n.reg .pred p;\nsetp.eq.u32 p, %2, 0;\n@p atom.relaxed.gpu.global.inc.u32 %0, [%1], %3;\n}\n"
                 : "+r"(ticket) : "l"(counter), "r"(tid_now() & 127), "r"(last) : "memory");
    return ticket;
}
template <int KK> struct Gemm2 { static __device__ __forceinline__ void run(float (&d)[32], const uint32_t* a, uint32_t lx) {
    Gemm2<KK - 1>::run(d, a, lx); wg64_rs<KK == 0, koff(KK, 8192)>(d, a + 4 * KK, lx);
    if constexpr (KK == PASS2 && KK < 11) ring_pass(); } };
template <int K0, int KK> struct Gemm2p { static __device__ __forceinline__ void run(float (&d)[32], const uint32_t* a, uint32_t lx) {
    if constexpr (KK > K0) Gemm2p<K0, KK - 1>::run(d, a, lx);
    wg64_rs<KK == 0, koff(KK, 8192)>(d, a + 4 * KK, lx); } };
template <int H, int C, int KK = 3> struct Gemm1h { static __device__ __forceinline__ void run(float (&d)[48], uint32_t lx, uint32_t lw) {
    if constexpr (KK > 0) Gemm1h<H, C, KK - 1>::run(d, lx, lw);
    wg96_ss<C == 0 && KK == 0, koff(4 * C + KK, 8192), koff(4 * C + KK, 24576) + H * 96 * 8>(d, lx, lw); } };
template <> struct Gemm2<-1> { static __device__ __forceinline__ void run(float (&)[32], const uint32_t*, uint32_t) {} };
template <int KK> struct Gemm3 { static __device__ __forceinline__ void run(float (&d)[96], const uint32_t* a, uint32_t lxt) {
    Gemm3<KK - 1>::run(d, a, lxt); wg192_rs<KK == 0, 1, KK * (2048 >> 4)>(d, a + 4 * KK, lxt);
    if constexpr (KK == PASS3 && KK < 3) ring_pass(); } };
template <> struct Gemm3<-1> { static __device__ __forceinline__ void run(float (&)[96], const uint32_t*, uint32_t) {} };
template <int K0, int KK> struct Gemm4 { static __device__ __forceinline__ void run(float (&d)[96], const uint32_t* a, uint32_t lw) {
    if constexpr (KK > K0) Gemm4<K0, KK - 1>::run(d, a, lw);
    wg192_rs<KK == 0, 0, koff(KK, 24576)>(d, a + 4 * KK, lw); } };

template <int J, int KK> struct Gemm3s { static __device__ __forceinline__ void run(float (&d)[32], uint32_t lp, uint32_t lxt) {
    if constexpr (KK > 0) Gemm3s<J, KK - 1>::run(d, lp, lxt);
    wg64_ss<KK == 0, KK * 2, (J * 8192 + KK * 2048) / 16>(d, lp, lxt); } };
template <int J, int K0, int KK> struct Gemm4s { static __device__ __forceinline__ void run(float (&d)[32], const uint32_t* a, uint32_t lw) {
    if constexpr (KK > K0) Gemm4s<J, K0, KK - 1>::run(d, a, lw);
    wg64_rs<KK == 0, koff(KK, 24576) + J * (8192 / 16)>(d, a + 4 * KK, lw); } };

__device__ __forceinline__ uint32_t pack_bf16(float lo, float hi) {
    uint32_t r;
    asm("cvt.rn.bf16x2.f32 %0, %1, %2;" : "=r"(r) : "f"(hi), "f"(lo));
    return r;
}
__device__ __forceinline__ float ex2(float x) {
    float r;
    asm("ex2.approx.ftz.f32 %0, %1;" : "=f"(r) : "f"(x));
    return r;
}
__device__ __forceinline__ float rcp(float x) {
    float r;
    asm("rcp.approx.ftz.f32 %0, %1;" : "=f"(r) : "f"(x));
    return r;
}

__device__ __forceinline__ void pack_slice(uint32_t* a, float (&d)[32]) {
    fence_regs(d);
#pragma unroll
    for (int i = 0; i < 16; i++) a[i] = pack_bf16(d[2 * i], d[2 * i + 1]);
#pragma unroll
    for (int i = 0; i < 16; i++) asm volatile("" : "+r"(a[i])::"memory");
}
template <int J> __device__ __forceinline__ void store_slice(float (&d)[32], uint8_t* hptr) {
    fence_regs(d);
#pragma unroll
    for (int r = 0; r < 2; r++) {
        uint4 h[2];
#pragma unroll
        for (int a = 0; a < 2; a++) {
            const int o = 16 * a + 2 * r;
            h[a] = make_uint4(pack_bf16(d[o], d[o + 1]), pack_bf16(d[o + 4], d[o + 5]), pack_bf16(d[o + 8], d[o + 9]), pack_bf16(d[o + 12], d[o + 13]));
        }
        stg128(hptr + r * (kC * 2) + J * 128, h[0]);
        stg128(hptr + r * (kC * 2) + J * 128 + 64, h[1]);
    }
    __syncwarp();
}
__device__ __forceinline__ void store_p_if(const uint32_t (&pa)[16], bool cond) {
    const uint32_t t = tid_now(), row = ((t >> 1) & 48) + (t & 15);
    const uint32_t adr = kSmemBase + kOffStage + row * 128 + ((((t >> 4) & 1) ^ (t & 7)) << 4);
#pragma unroll
    for (int i = 0; i < 4; i++)
        asm volatile("{\n.reg .pred p;\nsetp.ne.u32 p, %5, 0;\n@p stmatrix.sync.aligned.m8n8.x4.shared.b16 [%4], {%0, %1, %2, %3};\n}\n"
                     :: "r"(pa[4 * i]), "r"(pa[4 * i + 1]), "r"(pa[4 * i + 2]), "r"(pa[4 * i + 3]), "r"(adr ^ (i << 5)), "r"((uint32_t)cond) : "memory");
}
__device__ __forceinline__ void last_window(__nv_bfloat16* out, int win) {
    constexpr uint32_t dWv = ((kSmemBase + kOffWv) >> 4) | (1u << 16);
    asm volatile("fence.proxy.async.shared::cta;" ::: "memory");
    const uint32_t w = wg_uniform();
    const uint32_t dXt = desc_xt(w);
    constexpr uint32_t dP = ((kSmemBase + kOffStage) >> 4) | (1u << 16);
    float u0[32], u1[32], u2[32];
    uint32_t fa[48];
    const bool help = (win & kHelp) != 0;
    uint8_t* hptr = out_address(out, out_pos(win)) + (help ? 256 : 0);
    const uint32_t dW0 = dWv + (help ? 2 * 8192 / 16 : 0);
    asm volatile("" : "+l"(hptr) :: "memory");
    ring_wait();
    wg_fence();
    Gemm3s<0, 3>::run(u0, dP, dXt); wg_commit();
    Gemm3s<1, 3>::run(u1, dP, dXt); wg_commit();
    Gemm3s<2, 3>::run(u2, dP, dXt); wg_commit();
    wg_wait2();
    pack_slice(fa, u0);
    wg_fence();
    Gemm4s<0, 0, 3>::run(u0, fa, dW0); wg_commit();
    wg_wait2();
    pack_slice(fa + 16, u1);
    wg_fence();
    Gemm4s<0, 4, 7>::run(u0, fa, dW0); wg_commit();
    wg_wait2();
    pack_slice(fa + 32, u2);
    wg_fence();
    Gemm4s<0, 8, 11>::run(u0, fa, dW0); wg_commit();
    if (help) {
        wg_wait0();
        fence_regs(fa);
        store_slice<0>(u0, hptr);
    } else {
        wg_fence();
        Gemm4s<1, 0, 5>::run(u1, fa, dWv); wg_commit();
        wg_wait1();
        store_slice<0>(u0, hptr);
        wg_fence();
        Gemm4s<1, 6, 11>::run(u1, fa, dWv); wg_commit();
        if ((win & 4095) >= kNWin - SHARED) {
            wg_wait0();
            fence_regs(fa);
            store_slice<1>(u1, hptr);
        } else {
            wg_fence();
            Gemm4s<2, 0, 5>::run(u2, fa, dWv); wg_commit();
            wg_wait1();
            store_slice<1>(u1, hptr);
            wg_fence();
            Gemm4s<2, 6, 11>::run(u2, fa, dWv); wg_commit();
            wg_wait0();
            fence_regs(fa);
            store_slice<2>(u2, hptr);
        }
    }
}

__device__ __forceinline__ int fold_offset(int n, int k0, int q) {
    const int u = ((k0 & 63) >> 3) + (q >> 1);
    return (k0 >> 6) * 24576 + (q & 1) * 8 + n * 128 + ((u ^ (n & 7)) << 4);
}
__device__ __forceinline__ void mma16816x2(float (&c)[4], float (&d)[4], const uint32_t (&a)[4], const uint32_t (&b)[4]) {
    asm volatile("mma.sync.aligned.m16n8k16.row.col.f32.bf16.bf16.f32 {%0,%1,%2,%3}, {%8,%9,%10,%11}, {%12,%13}, {%0,%1,%2,%3};\n"
                 "mma.sync.aligned.m16n8k16.row.col.f32.bf16.bf16.f32 {%4,%5,%6,%7}, {%8,%9,%10,%11}, {%14,%15}, {%4,%5,%6,%7};"
                 : "+f"(c[0]), "+f"(c[1]), "+f"(c[2]), "+f"(c[3]), "+f"(d[0]), "+f"(d[1]), "+f"(d[2]), "+f"(d[3])
                 : "r"(a[0]), "r"(a[1]), "r"(a[2]), "r"(a[3]), "r"(b[0]), "r"(b[1]), "r"(b[2]), "r"(b[3]));
}
__device__ __forceinline__ void cp_async16(uint32_t dst, const void* src) {
    asm volatile("cp.async.cg.shared.global [%0], [%1], 16;" ::"r"(dst), "l"(src) : "memory");
}
template <bool kTrans> __device__ __forceinline__ void ldsm4(uint32_t (&r)[4], uint32_t addr) {
    if constexpr (kTrans)
        asm volatile("ldmatrix.sync.aligned.m8n8.x4.trans.shared.b16 {%0, %1, %2, %3}, [%4];" : "=r"(r[0]), "=r"(r[1]), "=r"(r[2]), "=r"(r[3]) : "r"(addr) : "memory");
    else
        asm volatile("ldmatrix.sync.aligned.m8n8.x4.shared.b16 {%0, %1, %2, %3}, [%4];" : "=r"(r[0]), "=r"(r[1]), "=r"(r[2]), "=r"(r[3]) : "r"(addr) : "memory");
}
__device__ __forceinline__ uint32_t nonzero(uint32_t w) { return w ? w : 0x80000000u; }
template <bool vo>
__device__ __forceinline__ void fold_job(Scratch* sc, const __nv_bfloat16* __restrict__ wqkv, const __nv_bfloat16* __restrict__ wo,
                                         int job, int warp, int lane) {
    constexpr int nw = vo ? 3 : 2;
    const int nb = vo ? job >> 2 : (job * 43) >> 8;
    const int n0 = nb * 16, k0 = (nw * (vo ? job & 3 : job - 6 * nb) + max(warp, 1) - 1) * 16;
    const uint32_t stage = kSmemBase + kOffWv;
    if (warp != kWarmW) {
        if (vo) {
            const char* src = reinterpret_cast<const char*>(wo) + (uint32_t)(((warp * 48 + (lane >> 1)) * kC + n0 + (lane & 1) * 8) * 2);
            const uint32_t dst = stage + warp * 1536 + ((lane ^ ((lane >> 3) & 1)) << 4);
#pragma unroll
            for (int i = 0; i < 3; i++) cp_async16(dst + i * 512, src + i * 16 * kC * 2);
        }
        if (!vo || warp != 0) {
            const int row0 = warp == 0 ? n0 : k0, col0 = warp == 0 ? kC : vo ? 2 * kC : 0;
            const char* src = reinterpret_cast<const char*>(wqkv) + (uint32_t)(((row0 + (lane >> 3)) * (3 * kC) + col0 + (lane & 7) * 8) * 2);
            const uint32_t dst = stage + warp * 6144 + (lane >> 3) * 384 + (((lane & 7) ^ (lane >> 3)) << 4);
#pragma unroll
            for (int i = 0; i < 12; i++) cp_async16((dst ^ (((i / 3) & 1) << 6)) + (i / 3) * 1536 + (i % 3) * 128, src + (i / 3) * 4 * 3 * kC * 2 + (i % 3) * 128);
        }
    }
    const int g = lane >> 2, q = lane & 3, mi = lane >> 3, r8 = lane & 7;
    const int row = 4 * (r8 >> 1) + (r8 & 1) + 2 * (mi >> 1), c = r8 + 8 * (mi >> 1);
    uint32_t baseB = stage + warp * 6144 + row * 384 + (((mi & 1) ^ (row & 7)) << 4);
    uint32_t baseA = stage + (vo ? ((2 * c + (mi & 1)) ^ ((c >> 2) & 1)) << 4 : (r8 + 8 * (mi & 1)) * 384 + (((mi >> 1) ^ r8) << 4));
    const int ch = n0 + g;
    const int n = vo ? 32 * (ch >> 5) + 8 * ((ch >> 1) & 3) + 2 * ((ch >> 3) & 3) + (ch & 1) : ch;
    char* img = reinterpret_cast<char*>(sc->wfold) + (vo ? kWBytes : 0);
    char* dst0 = img + fold_offset(n, k0, q);
    char* dst1 = img + fold_offset(n + (vo ? 2 : 8), k0, q);
    asm volatile("" : "+r"(baseA), "+r"(baseB), "+l"(dst0), "+l"(dst1));
    if (warp != kWarmW) {
        asm volatile("cp.async.wait_all;" ::: "memory");
        if (warp == 0) {
            asm volatile("bar.arrive 13, %0;" ::"n"(32 * nw + 32) : "memory");
            return;
        }
        asm volatile("bar.sync 13, %0;" ::"n"(32 * nw + 32) : "memory");
    }
    float c0[4] = {0.f, 0.f, 0.f, 0.f}, c1[4] = {0.f, 0.f, 0.f, 0.f}, c2[4] = {0.f, 0.f, 0.f, 0.f}, c3[4] = {0.f, 0.f, 0.f, 0.f};
    uint32_t A[12][4], B[12][4];
#pragma unroll
    for (int ks = 0; ks < 12; ks++) {
        ldsm4<vo>(A[ks], vo ? baseA + ks * 512 : (baseA ^ ((ks & 3) << 5)) + (ks >> 2) * 128);
        ldsm4<false>(B[ks], (baseB ^ ((ks & 3) << 5)) + (ks >> 2) * 128);
    }
#pragma unroll
    for (int ks = 0; ks < 12; ks += 2) {
        mma16816x2(c0, c1, A[ks], B[ks]);
        mma16816x2(c2, c3, A[ks + 1], B[ks + 1]);
    }
#pragma unroll
    for (int i = 0; i < 4; i++) { c0[i] += c2[i]; c1[i] += c3[i]; }
    asm volatile("{\n.reg .pred p;\nsetp.ne.u32 p, %6, %7;\n@p st.global.v2.u32 [%0], {%2, %3};\n@p st.global.v2.u32 [%1], {%4, %5};\n}\n"
                 ::"l"(dst0), "l"(dst1),
                   "r"(nonzero(pack_bf16(c0[0], c0[1]))), "r"(nonzero(pack_bf16(c1[0], c1[1]))), "r"(nonzero(pack_bf16(c0[2], c0[3]))), "r"(nonzero(pack_bf16(c1[2], c1[3]))),
                   "r"(warp), "n"(kWarmW) : "memory");
}
constexpr uint32_t kWarpsQK = 0x17;

__device__ __forceinline__ bool bar_or(uint32_t id, uint32_t n, bool pred) {
    uint32_t r;
    asm volatile("{\n.reg .pred p, q;\nsetp.ne.u32 q, %3, 0;\nbar.red.or.pred p, %1, %2, q;\nselp.u32 %0, 1, 0, p;\n}\n"
                 : "=r"(r) : "r"(id), "r"(n), "r"((uint32_t)pred) : "memory");
    return r != 0;
}
template <int N = 6> __device__ __forceinline__ bool chunk_incomplete(uint32_t base) {
    const uint32_t t = tid_now(), r = (t >> 2) & 7;
    const uint32_t adr = base + (((t >> 5) & 3) * 8 * N + r) * 128 + (t & 3) * 32 + r * 4;
    uint32_t m = ~0u;
#pragma unroll
    for (int j = 0; j < N; j++) {
        uint32_t v;
        asm volatile("ld.shared.u32 %0, [%1];" : "=r"(v) : "r"(adr + j * 1024) : "memory");
        m = min(m, v);
    }
    return m == 0;
}
__device__ __forceinline__ void load_image(uint32_t dst, const void* src, uint32_t bar) {
    mbar_expect_tx(bar, kWBytes);
#pragma unroll
    for (int c = 0; c < 3; c++) bulk_load(dst + c * 24576, reinterpret_cast<const char*>(src) + c * 24576, 24576, bar);
}
__device__ __forceinline__ void repair_image(uint32_t dst, const void* src, uint32_t bar, uint32_t par) {
    uint32_t tries = 0;
    bool bad;
    do {
        if (((tid_now() >> 5) & 3) == 0) {
            if (elect_one()) {
                asm volatile("fence.proxy.async;" ::: "memory");
                load_image(dst, src, bar);
            }
            __syncwarp();
        }
        mbar_wait(bar, par);
        par ^= 1;
        bad = chunk_incomplete(dst) | chunk_incomplete(dst + 24576) | chunk_incomplete(dst + 2 * 24576);
        if (++tries > (1u << 16)) __trap();
    } while (bar_or((tid_now() >> 7) + 1, 128, bad));
}
__device__ __forceinline__ void count_image(Scratch* sc) {
    asm volatile("red.relaxed.gpu.global.inc.u32 [%0], %1;" ::"l"(sc->cnt), "r"(3 * nctaid_now() - 1) : "memory");
}
__device__ __forceinline__ uint32_t ld_acquire(const uint32_t* p) {
    uint32_t v;
    asm volatile("ld.acquire.gpu.global.u32 %0, [%1];" : "=r"(v) : "l"(p) : "memory");
    return v;
}
__device__ __noinline__ void clear_images(Scratch* sc) {
    const uint32_t g = gridDim.x, t = threadIdx.x & 127;
    if (t == 0) {
        uint32_t spins = 0;
        while (ld_acquire(sc->cnt) < 2 * g) { if (++spins > (1u << 24)) __trap(); }
    }
    asm volatile("bar.sync %0, 128;" ::"r"((threadIdx.x >> 7) + 1) : "memory");
    for (uint32_t i = blockIdx.x * 64 + t; t < 64 && i < 2 * kWBytes / 16; i += g * 64) sc->wfold[i] = make_uint4(0, 0, 0, 0);
    if (t == 0) count_image(sc);
}
__device__ __forceinline__ void prefetch_x(const CUtensorMap* tm, int win) {
    const int wh = win >> 6, ww = win & 63;
    asm volatile("cp.async.bulk.prefetch.tensor.3d.L2.global.tile [%0, {%1, %2, %3}];"
                 ::"l"(tm), "r"(0), "r"(ww * 8), "r"(wh * 8) : "memory");
}

__device__ __forceinline__ void prefetch_ahead_of(const CUtensorMap* tmp, int w, int G) {
    auto lead = [&](int v) {
        int down = max(((kNWin - PF_END - v) * PF_DOWN) >> 8, PF_MIN);
        return min(min(G + (((v - kNWG * G) * PF_UP) >> 8), PF_LEAD), down);
    };
    const int hi = w + lead(w);
    int lo = max(w - 1 + lead(w - 1), w) + 1;
#pragma unroll 1
    for (; lo <= hi && lo < kNWin; lo++) prefetch_x(tmp, lo);
}

__device__ __forceinline__ void publish(uint32_t ticket, int G) {
    constexpr uint32_t sbase = kSmemBase;
    if (((tid_now() >> 5) & 3) == 0) {
        if ((tid_now() & 31) == 0) {
            uint32_t nxt = 2 * kNWG * G + ticket;
            if (nxt >= kNWin) nxt = nxt < kNWin + SHARED ? (2 * kNWin - 1 - nxt) | kHelp : kDone;
            if (nxt == kDone) {
                uint32_t p0, p1, p2, p3;
                asm volatile("ld.shared.v4.u32 {%0, %1, %2, %3}, [%4];" : "=r"(p0), "=r"(p1), "=r"(p2), "=r"(p3) : "r"(sbase + kOffBar + 64) : "memory");
                nxt = kDone + (p0 >> 30) + (p1 >> 30) + (p2 >> 30);
            }
            asm volatile("st.shared.u32 [%0], %1;" ::"r"(sbase + kOffBar + 64 + 4 * (tid_now() >> 7)), "r"(nxt) : "memory");
        }
        __syncwarp();
        asm volatile("bar.arrive %0, 128;" ::"r"((tid_now() >> 7) + 4) : "memory");
    }
}

template <bool kFewSMs>
__global__ void __launch_bounds__(kThreads, 1)
swin_attn_kernel(const __nv_bfloat16* __restrict__ wqkv, const __nv_bfloat16* __restrict__ wo, const __nv_bfloat16* __restrict__ xin, Scratch* sc, uint32_t* tickets,
                 const int G, const uint32_t trk, __nv_bfloat16* __restrict__ out, const uint32_t last_ticket,
                 const __grid_constant__ CUtensorMap tmx, const __grid_constant__ CUtensorMap tmp, const __grid_constant__ CUtensorMap tmo) {
    extern __shared__ uint8_t smem_raw[];
    constexpr uint32_t sbase = kSmemBase;
    const uint32_t t_start = clock_now();
    asm volatile("{\n.reg .pred p, q;\n.reg .b32 i, j;\n.reg .b64 a, b;\nmad.lo.u32 i, %2, 14, %3;\nsetp.lt.u32 p, %3, 14;\nsetp.lt.and.u32 p, i, 1728, p;\n"
                 "mad.wide.u32 a, i, 128, %0;\n@p prefetch.global.L2 [a];\n"
                 "mad.lo.u32 j, %2, 5, %3;\nsetp.lt.u32 q, %3, 5;\nsetp.lt.and.u32 q, j, 576, q;\n"
                 "mad.wide.u32 b, j, 128, %1;\n@q prefetch.global.L2 [b];\n}\n" ::"l"(wqkv), "l"(wo), "r"(blockIdx.x), "r"(threadIdx.x) : "memory");
    if (smem_u32(smem_raw) != kSmemBase) __trap();
    const int tid = threadIdx.x, lane = tid & 31;
    const uint32_t warpu = __reduce_or_sync(0xffffffffu, (uint32_t)tid >> 5), wgu = warpu >> 2;
    const int warp = (int)warpu, wg = (int)wgu;
    const uint32_t bar_full = sbase + kOffBar + 8 * wg;
    constexpr uint32_t bar_m = sbase + kOffBarM, bar_w1 = sbase + kOffBar + 40;
    auto bar_v = [](int c) { return bar_w1 + 16 - 8 * c; };
    int win = wg * G + blockIdx.x;

    const int direct = blockIdx.x >= X0_LATE ? 1 : 2;
    if (!kFewSMs && blockIdx.x < kJobsM && ((kWarpsQK >> warp) & 1)) fold_job<false>(sc, wqkv, wo, blockIdx.x, warp, lane);
    if (warp == 10) {
        auto x_lines = [&](int c) {
            const int w = (c / 3) * G + blockIdx.x;
            return reinterpret_cast<const char*>(xin) + (uint32_t)((((w >> 6) * 8 + (lane >> 3)) * kHW + (w & 63) * 8 + (lane & 7)) * (kC * 2) + (c % 3) * 128);
        };
        if (elect_one()) {
            asm volatile("prefetch.tensormap [%0];" ::"l"(&tmx) : "memory");
#pragma unroll
            for (int w = 0; w < kNWG; w++) mbar_init(sbase + kOffBar + 8 * w, 1);
            mbar_init(sbase + kOffBar + 24, 1);
            mbar_init(sbase + kOffBar + 88, 1);
            mbar_init(sbase + kOffBar + 96, 1);
            mbar_init(sbase + kOffBar + 104, 1);
            mbar_init(sbase + kOffBar + 112, 1);
#pragma unroll
            for (int c = 0; c < 3; c++) mbar_init(bar_v(c), 1);
#pragma unroll
            for (int i = 0; i < 6; i++) mbar_init(bar_m + 8 * i, 1);
            asm volatile("st.shared.v4.u32 [%0], {%1, %1, %1, %1};" ::"r"(sbase + kOffBar + 64), "r"(0) : "memory");
            asm volatile("fence.mbarrier_init.release.cluster;" ::: "memory");
            asm volatile("mbarrier.arrive.shared::cta.b64 _, [%0];" ::"r"(sbase + kOffBar) : "memory");
        }
        __syncwarp();
        asm volatile("bar.arrive 15, 64;" ::: "memory");
        asm volatile("bar.arrive 0, %0;" ::"n"(kThreads) : "memory");
        const uint32_t due = (blockIdx.x * TRK_Q) >> 8;
        if (elect_one()) {
#pragma unroll
            for (int c = 0; c < 2; c++) {
                if (c >= direct) break;
                while (clock_now() - t_start < TRK_T0 + (due + c * TRK_S) / 3) {}
                tma_load_x_chunk(sbase + kOffX + c * 8192, &tmx, bar_m + 16 * c, blockIdx.x, c);
            }
        }
        __syncwarp();
#pragma unroll 1
        for (int c = direct; c < 3 * kNWG; c++) {
            const char* p = x_lines(c);
            while (clock_now() - t_start < TRK_T0 + (due + c * TRK_S) / 3) {}
            asm volatile("prefetch.global.L2 [%0];\nprefetch.global.L2 [%0 + %1];" ::"l"(p), "n"(4 * kHW * kC * 2) : "memory");
        }
        asm volatile("prefetch.tensormap [%0];" ::"l"(&tmp) : "memory");
        asm volatile("prefetch.tensormap [%0];" ::"l"(&tmo) : "memory");
    }
    int role = warp;
    asm volatile("" : "+r"(role));
    if (role == 10) {
    } else if (warp > kWarmW) {
        if (warp == 11) {
            asm volatile("bar.sync 15, 64;" ::: "memory");
            asm volatile("bar.arrive 0, %0;" ::"n"(kThreads) : "memory");
            if (elect_one()) {
                const char* img = reinterpret_cast<const char*>(sc->wfold);
#pragma unroll
                for (int i = 0; i < 6; i++) mbar_expect_tx(bar_m + 8 * i, 12288 + (i & 1 ? 0 : 8192));
#pragma unroll
                for (int c = 0; c < 3; c++) mbar_expect_tx(sbase + kOffBar + (c == 0 ? 8 : 80 + 8 * c), 8192);
                while (clock_now() - t_start < REQ_T) {}
#pragma unroll
                for (int i = 0; i < 6; i++) {
                    if (i >= 2 * direct && !(i & 1)) tma_load_x_chunk(sbase + kOffX + (i >> 1) * 8192, &tmx, bar_m + 8 * i, blockIdx.x, i >> 1);
                    bulk_load(sbase + kOffWm + i * 12288, img + i * 12288, 12288, bar_m + 8 * i);
                }
                mbar_wait(bar_m + 8, 0);
#pragma unroll
                for (int c = 0; c < 3; c++)
                    tma_load_x_chunk(sbase + kOffX + kXBytes + c * 8192, &tmx, sbase + kOffBar + (c == 0 ? 8 : 80 + 8 * c), G + blockIdx.x, c);
            }
            __syncwarp();
        } else {
            asm volatile("bar.sync 0, %0;" ::"n"(kThreads) : "memory");
            if (warp == 9) {
                if (elect_one()) {
                    while (clock_now() - t_start < REQ_TV) {}
                    mbar_wait(bar_m + 24, 0);
                    asm volatile("fence.proxy.async.shared::cta;" ::: "memory");
#pragma unroll
                    for (int c = 0; c < 3; c++) {
                        mbar_expect_tx(bar_v(c), 24576);
                        bulk_load(sbase + kOffWv + c * 24576, reinterpret_cast<const char*>(sc->wfold) + kWBytes + c * 24576, 24576, bar_v(c));
                    }
#pragma unroll
                    for (int c = 0; c < 3; c++) {
                        const uint32_t bar = sbase + kOffBar + (c == 0 ? 16 : 96 + 8 * c);
                        mbar_expect_tx(bar, 8192);
                        tma_load_x_chunk(sbase + kOffX + 2 * kXBytes + c * 8192, &tmx, bar, 2 * G + blockIdx.x, c);
                    }
                }
                __syncwarp();
            }
        }
    } else {
        if constexpr (kFewSMs) {
#pragma unroll 1
            for (int j = blockIdx.x; j < kJobs; j += G) {
                if (j >= kJobsM) fold_job<true>(sc, wqkv, wo, j - kJobsM, warp, lane);
                else if ((kWarpsQK >> warp) & 1) fold_job<false>(sc, wqkv, wo, j, warp, lane);
                asm volatile("bar.sync 14, %0;" ::"n"(32 * kWarmW + 32) : "memory");
            }
        } else {
            if (blockIdx.x - kJobsM < kJobs - kJobsM) fold_job<true>(sc, wqkv, wo, blockIdx.x - kJobsM, warp, lane);
        }
        asm volatile("bar.sync 0, %0;" ::"n"(kThreads) : "memory");
    }
    bool bad_v = false;
    if (wg == 1) {
        mbar_wait(bar_m + 8 * (warp & 3), 0);
        bool bad = chunk_incomplete<12>(sbase + kOffWm);
#pragma unroll
        for (int i = 4; i < 6; i++) {
            mbar_wait(bar_m + 8 * i, 0);
            bad |= chunk_incomplete<3>(sbase + kOffWm + i * 12288);
        }
        bad = bar_or(2, 128, bad);
        if (bad) {
            repair_image(sbase + kOffWm, sc->wfold, sbase + kOffBar + 24, 0);
        }
        asm volatile("st.shared.u32 [%0], %1;" ::"r"(sbase + kOffBar + 80), "r"((uint32_t)bad) : "memory");
        asm volatile("bar.arrive 11, 256;" ::: "memory");
    } else if (wg == 2) {
#pragma unroll
        for (int c = 0; c < 2; c++) {
            mbar_wait(bar_v(c), 0);
            bad_v |= chunk_incomplete(sbase + kOffWv + c * 24576);
        }
    }

    constexpr uint32_t dWm = ((sbase + kOffWm) >> 4) | (1u << 16);
    constexpr uint32_t dWv = ((sbase + kOffWv) >> 4) | (1u << 16);
    const float cs = 0.07216878364870322f * 1.4426950408889634f;
    mbar_wait(wg == 0 ? bar_m : bar_full, 0);

    uint4 hv[12];
    uint32_t pos;
    float acc[96];
    asm volatile("" : "+r"(win));
    uint32_t ticket = win - kNWG * G;
    float s[32];
    {
        const uint32_t dX = desc_x(wg_uniform());
        uint32_t fa[48];
        if (wg == 0) {
            uint32_t redo = 0;
            do {
                float ta[48], tb[48];
                wg_fence();
                Gemm1h<0, 0>::run(ta, dX, dWm);
                mbar_wait(bar_m + 8, 0);
                wg_fence();
                Gemm1h<1, 0>::run(tb, dX, dWm);
                mbar_wait(bar_m + 16, 0);
                wg_fence();
                Gemm1h<0, 1>::run(ta, dX, dWm);
                mbar_wait(bar_m + 24, 0);
                wg_fence();
                Gemm1h<1, 1>::run(tb, dX, dWm);
                mbar_wait(bar_m + 32, 0);
                wg_fence();
                Gemm1h<0, 2>::run(ta, dX, dWm);
                wg_commit();
                mbar_wait(bar_m + 40, 0);
                wg_fence();
                Gemm1h<1, 2>::run(tb, dX, dWm);
                wg_commit();
                wg_wait1();
                fence_regs(ta);
#pragma unroll
                for (int i = 0; i < 24; i++) fa[i] = pack_bf16(ta[2 * i], ta[2 * i + 1]);
#pragma unroll
                for (int i = 0; i < 24; i++) asm volatile("" : "+r"(fa[i])::"memory");
                wg_fence();
                Gemm2p<0, 5>::run(s, fa, dX);
                wg_commit();
                wg_wait1();
                fence_regs(tb);
#pragma unroll
                for (int i = 0; i < 24; i++) fa[24 + i] = pack_bf16(tb[2 * i], tb[2 * i + 1]);
#pragma unroll
                for (int i = 24; i < 48; i++) asm volatile("" : "+r"(fa[i])::"memory");
                wg_fence();
                Gemm2p<6, 11>::run(s, fa, dX);
                wg_commit();
                if (!redo) {
                    ring_pass();
                    asm volatile("bar.sync 11, 256;" ::: "memory");
                    asm volatile("ld.shared.u32 %0, [%1];" : "=r"(redo) : "r"(sbase + kOffBar + 80) : "memory");
                    publish(ticket, G);
                    asm volatile("bar.arrive 15, 256;" ::: "memory");
                } else {
                    redo = 0;
                }
                redo = __reduce_or_sync(0xffffffffu, redo);
                wg_wait0();
                fence_regs(s);
                fence_regs(fa);
            } while (redo);
        } else {
            ring_wait();
            wg_fence();
            Gemm1<0, 3>::run(acc, dX, dWm);
            if (wg == 2) {
                mbar_wait(bar_v(2), 0);
                bad_v |= chunk_incomplete(sbase + kOffWv + 2 * 24576);
            }
            const uint32_t bar_c1 = sbase + kOffBar + 72 + 16 * wg;
            mbar_wait(bar_c1, 0);
            wg_fence();
            Gemm1<4, 7>::run(acc, dX, dWm);
            mbar_wait(bar_c1 + 8, 0);
            wg_fence();
            Gemm1<8, 11>::run(acc, dX, dWm);
            wg_commit();
            if (wg == 2) bad_v = bar_or(3, 128, bad_v);
            if (!bad_v) asm volatile("bar.arrive 8, 256;" ::: "memory");
            if (warp == 5) {
                if (elect_one()) prefetch_x(&tmp, kNWG * G + blockIdx.x);
                __syncwarp();
            }
            if (!bad_v && (tid & 127) == 0) count_image(sc);
            wg_wait0();
            fence_regs(acc);
            if (bad_v) {
                repair_image(sbase + kOffWv, reinterpret_cast<const char*>(sc->wfold) + kWBytes, bar_w1, 1);
                asm volatile("bar.arrive 8, 256;" ::: "memory");
                if (tid == 256) count_image(sc);
            }
#pragma unroll
            for (int i = 0; i < 48; i++) fa[i] = pack_bf16(acc[2 * i], acc[2 * i + 1]);
            fence_regs(fa);
            wg_fence();
            ring_wait();
            Gemm2<11>::run(s, fa, dX);
            wg_commit();
            publish(ticket, G);
            asm volatile("bar.arrive 15, 256;" ::: "memory");
            wg_wait0();
            fence_regs(s);
            fence_regs(fa);
        }
        __syncwarp();
    }

    while (true) {
        uint32_t fa[48];
        uint32_t pa[16];
        {
            float a0[8], a1[8];
#pragma unroll
            for (int j = 0; j < 8; j++) { a0[j] = fmaxf(s[4 * j], s[4 * j + 1]); a1[j] = fmaxf(s[4 * j + 2], s[4 * j + 3]); }
#pragma unroll
            for (int d = 4; d > 0; d >>= 1)
#pragma unroll
                for (int j = 0; j < d; j++) { a0[j] = fmaxf(a0[j], a0[j + d]); a1[j] = fmaxf(a1[j], a1[j + d]); }
            float m0 = a0[0], m1 = a1[0];
            m0 = fmaxf(m0, __shfl_xor_sync(0xffffffffu, m0, 1));
            m1 = fmaxf(m1, __shfl_xor_sync(0xffffffffu, m1, 1));
            m0 = fmaxf(m0, __shfl_xor_sync(0xffffffffu, m0, 2));
            m1 = fmaxf(m1, __shfl_xor_sync(0xffffffffu, m1, 2));
            m0 *= cs; m1 *= cs;
            float l0 = 0.f, l1 = 0.f;
#pragma unroll
            for (int j = 0; j < 8; j++) {
                s[4 * j]     = ex2(fmaf(s[4 * j], cs, -m0));
                s[4 * j + 1] = ex2(fmaf(s[4 * j + 1], cs, -m0));
                s[4 * j + 2] = ex2(fmaf(s[4 * j + 2], cs, -m1));
                s[4 * j + 3] = ex2(fmaf(s[4 * j + 3], cs, -m1));
                l0 += s[4 * j] + s[4 * j + 1];
                l1 += s[4 * j + 2] + s[4 * j + 3];
            }
            l0 += __shfl_xor_sync(0xffffffffu, l0, 1);
            l1 += __shfl_xor_sync(0xffffffffu, l1, 1);
            l0 += __shfl_xor_sync(0xffffffffu, l0, 2);
            l1 += __shfl_xor_sync(0xffffffffu, l1, 2);
            const float r0 = rcp(l0), r1 = rcp(l1);
#pragma unroll
            for (int j = 0; j < 8; j++) {
                pa[2 * j]     = pack_bf16(s[4 * j] * r0, s[4 * j + 1] * r0);
                pa[2 * j + 1] = pack_bf16(s[4 * j + 2] * r1, s[4 * j + 3] * r1);
            }
        }

        const uint32_t wu = __reduce_or_sync(0xffffffffu, tid_now() >> 5);
        const uint32_t dXt = desc_xt(wu >> 2);
        if ((wu & 3) != 0) asm volatile("bar.sync %0, 128;" ::"r"((wu >> 2) + 4) : "memory");
        uint32_t pub;
        asm volatile("ld.shared.u32 %0, [%1];" : "=r"(pub) : "r"(sbase + kOffBar + 64 + 4 * (tid_now() >> 7)) : "memory");
        const int nxt = (int)__reduce_or_sync(0xffffffffu, pub);
        store_p_if(pa, nxt == (int)kDone + kNWG - 1);
        if (nxt == (int)kDone + kNWG - 1) {
            last_window(out, win);
            asm volatile("exit;");
            __builtin_unreachable();
        }
        fence_regs(pa);
        wg_fence();
        ring_wait();
        Gemm3<3>::run(acc, pa, dXt);
        wg_commit();
        if constexpr (PASS3 == 3) ring_pass();
        wg_wait0();
        fence_regs(acc);
        fence_regs(pa);

        if (((tid_now() >> 5) & 3) == 0) {
            asm volatile("bar.sync %0, 128;" ::"r"((tid_now() >> 7) + 1) : "memory");
            if (elect_one()) {
                const uint32_t wgl = tid_now() >> 7;
                const uint32_t bar = sbase + kOffBar + 8 * wgl;
                if (nxt < (int)kDone) {
                    mbar_expect_tx(bar, kXBytes);
                    tma_load_x_hint(sbase + kOffX + wgl * kXBytes, &tmx, bar, nxt & 4095, nxt >= kNWin - EF_LAST);
                    uint32_t again;
                    asm volatile("ld.volatile.shared.u32 %0, [%1];" : "=r"(again) : "r"(sbase + kOffBar + 64 + 4 * wgl) : "memory");
                    prefetch_ahead_of(&tmp, (int)again, G);
                }
            }
            __syncwarp();
        } else {
            asm volatile("bar.arrive %0, 128;" ::"r"((tid_now() >> 7) + 1) : "memory");
        }
#pragma unroll
        for (int i = 0; i < 48; i++) fa[i] = pack_bf16(acc[2 * i], acc[2 * i + 1]);

        asm volatile("{\n.reg .pred p;\nsetp.lt.s32 p, %5, 0;\n@p st.volatile.shared.v4.b32 [%4], {%0, %1, %2, %3};\n}\n"
                     :: "r"(fa[44]), "r"(fa[45]), "r"(fa[46]), "r"(fa[47]), "r"(sbase + kOffBar + 64), "r"(nxt) : "memory");
        fence_regs(fa);
        wg_fence();
        ring_wait();
        Gemm4<0, 1>::run(acc, fa, dWv);
        wg_commit();
        Gemm4<2, 10>::run(acc, fa, dWv);
        wg_commit();
        wg_wait1();
        uint32_t fl[4];
        uint32_t zero;
        asm volatile("ld.volatile.shared.u32 %0, [%1];" : "=r"(zero) : "r"(sbase + kOffBar + 76) : "memory");
#pragma unroll
        for (int i = 0; i < 4; i++) fl[i] = fa[44 + i] ^ zero;
        if constexpr (PASS4 == 10) ring_pass();
        wg_fence();
        wg192_rs<false, 0, koff(11, 24576)>(acc, fl, dWv);
        wg_commit();
        if constexpr (PASS4 == 11) ring_pass();
        pos = out_pos(win ^ zero);
        win = nxt | (~win & kPhase);
        const uint32_t dX = desc_x(__reduce_or_sync(0xffffffffu, (tid_now() >> 7) ^ zero));
        asm volatile("" : "+r"(pos) :: "memory");
        wg_wait0();
        fence_regs(acc);
        fence_regs(fa);
        fence_regs(fl);

#pragma unroll
        for (int a = 0; a < 6; a++) {
            hv[2 * a].x     = pack_bf16(acc[16 * a + 0], acc[16 * a + 1]);
            hv[2 * a].y     = pack_bf16(acc[16 * a + 4], acc[16 * a + 5]);
            hv[2 * a].z     = pack_bf16(acc[16 * a + 8], acc[16 * a + 9]);
            hv[2 * a].w     = pack_bf16(acc[16 * a + 12], acc[16 * a + 13]);
            hv[2 * a + 1].x = pack_bf16(acc[16 * a + 2], acc[16 * a + 3]);
            hv[2 * a + 1].y = pack_bf16(acc[16 * a + 6], acc[16 * a + 7]);
            hv[2 * a + 1].z = pack_bf16(acc[16 * a + 10], acc[16 * a + 11]);
            hv[2 * a + 1].w = pack_bf16(acc[16 * a + 14], acc[16 * a + 15]);
        }
        if (win < (int)kDone) mbar_wait(sbase + kOffBar + 8 * (tid_now() >> 7), (win >> 16) & 1);
        if (win >= (int)kDone) break;
        wg_fence();
        ring_wait();
        Gemm1<0, PASS1>::run(acc, dX, dWm);
        if constexpr (PASS1 < 11) {
            ring_pass();
            Gemm1<PASS1 + 1, 11>::run(acc, dX, dWm);
        }
        wg_commit();
        if constexpr (PASS1 == 11) ring_pass();
        ticket = draw_ticket(tickets, last_ticket);
        asm volatile("bar.sync 15, 256;" ::: "memory");
        stage_window<0>(hv, &tmo, pos, win);
        wg_wait0();
        fence_regs(acc);
#pragma unroll
        for (int i = 0; i < 48; i++) fa[i] = pack_bf16(acc[2 * i], acc[2 * i + 1]);

        fence_regs(fa);
        wg_fence();
        ring_wait();
        Gemm2<11>::run(s, fa, dX);
        wg_commit();
        if constexpr (PASS2 == 11) ring_pass();
        publish(ticket, G);
        asm volatile("cp.async.bulk.wait_group.read 0;" ::: "memory");
        asm volatile("bar.arrive 15, 256;" ::: "memory");
        wg_wait0();
        fence_regs(s);
        fence_regs(fa);
    }
    if ((win & 3) == 0) {
        const uint32_t buf = sbase + kOffX + (tid_now() >> 7) * kXBytes + ((tid_now() >> 5) & 3) * 2048;
        asm volatile("bar.sync %0, 128;" ::"r"((tid_now() >> 7) + 1) : "memory");
        ring_wait();
        ring_pass();
        stage_put<0>(hv, buf);
        stage_send(&tmo, pos, 0, buf);
        stage_put<1>(hv, buf + 8192);
        stage_send(&tmo, pos, 1, buf + 8192);
        stage_put<2>(hv, buf + 2 * 8192);
        stage_send(&tmo, pos, 2, buf + 2 * 8192);
        clear_images(sc);
        asm volatile("bar.sync 15, 256;" ::: "memory");
        stage_wait();
    } else {
        uint8_t* hptr = out_address(out, pos);
        store_tail<0>(hv, hptr, clock_now());
    }
}

typedef CUresult (*EncodeTiledFn)(CUtensorMap*, CUtensorMapDataType, cuuint32_t, void*, const cuuint64_t*,
                                  const cuuint64_t*, const cuuint32_t*, const cuuint32_t*, CUtensorMapInterleave,
                                  CUtensorMapSwizzle, CUtensorMapL2promotion, CUtensorMapFloatOOBfill);

}

extern "C" void kernel_launch(void* const* d_in, const int* in_sizes, int n_in, void* d_out, int out_size) {
    (void)in_sizes; (void)n_in; (void)out_size;
    const __nv_bfloat16* x    = (const __nv_bfloat16*)d_in[0];
    const __nv_bfloat16* wqkv = (const __nv_bfloat16*)d_in[1];
    const __nv_bfloat16* wo   = (const __nv_bfloat16*)d_in[2];

    static EncodeTiledFn encode = nullptr;
    static int num_sms = 0;
    static void* scratch = nullptr;
    if (!encode) {
        void* fn = nullptr;
        cudaDriverEntryPointQueryResult qr;
        cudaGetDriverEntryPoint("cuTensorMapEncodeTiled", &fn, cudaEnableDefault, &qr);
        encode = (EncodeTiledFn)fn;
        int dev = 0;
        cudaGetDevice(&dev);
        cudaDeviceGetAttribute(&num_sms, cudaDevAttrMultiProcessorCount, dev);
        if (num_sms > kNWin / 16) num_sms = kNWin / 16;
        cudaGetSymbolAddress(&scratch, g_scratch);
        cudaFuncSetAttribute(swin_attn_kernel<false>, cudaFuncAttributeMaxDynamicSharedMemorySize, kSmemBytes);
        cudaFuncSetAttribute(swin_attn_kernel<true>, cudaFuncAttributeMaxDynamicSharedMemorySize, kSmemBytes);
    }
    CUtensorMap tmx;
    const cuuint64_t gdim[5] = {(cuuint64_t)kC, (cuuint64_t)kHW / 2, 2, 2, (cuuint64_t)kHW / 2};
    const cuuint64_t gstr[4] = {(cuuint64_t)kC * 4, (cuuint64_t)kHW * kC * 2, (cuuint64_t)kC * 2, (cuuint64_t)kHW * kC * 4};
    const cuuint32_t box[5] = {64, 4, 2, 2, 4};
    const cuuint32_t estr[5] = {1, 1, 1, 1, 1};
    encode(&tmx, CU_TENSOR_MAP_DATA_TYPE_BFLOAT16, 5, (void*)x, gdim, gstr, box, estr, CU_TENSOR_MAP_INTERLEAVE_NONE,
           CU_TENSOR_MAP_SWIZZLE_128B, CU_TENSOR_MAP_L2_PROMOTION_NONE, CU_TENSOR_MAP_FLOAT_OOB_FILL_NONE);

    CUtensorMap tmp;
    const cuuint64_t pdim[3] = {(cuuint64_t)kC, (cuuint64_t)kHW, (cuuint64_t)kHW};
    const cuuint64_t pstr[2] = {(cuuint64_t)kC * 2, (cuuint64_t)kHW * kC * 2};
    const cuuint32_t pbox[3] = {(cuuint32_t)kC, 8, 8};
    encode(&tmp, CU_TENSOR_MAP_DATA_TYPE_BFLOAT16, 3, (void*)x, pdim, pstr, pbox, estr, CU_TENSOR_MAP_INTERLEAVE_NONE,
           CU_TENSOR_MAP_SWIZZLE_NONE, CU_TENSOR_MAP_L2_PROMOTION_NONE, CU_TENSOR_MAP_FLOAT_OOB_FILL_NONE);
    CUtensorMap tmo;
    const cuuint64_t odim[5] = {64, 6, (cuuint64_t)kHW / 4, 2, (cuuint64_t)kHW};
    const cuuint64_t ostr[4] = {128, (cuuint64_t)kC * 8, (cuuint64_t)kC * 4, (cuuint64_t)kHW * kC * 2};
    const cuuint32_t obox[5] = {64, 2, 2, 2, 2};
    encode(&tmo, CU_TENSOR_MAP_DATA_TYPE_BFLOAT16, 5, d_out, odim, ostr, obox, estr, CU_TENSOR_MAP_INTERLEAVE_NONE,
           CU_TENSOR_MAP_SWIZZLE_128B, CU_TENSOR_MAP_L2_PROMOTION_NONE, CU_TENSOR_MAP_FLOAT_OOB_FILL_NONE);
    if (num_sms >= kJobs)
        swin_attn_kernel<false><<<num_sms, kThreads, kSmemBytes, cudaStreamPerThread>>>(wqkv, wo, x, (Scratch*)scratch, ((Scratch*)scratch)->ticket, num_sms, TRK_HOST, (__nv_bfloat16*)d_out, kNWin + SHARED_HOST - 1 - kNWG * num_sms, tmx, tmp, tmo);
    else
        swin_attn_kernel<true><<<num_sms, kThreads, kSmemBytes, cudaStreamPerThread>>>(wqkv, wo, x, (Scratch*)scratch, ((Scratch*)scratch)->ticket, num_sms, TRK_HOST, (__nv_bfloat16*)d_out, kNWin + SHARED_HOST - 1 - kNWG * num_sms, tmx, tmp, tmo);
}
```
